```python
import torch

def _softmax(x, axis=-1):
    return torch.softmax(x, dim=axis)
def _gelu(x):
    return torch.nn.functional.gelu(x, approximate="tanh")
def _silu(x):
    return torch.nn.functional.silu(x)
def _sigmoid(x):
    return torch.sigmoid(x)
def _layernorm(x, axis=-1, eps=1e-5):
    m = x.mean(dim=axis, keepdim=True)
    v = x.var(dim=axis, keepdim=True, unbiased=False)
    return (x - m) / torch.sqrt(v + eps)
def _scatter_add(tgt, idx, src, axis=0):
    return tgt.clone().index_add_(axis, idx, src)
def _segment_sum(src, seg, n):
    out = torch.zeros((n,) + src.shape[1:], dtype=src.dtype)
    return out.index_add_(0, seg, src)
def _pad(x, pw):
    flat = tuple(v for pair in reversed(pw) for v in pair)
    return torch.nn.functional.pad(x, flat)

kernel_name = 'interleave_layers__sliding_local_dilated__softmax_full_mha__prompt'

def setup_inputs():

    _w = (lambda a: (lambda t: t.to(torch.bfloat16) if t.is_floating_point() else t)(torch.as_tensor(a)))
    def _A_setup():
        B, S, D = 1, 2048, 1024
        return {
            "x": _w((lambda *s: torch.randn(*s, dtype=torch.bfloat16) * 0.05)(B, S, D)),
            "wqkv": _w((lambda *s: torch.randn(*s, dtype=torch.bfloat16) * 0.05)(D, 3 * D)),
            "wo": _w((lambda *s: torch.randn(*s, dtype=torch.bfloat16) * 0.05)(D, D)),
        }
    _A_in = _A_setup()

    def _B_setup():
        B, S, D = 1, 2048, 1024
        return {
            "x": _w((lambda *s: torch.randn(*s, dtype=torch.bfloat16) * 0.05)(B, S, D)),
            "wqkv": _w((lambda *s: torch.randn(*s, dtype=torch.bfloat16) * 0.05)(D, 3 * D)),
            "wo": _w((lambda *s: torch.randn(*s, dtype=torch.bfloat16) * 0.05)(D, D)),
        }
    _B_in = _B_setup()

    return {
        "A_x": _A_in["x"],
        "A_wqkv": _A_in["wqkv"],
        "A_wo": _A_in["wo"],
        "B_x": _B_in["x"],
        "B_wqkv": _B_in["wqkv"],
        "B_wo": _B_in["wo"],
    }

def reference(A_x, A_wqkv, A_wo, B_x, B_wqkv, B_wo):
    def _A_ref(x, wqkv, wo):
        B, S, D = x.shape
        H = 32; Dh = D // H
        W, dil = 8, 2
        qkv = (lambda x, *d: x.permute(*d))((x @ wqkv).reshape(B, S, 3, H, Dh), 2, 0, 3, 1, 4)
        q, k, v = qkv[0], qkv[1], qkv[2]
        scale = Dh ** -0.5
        pos = torch.arange(S)
        off = torch.arange(W) * dil
        idx = pos[:, None] - off[None, :]
        mask = idx >= 0
        idx_c = torch.where(mask, idx, 0).reshape(-1)
        kg = k[:, :, idx_c, :].reshape(B, H, S, W, Dh)
        vg = v[:, :, idx_c, :].reshape(B, H, S, W, Dh)
        logits = torch.einsum("bhsd,bhswd->bhsw", q, kg) * scale
        logits = torch.where(mask[None, None, :, :], logits, -1e9)
        attn = _softmax(logits, axis=-1)
        o = torch.einsum("bhsw,bhswd->bhsd", attn, vg)
        return (lambda x, *d: x.permute(*d))(o, 0, 2, 1, 3).reshape(B, S, D) @ wo

    def _B_ref(x, wqkv, wo):
        B, S, D = x.shape
        H = 32; Dh = D // H
        qkv = (lambda x, *d: x.permute(*d))((x @ wqkv).reshape(B, S, 3, H, Dh), 2, 0, 3, 1, 4)
        q, k, v = qkv[0], qkv[1], qkv[2]
        scale = Dh ** -0.5
        scores = torch.einsum("bhqd,bhkd->bhqk", q, k) * scale
        p = _softmax(scores, axis=-1)
        o = torch.einsum("bhqk,bhkd->bhqd", p, v)
        return (lambda x, *d: x.permute(*d))(o, 0, 2, 1, 3).reshape(B, S, D) @ wo

    x = A_x
    x = x + _A_ref(_layernorm(x, axis=-1), A_wqkv, A_wo)
    x = x + _B_ref(_layernorm(x, axis=-1), B_wqkv, B_wo)
    x = x + _A_ref(_layernorm(x, axis=-1), A_wqkv, A_wo)
    x = x + _B_ref(_layernorm(x, axis=-1), B_wqkv, B_wo)
    return x
```

```cpp
#include <cuda_runtime.h>
#include <cuda_bf16.h>
#include <cuda.h>
#include <stdint.h>

typedef __nv_bfloat16 bf16;

__device__ __forceinline__ void wgmma_m64n192k16_ss_tb(float (&d)[96], uint64_t da, uint64_t db, int scale_d) {
  asm volatile("{\n.reg .pred p;\nsetp.ne.b32 p, %98, 0;\n"
    "wgmma.mma_async.sync.aligned.m64n192k16.f32.bf16.bf16 "
    "{%0, %1, %2, %3, %4, %5, %6, %7, %8, %9, %10, %11, %12, %13, %14, %15, "
    "%16, %17, %18, %19, %20, %21, %22, %23, %24, %25, %26, %27, %28, %29, %30, %31, "
    "%32, %33, %34, %35, %36, %37, %38, %39, %40, %41, %42, %43, %44, %45, %46, %47, "
    "%48, %49, %50, %51, %52, %53, %54, %55, %56, %57, %58, %59, %60, %61, %62, %63, "
    "%64, %65, %66, %67, %68, %69, %70, %71, %72, %73, %74, %75, %76, %77, %78, %79, "
    "%80, %81, %82, %83, %84, %85, %86, %87, %88, %89, %90, %91, %92, %93, %94, %95}, "
    "%96, %97, p, 1, 1, 0, 1;\n}\n"
    : "+f"(d[0]), "+f"(d[1]), "+f"(d[2]), "+f"(d[3]), "+f"(d[4]), "+f"(d[5]), "+f"(d[6]), "+f"(d[7]),
      "+f"(d[8]), "+f"(d[9]), "+f"(d[10]), "+f"(d[11]), "+f"(d[12]), "+f"(d[13]), "+f"(d[14]), "+f"(d[15]),
      "+f"(d[16]), "+f"(d[17]), "+f"(d[18]), "+f"(d[19]), "+f"(d[20]), "+f"(d[21]), "+f"(d[22]), "+f"(d[23]),
      "+f"(d[24]), "+f"(d[25]), "+f"(d[26]), "+f"(d[27]), "+f"(d[28]), "+f"(d[29]), "+f"(d[30]), "+f"(d[31]),
      "+f"(d[32]), "+f"(d[33]), "+f"(d[34]), "+f"(d[35]), "+f"(d[36]), "+f"(d[37]), "+f"(d[38]), "+f"(d[39]),
      "+f"(d[40]), "+f"(d[41]), "+f"(d[42]), "+f"(d[43]), "+f"(d[44]), "+f"(d[45]), "+f"(d[46]), "+f"(d[47]),
      "+f"(d[48]), "+f"(d[49]), "+f"(d[50]), "+f"(d[51]), "+f"(d[52]), "+f"(d[53]), "+f"(d[54]), "+f"(d[55]),
      "+f"(d[56]), "+f"(d[57]), "+f"(d[58]), "+f"(d[59]), "+f"(d[60]), "+f"(d[61]), "+f"(d[62]), "+f"(d[63]),
      "+f"(d[64]), "+f"(d[65]), "+f"(d[66]), "+f"(d[67]), "+f"(d[68]), "+f"(d[69]), "+f"(d[70]), "+f"(d[71]),
      "+f"(d[72]), "+f"(d[73]), "+f"(d[74]), "+f"(d[75]), "+f"(d[76]), "+f"(d[77]), "+f"(d[78]), "+f"(d[79]),
      "+f"(d[80]), "+f"(d[81]), "+f"(d[82]), "+f"(d[83]), "+f"(d[84]), "+f"(d[85]), "+f"(d[86]), "+f"(d[87]),
      "+f"(d[88]), "+f"(d[89]), "+f"(d[90]), "+f"(d[91]), "+f"(d[92]), "+f"(d[93]), "+f"(d[94]), "+f"(d[95])
    : "l"(da), "l"(db), "r"(scale_d));
}

__device__ __forceinline__ void wgmma_m64n128k16_ss_tb(float (&d)[64], uint64_t da, uint64_t db, int scale_d) {
  asm volatile("{\n.reg .pred p;\nsetp.ne.b32 p, %66, 0;\n"
    "wgmma.mma_async.sync.aligned.m64n128k16.f32.bf16.bf16 "
    "{%0, %1, %2, %3, %4, %5, %6, %7, %8, %9, %10, %11, %12, %13, %14, %15, "
    "%16, %17, %18, %19, %20, %21, %22, %23, %24, %25, %26, %27, %28, %29, %30, %31, "
    "%32, %33, %34, %35, %36, %37, %38, %39, %40, %41, %42, %43, %44, %45, %46, %47, "
    "%48, %49, %50, %51, %52, %53, %54, %55, %56, %57, %58, %59, %60, %61, %62, %63}, "
    "%64, %65, p, 1, 1, 0, 1;\n}\n"
    : "+f"(d[0]), "+f"(d[1]), "+f"(d[2]), "+f"(d[3]), "+f"(d[4]), "+f"(d[5]), "+f"(d[6]), "+f"(d[7]),
      "+f"(d[8]), "+f"(d[9]), "+f"(d[10]), "+f"(d[11]), "+f"(d[12]), "+f"(d[13]), "+f"(d[14]), "+f"(d[15]),
      "+f"(d[16]), "+f"(d[17]), "+f"(d[18]), "+f"(d[19]), "+f"(d[20]), "+f"(d[21]), "+f"(d[22]), "+f"(d[23]),
      "+f"(d[24]), "+f"(d[25]), "+f"(d[26]), "+f"(d[27]), "+f"(d[28]), "+f"(d[29]), "+f"(d[30]), "+f"(d[31]),
      "+f"(d[32]), "+f"(d[33]), "+f"(d[34]), "+f"(d[35]), "+f"(d[36]), "+f"(d[37]), "+f"(d[38]), "+f"(d[39]),
      "+f"(d[40]), "+f"(d[41]), "+f"(d[42]), "+f"(d[43]), "+f"(d[44]), "+f"(d[45]), "+f"(d[46]), "+f"(d[47]),
      "+f"(d[48]), "+f"(d[49]), "+f"(d[50]), "+f"(d[51]), "+f"(d[52]), "+f"(d[53]), "+f"(d[54]), "+f"(d[55]),
      "+f"(d[56]), "+f"(d[57]), "+f"(d[58]), "+f"(d[59]), "+f"(d[60]), "+f"(d[61]), "+f"(d[62]), "+f"(d[63])
    : "l"(da), "l"(db), "r"(scale_d));
}

__device__ __forceinline__ void wgmma_m64n32k16_rs_nb_h(float (&d)[16], uint32_t a0, uint32_t a1, uint32_t a2, uint32_t a3, uint64_t db, int scale_d) {
  asm volatile("{\n.reg .pred p;\nsetp.ne.b32 p, %21, 0;\n"
    "wgmma.mma_async.sync.aligned.m64n32k16.f32.f16.f16 "
    "{%0, %1, %2, %3, %4, %5, %6, %7, %8, %9, %10, %11, %12, %13, %14, %15}, "
    "{%16, %17, %18, %19}, %20, p, 1, 1, 0;\n}\n"
    : "+f"(d[0]), "+f"(d[1]), "+f"(d[2]), "+f"(d[3]), "+f"(d[4]), "+f"(d[5]), "+f"(d[6]), "+f"(d[7]),
      "+f"(d[8]), "+f"(d[9]), "+f"(d[10]), "+f"(d[11]), "+f"(d[12]), "+f"(d[13]), "+f"(d[14]), "+f"(d[15])
    : "r"(a0), "r"(a1), "r"(a2), "r"(a3), "l"(db), "r"(scale_d));
}

__device__ __forceinline__ void wgmma_m64n32k16_rs_nb_hh(uint32_t (&d)[8], uint32_t a0, uint32_t a1, uint32_t a2, uint32_t a3, uint64_t db, int scale_d) {
  asm volatile("{\n.reg .pred p;\nsetp.ne.b32 p, %13, 0;\n"
    "wgmma.mma_async.sync.aligned.m64n32k16.f16.f16.f16 "
    "{%0, %1, %2, %3, %4, %5, %6, %7}, "
    "{%8, %9, %10, %11}, %12, p, 1, 1, 0;\n}\n"
    : "+r"(d[0]), "+r"(d[1]), "+r"(d[2]), "+r"(d[3]), "+r"(d[4]), "+r"(d[5]), "+r"(d[6]), "+r"(d[7])
    : "r"(a0), "r"(a1), "r"(a2), "r"(a3), "l"(db), "r"(scale_d));
}

__device__ __forceinline__ void wgmma_m64n40k16_rs_tb(float (&d)[20], uint32_t a0, uint32_t a1, uint32_t a2, uint32_t a3, uint64_t db, int scale_d) {
  asm volatile("{\n.reg .pred p;\nsetp.ne.b32 p, %25, 0;\n"
    "wgmma.mma_async.sync.aligned.m64n40k16.f32.bf16.bf16 "
    "{%0, %1, %2, %3, %4, %5, %6, %7, %8, %9, %10, %11, %12, %13, %14, %15, "
    "%16, %17, %18, %19}, "
    "{%20, %21, %22, %23}, %24, p, 1, 1, 1;\n}\n"
    : "+f"(d[0]), "+f"(d[1]), "+f"(d[2]), "+f"(d[3]), "+f"(d[4]), "+f"(d[5]), "+f"(d[6]), "+f"(d[7]),
      "+f"(d[8]), "+f"(d[9]), "+f"(d[10]), "+f"(d[11]), "+f"(d[12]), "+f"(d[13]), "+f"(d[14]), "+f"(d[15]),
      "+f"(d[16]), "+f"(d[17]), "+f"(d[18]), "+f"(d[19])
    : "r"(a0), "r"(a1), "r"(a2), "r"(a3), "l"(db), "r"(scale_d));
}

#define DEVINL __device__ __forceinline__
DEVINL void wg_fence() { asm volatile("wgmma.fence.sync.aligned;" ::: "memory"); }
DEVINL void wg_commit() { asm volatile("wgmma.commit_group.sync.aligned;" ::: "memory"); }
template <int N> DEVINL void wg_wait() { asm volatile("wgmma.wait_group.sync.aligned %0;" ::"n"(N) : "memory"); }
DEVINL uint64_t mkdesc(uint32_t addr, uint32_t lbo, uint32_t sbo, int sw) {
  return (uint64_t)((addr & 0x3FFFF) >> 4) | ((uint64_t)(lbo >> 4) << 16) | ((uint64_t)(sbo >> 4) << 32) | ((uint64_t)sw << 62);
}
DEVINL void mbar_init(uint32_t bar, uint32_t cnt) { asm volatile("mbarrier.init.shared::cta.b64 [%0], %1;" ::"r"(bar), "r"(cnt) : "memory"); }
DEVINL void mbar_arrive(uint32_t bar) { asm volatile("mbarrier.arrive.shared::cta.b64 _, [%0];" ::"r"(bar) : "memory"); }
DEVINL bool mbar_try(uint32_t bar, uint32_t parity) {
  uint32_t ok;
  asm volatile("{\n.reg .pred p;\nmbarrier.try_wait.parity.shared::cta.b64 p, [%1], %2;\nselp.u32 %0, 1, 0, p;\n}" : "=r"(ok) : "r"(bar), "r"(parity) : "memory");
  return ok;
}
DEVINL bool mbar_test(uint32_t bar, uint32_t parity) {
  uint32_t ok;
  asm volatile("{\n.reg .pred p;\nmbarrier.test_wait.parity.shared::cta.b64 p, [%1], %2;\nselp.u32 %0, 1, 0, p;\n}" : "=r"(ok) : "r"(bar), "r"(parity) : "memory");
  return ok;
}
DEVINL void mbar_hint(uint32_t bar, uint32_t parity) {
#pragma unroll 1
  for (uint32_t n = 0; n < 16u; n++) if (mbar_try(bar, parity)) break;
}
DEVINL void mbar_wait(uint32_t bar, uint32_t parity) {
#pragma unroll 1
  for (uint32_t n = 0; n < 100000u; n++) if (mbar_try(bar, parity)) break;
}
#define EL(txt) "{\n.reg .pred pe;\nelect.sync _|pe, 0xffffffff;\n@pe " txt "\n}"
DEVINL void e_expect_tx(uint32_t bar, uint32_t bytes) { asm volatile(EL("mbarrier.arrive.expect_tx.shared::cta.b64 _, [%0], %1;") ::"r"(bar), "r"(bytes) : "memory"); }
DEVINL void e_arrive(uint32_t bar) { asm volatile(EL("mbarrier.arrive.shared::cta.b64 _, [%0];") ::"r"(bar) : "memory"); }
DEVINL void e_red(uint32_t* p) { asm volatile(EL("red.release.gpu.global.add.u32 [%0], 1;") ::"l"(p) : "memory"); }
DEVINL void e_red_relaxed(uint32_t* p) { asm volatile(EL("red.relaxed.gpu.global.add.u32 [%0], 1;") ::"l"(p) : "memory"); }
DEVINL void tma_ld(uint32_t dst, const CUtensorMap* m, int c0, int c1, uint32_t bar) {
  asm volatile(EL("cp.async.bulk.tensor.2d.shared::cluster.global.mbarrier::complete_tx::bytes [%0], [%1, {%3, %4}], [%2];")
               ::"r"(dst), "l"(m), "r"(bar), "r"(c0), "r"(c1) : "memory");
}
DEVINL void tma_ld3(uint32_t dst, const CUtensorMap* m, int c0, int c1, int c2, uint32_t bar) {
  asm volatile(EL("cp.async.bulk.tensor.3d.shared::cluster.global.mbarrier::complete_tx::bytes [%0], [%1, {%3, %4, %5}], [%2];")
               ::"r"(dst), "l"(m), "r"(bar), "r"(c0), "r"(c1), "r"(c2) : "memory");
}
DEVINL void tma_ld5(uint32_t dst, const CUtensorMap* m, int c2, int c3, int c4, uint32_t bar) {
  asm volatile(EL("cp.async.bulk.tensor.5d.shared::cluster.global.mbarrier::complete_tx::bytes [%0], [%1, {0, 0, %3, %4, %5}], [%2];")
               ::"r"(dst), "l"(m), "r"(bar), "r"(c2), "r"(c3), "r"(c4) : "memory");
}
DEVINL void tma_ld_mc(uint32_t dst, const CUtensorMap* m, int c0, int c1, uint32_t bar) {
  asm volatile(EL("cp.async.bulk.tensor.2d.shared::cluster.global.mbarrier::complete_tx::bytes.multicast::cluster [%0], [%1, {%3, %4}], [%2], %5;")
               ::"r"(dst), "l"(m), "r"(bar), "r"(c0), "r"(c1), "h"((uint16_t)3) : "memory");
}
DEVINL void e_arrive_both(uint32_t bar) {
  asm volatile("{\n.reg .pred pe;\n.reg .b32 r0, r1;\nelect.sync _|pe, 0xffffffff;\nmapa.shared::cluster.u32 r0, %0, 0;\nmapa.shared::cluster.u32 r1, %0, 1;\n"
               "@pe mbarrier.arrive.shared::cluster.b64 _, [r0];\n@pe mbarrier.arrive.shared::cluster.b64 _, [r1];\n}" ::"r"(bar) : "memory");
}
DEVINL void tma_st(const CUtensorMap* m, int c0, int c1, uint32_t src) {
  asm volatile(EL("cp.async.bulk.tensor.2d.global.shared::cta.bulk_group [%0, {%2, %3}], [%1];") ::"l"(m), "r"(src), "r"(c0), "r"(c1) : "memory");
}
DEVINL void bulk_commit() { asm volatile("cp.async.bulk.commit_group;" ::: "memory"); }
template <int N> DEVINL void bulk_wait_n() { asm volatile("cp.async.bulk.wait_group %0;\nbar.warp.sync 0xffffffff;" ::"n"(N) : "memory"); }
DEVINL void l2_prefetch(const void* g, uint32_t bytes) { asm volatile(EL("cp.async.bulk.prefetch.L2.global [%0], %1;") ::"l"(g), "r"(bytes) : "memory"); }
DEVINL void fence_async_smem() { asm volatile("fence.proxy.async.shared::cta;" ::: "memory"); }
DEVINL void fence_async_gl() { asm volatile("fence.proxy.async.global;" ::: "memory"); }
DEVINL void cluster_wait() { asm volatile("barrier.cluster.wait.aligned;" ::: "memory"); }
DEVINL void bar_sync(int id, int n) { asm volatile("bar.sync %0, %1;" ::"r"(id), "r"(n) : "memory"); }
DEVINL void bar_arrive(int id, int n) { asm volatile("bar.arrive %0, %1;" ::"r"(id), "r"(n) : "memory"); }
DEVINL uint32_t ld_acquire(const uint32_t* p) { uint32_t v; asm volatile("ld.acquire.gpu.global.u32 %0, [%1];" : "=r"(v) : "l"(p) : "memory"); return v; }
DEVINL void watch(const uint32_t* p, uint32_t target, uint32_t all, uint32_t tag, uint32_t slot) {
  uint32_t seen = 0;
#pragma unroll 1
  for (uint32_t n = 0; n < 200000u && seen != all; n++) {
    const uint32_t m = __ballot_sync(~0u, (int)(ld_acquire(p) - target) >= 0) & all;
    if (m != seen) { seen = m; asm volatile("st.release.cta.shared.u32 [%0], %1;" ::"r"(slot), "r"(tag << 16 | m) : "memory"); }
  }
}
template <bool RELAXED = false> DEVINL void await_bit(uint32_t slot, uint32_t tag, int j, uint32_t& rdy) {
  if ((rdy >> j) & 1) return;
#pragma unroll 1
  for (uint32_t n = 0; n < 8000000u; n++) {
    uint32_t v;
    asm volatile("ld.acquire.cta.shared.u32 %0, [%1];" : "=r"(v) : "r"(slot) : "memory");
    if ((v >> 16) == tag && ((v >> j) & 1)) { rdy = v; break; }
    if (RELAXED) __nanosleep(200);
  }
  asm volatile("fence.proxy.async.global;" ::: "memory");
}
DEVINL void poll_ge(const uint32_t* p, uint32_t target) {
#pragma unroll 1
  for (uint32_t n = 0; n < 200000u; n++) if (__all_sync(~0u, (int)(ld_acquire(p) - target) >= 0)) break;
}
DEVINL int lane_id() { int v; asm volatile("mov.u32 %0, %%laneid;" : "=r"(v)); return v; }
__host__ DEVINL int remap(int v) {
  const int c = v >> 1, u = c - 36, r = (u * 37) >> 8;
  const int L = c < 4 ? 32 + 8 * c : c < 36 ? c - 4 : 33 + u + r;
  return 2 * L + (v & 1);
}
DEVINL int block_id() { int v; asm volatile("mov.u32 %0, %%ctaid.x;" : "=r"(v)); return v; }
#define cta_id() prm.map[block_id()]
#define IDS() const int lane = lane_id(), b = cta_id(), bm = b >> 4, bn = b & 15, rank = b & 1, pm = 2 * bm + (bn >> 3), pn = bn & 7, po = pm & 1; \
  (void)lane; (void)bm; (void)bn; (void)rank; (void)pm; (void)pn; (void)po
DEVINL void st_tagged(unsigned long long* p, uint32_t v, uint32_t tag) {
  asm volatile("{\n.reg .b64 t;\nmov.b64 t, {%1, %2};\nst.relaxed.gpu.global.b64 [%0], t;\n}" ::"l"(p), "r"(v), "r"(tag) : "memory");
}
DEVINL float ex2(float x) { float y; asm("ex2.approx.ftz.f32 %0, %1;" : "=f"(y) : "f"(x)); return y; }
DEVINL float rcp(float x) { float y; asm("rcp.approx.ftz.f32 %0, %1;" : "=f"(y) : "f"(x)); return y; }
DEVINL uint32_t pack2(float lo, float hi) { uint32_t r; asm("cvt.rn.bf16x2.f32 %0, %1, %2;" : "=r"(r) : "f"(hi), "f"(lo)); return r; }
DEVINL float bf_lo(uint32_t w) { return __uint_as_float(w << 16); }
DEVINL float bf_hi(uint32_t w) { return __uint_as_float(w & 0xFFFF0000u); }
DEVINL float bf_round(float x) { return bf_lo(pack2(x, 0.f)); }
DEVINL uint32_t add_bf16x2(uint32_t a, uint32_t b) { uint32_t r; asm("add.rn.bf16x2 %0, %1, %2;" : "=r"(r) : "r"(a), "r"(b)); return r; }
DEVINL void stsm4(uint32_t addr, uint32_t a, uint32_t b, uint32_t c, uint32_t d) {
  asm volatile("stmatrix.sync.aligned.m8n8.x4.shared.b16 [%0], {%1, %2, %3, %4};" ::"r"(addr), "r"(a), "r"(b), "r"(c), "r"(d) : "memory");
}
DEVINL void ldsm4(uint32_t addr, uint32_t (&r)[4]) {
  asm volatile("ldmatrix.sync.aligned.m8n8.x4.shared.b16 {%0, %1, %2, %3}, [%4];" : "=r"(r[0]), "=r"(r[1]), "=r"(r[2]), "=r"(r[3]) : "r"(addr) : "memory");
}
DEVINL void ldsm4t(uint32_t addr, uint32_t (&r)[4]) {
  asm volatile("ldmatrix.sync.aligned.m8n8.x4.trans.shared.b16 {%0, %1, %2, %3}, [%4];" : "=r"(r[0]), "=r"(r[1]), "=r"(r[2]), "=r"(r[3]) : "r"(addr) : "memory");
}
DEVINL void sts128(uint32_t addr, uint32_t a, uint32_t b, uint32_t c, uint32_t d) {
  asm volatile("st.shared.v4.b32 [%0], {%1, %2, %3, %4};" ::"r"(addr), "r"(a), "r"(b), "r"(c), "r"(d) : "memory");
}
DEVINL float2 lds64f(uint32_t addr) { float2 v; asm volatile("ld.shared.v2.f32 {%0, %1}, [%2];" : "=f"(v.x), "=f"(v.y) : "r"(addr) : "memory"); return v; }
DEVINL void mma16816(float (&d)[4], uint32_t a0, uint32_t a1, uint32_t a2, uint32_t a3, uint32_t b0, uint32_t b1) {
  asm("mma.sync.aligned.m16n8k16.row.col.f32.bf16.bf16.f32 {%0, %1, %2, %3}, {%4, %5, %6, %7}, {%8, %9}, {%0, %1, %2, %3};"
               : "+f"(d[0]), "+f"(d[1]), "+f"(d[2]), "+f"(d[3]) : "r"(a0), "r"(a1), "r"(a2), "r"(a3), "r"(b0), "r"(b1));
}
template <int N> DEVINL void fence_regs(uint32_t (&d)[N]) {
#pragma unroll
  for (int i = 0; i < N; i++) asm volatile("" : "+r"(d[i])::"memory");
}
template <int N> DEVINL void fence_regs(float (&d)[N]) {
#pragma unroll
  for (int i = 0; i < N; i++) asm volatile("" : "+f"(d[i])::"memory");
}

__device__ __align__(1024) bf16 g_xs[2048 * 1024];
__device__ __align__(1024) bf16 g_os[2048 * 1024];
__device__ __align__(1024) bf16 g_k[32 * 2048 * 32];
__device__ __align__(1024) bf16 g_v[32 * 2048 * 32];
__device__ __align__(128) float2 g_stats[8 * 2048];
__device__ __align__(16) float g_csp[2 * 16 * 8 * 192];
__device__ __align__(128) float g_kn[2 * 128 * 16];
__device__ unsigned long long g_halo[2 * 128 * 32 * 32];
__device__ __align__(128) uint32_t g_cnt[256 * 32];
__device__ uint32_t g_epoch;

DEVINL uint32_t* cnt_x(int l, int bm) { return g_cnt + (l * 8 + bm) * 32; }
DEVINL uint32_t* cnt_o(int l, int pm, int h) { return g_cnt + (32 + (l * 16 + pm) * 2 + h) * 32; }
DEVINL uint32_t* cnt_kv(int lb, int bn) { return g_cnt + (160 + lb * 16 + bn) * 32; }
DEVINL uint32_t* cnt_ad(int bn) { return g_cnt + (192 + bn) * 32; }
DEVINL uint32_t* cnt_cs(int t, int bn) { return g_cnt + (208 + t * 16 + bn) * 32; }

DEVINL int qord(int i, int l, int pn) { return l == 0 ? i : i < 4 ? ((2 * pn) ^ (i & 2)) + (i & 1) : i - 4 < 2 * (pn & 6) ? i - 4 : i; }
struct Params {
  CUtensorMap m[15];
  const bf16* x0;
  const bf16* wq[2];
  uint32_t zero;
  int map[128];
};
enum { M_X0A = 0, M_XSA, M_WQA, M_WQB, M_WOA, M_WOB, M_OS, M_K, M_V, M_X0R, M_XSR, M_XSO, M_OUT, M_XST, M_X0H, M_COUNT };

constexpr uint32_t QSTG = 57344;
constexpr uint32_t T0 = 65536, TSTG = 32768;
constexpr uint32_t ONES = 230400;
constexpr uint32_t PSTG = 32768, RES = 196608;
constexpr uint32_t KSC = 98304, VSC = 133120;
constexpr uint32_t ROWST = 229376, COLS = 231424, BARS = 232192, SMEM_BYTES = 232448;
constexpr uint32_t B_QF = BARS, B_QE = BARS + 32, B_TF = BARS + 64, B_TE = BARS + 96, B_PF = BARS + 128, B_PE = BARS + 176,
                   B_RF = BARS + 224, W_X = BARS + 232, W_O = BARS + 236, B_QL = BARS + 240, B_PA = BARS + 248;
enum { NB_ST = 1, NB_KV = 2  , NB_DONE = 3, NB_SC = 4, NB_SIG = 5  , NB_KN = 9  , NB_X = 11, NB_HALO = 12  , NB_X0 = 15 };

DEVINL uint32_t pslot_b(uint32_t s) { return ((0x320415u >> (4 * s)) & 7) * 16384u; }
DEVINL uint32_t pslot_a(uint32_t s, int l) { return 98304u + ((((l & 1) ? 0x541230u : 0x041235u) >> (4 * s)) & 7) * 16384u; }

constexpr float QSCALE = 0.17677669529663687f * 1.4426950408889634f;

DEVINL uint32_t hadd2(uint32_t a, uint32_t b) { uint32_t r; asm("add.rn.f16x2 %0, %1, %2;" : "=r"(r) : "r"(a), "r"(b)); return r; }
DEVINL uint32_t hsub2(uint32_t a, uint32_t b) { uint32_t r; asm("sub.rn.f16x2 %0, %1, %2;" : "=r"(r) : "r"(a), "r"(b)); return r; }
DEVINL uint32_t hfma2(uint32_t a, uint32_t b, uint32_t c) { uint32_t r; asm("fma.rn.f16x2 %0, %1, %2, %3;" : "=r"(r) : "r"(a), "r"(b), "r"(c)); return r; }
DEVINL uint32_t pack2h(float lo, float hi) { uint32_t r; asm("cvt.rn.f16x2.f32 %0, %1, %2;" : "=r"(r) : "f"(hi), "f"(lo)); return r; }
DEVINL uint32_t h2_to_bf2(uint32_t h) {
  float a, b;
  asm("{\n.reg .b16 l, h;\nmov.b32 {l, h}, %2;\ncvt.f32.f16 %0, l;\ncvt.f32.f16 %1, h;\n}" : "=f"(a), "=f"(b) : "r"(h));
  return pack2(a, b);
}
DEVINL uint32_t exp2_h2(uint32_t s) {
  const uint32_t r = hadd2(s, 0x65B665B6u);
  const uint32_t f = hsub2(s, hadd2(r, 0xE5B6E5B6u));
  uint32_t p = hfma2(f, 0x48FC48FCu, 0x517F517Fu);
  p = hfma2(p, f, 0x57D857D8u);
  p = hfma2(p, f, 0x648264B5u);
  return r * 128u + p;
}
constexpr uint32_t NOT_F16 = 0x7FC00000u;
DEVINL uint32_t f16_class(uint32_t norm2) { return norm2 - 0x35000000u > 0x4E800000u - 0x35000000u ? NOT_F16 : norm2; }

DEVINL void attn_slow(const uint32_t (&q)[8], int head, const float* kn, float (&res)[20], int lane) {
  const int g = lane >> 2, qd = lane & 3;
  const bf16* kb = g_k + (size_t)head * 2048 * 32;
  const bf16* vb = g_v + (size_t)head * 2048 * 32;
  float o[4][4], m0 = -INFINITY, m1 = -INFINITY, l0 = 0.f, l1 = 0.f;
#pragma unroll
  for (int j = 0; j < 4; j++) { o[j][0] = o[j][1] = o[j][2] = o[j][3] = 0.f; }
#pragma unroll 1
  for (int k0 = 0; k0 < 2048; k0 += 16) {
    float s[2][4];
    const bool kh = __float_as_uint(__ldcg(kn + (k0 >> 8) * 16 + ((k0 >> 7) & 1) * 4 + ((k0 >> 4) & 3))) != NOT_F16;
#pragma unroll
    for (int nt = 0; nt < 2; nt++) {
      s[nt][0] = s[nt][1] = s[nt][2] = s[nt][3] = 0.f;
      const uint32_t* kp = (const uint32_t*)(kb + (size_t)(k0 + nt * 8 + g) * 32) + qd;
      uint32_t kf[4];
#pragma unroll
      for (int i = 0; i < 4; i++) { kf[i] = __ldcg(kp + 4 * i); if (kh) kf[i] = h2_to_bf2(kf[i]); }
      mma16816(s[nt], q[0], q[1], q[2], q[3], kf[0], kf[1]);
      mma16816(s[nt], q[4], q[5], q[6], q[7], kf[2], kf[3]);
    }
    float a0 = fmaxf(fmaxf(s[0][0], s[0][1]), fmaxf(s[1][0], s[1][1]));
    float a1 = fmaxf(fmaxf(s[0][2], s[0][3]), fmaxf(s[1][2], s[1][3]));
    a0 = fmaxf(a0, __shfl_xor_sync(~0u, a0, 1)); a0 = fmaxf(a0, __shfl_xor_sync(~0u, a0, 2));
    a1 = fmaxf(a1, __shfl_xor_sync(~0u, a1, 1)); a1 = fmaxf(a1, __shfl_xor_sync(~0u, a1, 2));
    const float n0 = fmaxf(m0, a0), n1 = fmaxf(m1, a1);
    const float c0 = (m0 == n0) ? 1.f : ex2(m0 - n0), c1 = (m1 == n1) ? 1.f : ex2(m1 - n1);
    m0 = n0; m1 = n1;
    const uint32_t p0 = pack2(ex2(s[0][0] - n0), ex2(s[0][1] - n0)), p1 = pack2(ex2(s[0][2] - n1), ex2(s[0][3] - n1));
    const uint32_t p2 = pack2(ex2(s[1][0] - n0), ex2(s[1][1] - n0)), p3 = pack2(ex2(s[1][2] - n1), ex2(s[1][3] - n1));
    l0 = l0 * c0 + bf_lo(p0) + bf_hi(p0) + bf_lo(p2) + bf_hi(p2);
    l1 = l1 * c1 + bf_lo(p1) + bf_hi(p1) + bf_lo(p3) + bf_hi(p3);
#pragma unroll
    for (int j = 0; j < 4; j++) {
      o[j][0] *= c0; o[j][1] *= c0; o[j][2] *= c1; o[j][3] *= c1;
      const unsigned short* vp = (const unsigned short*)(vb + (size_t)(k0 + 2 * qd) * 32 + j * 8 + g);
      const uint32_t b0 = (uint32_t)__ldcg(vp) | ((uint32_t)__ldcg(vp + 32) << 16);
      const uint32_t b1 = (uint32_t)__ldcg(vp + 256) | ((uint32_t)__ldcg(vp + 288) << 16);
      mma16816(o[j], p0, p1, p2, p3, b0, b1);
    }
  }
  l0 += __shfl_xor_sync(~0u, l0, 1); l0 += __shfl_xor_sync(~0u, l0, 2);
  l1 += __shfl_xor_sync(~0u, l1, 1); l1 += __shfl_xor_sync(~0u, l1, 2);
#pragma unroll
  for (int j = 0; j < 4; j++) { res[4 * j] = o[j][0]; res[4 * j + 1] = o[j][1]; res[4 * j + 2] = o[j][2]; res[4 * j + 3] = o[j][3]; }
  res[16] = l0; res[18] = l1;
}

__global__ void __cluster_dims__(2, 1, 1) __launch_bounds__(384, 1) fused_kernel(const __grid_constant__ Params prm) {
  extern __shared__ __align__(1024) char smem[];
  const uint32_t sb = (uint32_t)__cvta_generic_to_shared(smem);
  const int tid = threadIdx.x, lane = tid & 31;
  const int wg = __shfl_sync(0xffffffffu, tid >> 7, 0);
  const int w = __shfl_sync(0xffffffffu, (tid >> 5) & 3, 0);
  const int bm = remap(blockIdx.x) >> 4, bn = remap(blockIdx.x) & 15;

  auto first_tile = [&](int kt) {
    e_expect_tx(sb + B_QF + 8 * kt, QSTG);
    tma_ld(sb + kt * QSTG, &prm.m[M_X0A], kt * 64, bm * 256, sb + B_QF + 8 * kt);
    tma_ld3(sb + kt * QSTG + 32768, &prm.m[M_WQA], bn * 64, kt * 64, 0, sb + B_QF + 8 * kt);
  };
  if (wg < 2) {
  } else if (w == 0) {
    if (lane < 4) { mbar_init(sb + B_QF + 8 * lane, 1); asm volatile("fence.mbarrier_init.release.cluster;" ::: "memory"); }
    __syncwarp();
    first_tile(0);
  } else if (w == 1) {
    if (lane == 25) *(uint2*)(smem + W_X) = make_uint2(0u, 0u);
    else if (lane < 28) {
      mbar_init(sb + B_QE + 8 * lane, lane < 4 ? 4 : lane < 8 ? 1 : lane < 12 ? 2 : lane < 18 ? 1 : lane < 24 ? 4 : lane < 27 ? 1 : 2);
      asm volatile("fence.mbarrier_init.release.cluster;" ::: "memory");
    }
  } else if (w == 2 && lane < M_COUNT) {
    asm volatile("prefetch.tensormap [%0];" ::"l"(&prm.m[lane]) : "memory");
  }
  __syncthreads();
  asm volatile("barrier.cluster.arrive.relaxed.aligned;" ::: "memory");

  if (wg == 2) {
    asm volatile("setmaxnreg.dec.sync.aligned.u32 56;");
    const uint32_t ep1 = *(volatile uint32_t*)&g_epoch + 1;
    if (w == 0) {
      first_tile(1);
      mbar_wait(sb + B_QF, 0);
      first_tile(2); first_tile(3);
#pragma unroll 1
      for (int kt = 4; kt < 16; kt++) l2_prefetch(prm.wq[0] + kt * 196608 + blockIdx.x * 1536, 3072);
      cluster_wait();
#pragma unroll 1
      for (int l = 0; l < 4; l++) {
        IDS();
        const CUtensorMap* mw = &prm.m[M_WQA + (l & 1)];
        const CUtensorMap* mx = &prm.m[l == 0 ? M_X0A : M_XSA];
        const CUtensorMap* mh = &prm.m[l == 0 ? M_X0H : M_XSO];
        const CUtensorMap* mo = &prm.m[M_WOA + (l & 1)];
        auto q_b = [&](int i) {
          const int s = i & 3;
          mbar_wait(sb + B_QE + 8 * s, ((i >> 2) & 1) ^ 1);
          e_expect_tx(sb + B_QF + 8 * s, QSTG);
          tma_ld3(sb + s * QSTG + 32768, mw, bn * 64, qord(i, l, pn) * 64, 0, sb + B_QF + 8 * s);
        };
        uint32_t rdy = l ? 0u : ~0u;
        auto q_a = [&](int i) {
          const int kt = qord(i, l, pn);
          await_bit(sb + W_X, l, kt >> 1, rdy);
          if (i < 4) tma_ld(sb + i * QSTG, mx, kt * 64, bm * 256, sb + B_QF + 8 * i);
          else tma_ld_mc(sb + (i & 3) * QSTG + rank * 16384, mh, kt * 64, bm * 256 + rank * 128, sb + B_QF + 8 * (i & 3));
        };
        if (l > 0) {
          await_bit(sb + W_X, l, pn, rdy);
#pragma unroll 1
          for (int i = 0; i < 2; i++) {
            e_expect_tx(sb + B_QF + 8 * i, 16384);
            tma_ld(sb + i * QSTG + (po ^ 1) * 16384, &prm.m[M_XSO], (2 * pn + i) * 64, (pm ^ 1) * 128, sb + B_QF + 8 * i);
          }
          mbar_wait(sb + B_QF, 0);
          q_a(2);
          mbar_wait(sb + B_QF + 8, 0);
        }
#pragma unroll 1
        for (int i = l ? 3 : 4; i < 16; i++) {
          q_b(i); q_a(i);
        }
        if (l & 1) {
          if (l == 3) poll_ge(cnt_ad(bn), ep1 * 16);
          bar_sync(NB_KV, 288);
          sts128(sb + ONES + lane * 32, 0x3f803f80u, 0x3f803f80u, 0x3f803f80u, 0x3f803f80u);
          sts128(sb + ONES + lane * 32 + 16, 0x3f803f80u, 0x3f803f80u, 0x3f803f80u, 0x3f803f80u);
          fence_async_smem();
          __syncwarp();
          e_arrive(sb + B_TF);
          const int krow = 2 * bn * 2048 + bm * 256;
          uint32_t* kvc = cnt_kv(l >> 1, bn);
          tma_st(&prm.m[M_K], 0, krow, sb + T0);
          tma_st(&prm.m[M_V], 0, krow, sb + T0 + 16384);
          bulk_commit(); bulk_wait_n<0>();
          e_red(kvc + bm);
          bar_sync(NB_KV + 12, 288);
          tma_st(&prm.m[M_K], 0, krow + 2048, sb);
          tma_st(&prm.m[M_V], 0, krow + 2048, sb + 16384);
          bulk_commit();
          uint32_t seen = 0;
#pragma unroll 1
          for (int it = 1; it < 16; it++) {
            const int s = it & 3, blk = it;
            if (it == 4) { bulk_wait_n<0>(); e_red(kvc + bm); }
            if (it == 12) { e_expect_tx(sb + B_RF, 32768); tma_ld3(sb + RES, &prm.m[M_XSR], 0, pm * 128, 2 * pn, sb + B_RF); }
            if (it == 2 || it == 3) mbar_wait(sb + B_TF + 8 * (it - 1), 0);
            mbar_wait(sb + B_TE + 8 * s, ((it >> 2) & 1) ^ 1);
            if (it < 8) {
#pragma unroll 1
              for (uint32_t n = 0; n < 200000u && !((seen >> it) & 1); n++)
                seen = __ballot_sync(~0u, (int)(ld_acquire(kvc + ((bm + lane) & 7)) - (ep1 * 2 - 1)) >= 0);
              fence_async_gl();
            } else if (it == 8) { poll_ge(kvc + (lane & 7), ep1 * 2); fence_async_gl(); }
            const int row = (2 * bn + (it >> 3)) * 2048 + ((bm + blk) & 7) * 256;
            e_expect_tx(sb + B_TF + 8 * s, 32768);
            tma_ld(sb + T0 + s * TSTG, &prm.m[M_K], 0, row, sb + B_TF + 8 * s);
            tma_ld(sb + T0 + s * TSTG + 16384, &prm.m[M_V], 0, row, sb + B_TF + 8 * s);
          }
        }
        auto p_b = [&](int i, uint32_t s, uint32_t par) {
          mbar_wait(sb + B_PE + 8 * s, par ^ 1);
          e_expect_tx(sb + B_PF + 8 * s, PSTG);
          tma_ld5(sb + pslot_b(s), mo, i >> 3, 2 * (i & 7), 2 * pn, sb + B_PF + 8 * s);
        };
        auto p_a = [&](int i, uint32_t s) {
          await_bit(sb + W_O, l + 1, i, rdy);
          tma_ld_mc(sb + pslot_a(s, l) + rank * 8192, &prm.m[M_OS], i * 64, pm * 128 + rank * 64, sb + B_PF + 8 * s);
        };
        auto p_a2 = [&](int i) {
          await_bit(sb + W_O, l + 1, i, rdy);
          tma_ld(sb + pslot_a(i, l), &prm.m[M_OS], i * 64, pm * 128, sb + B_PF + 8 * i);
          tma_ld(sb + pslot_a(i, l) + 8192, &prm.m[M_OS], i * 64, pm * 128 + 64, sb + B_PF + 8 * i);
        };
        rdy = 0;
        if (l & 1) {
#pragma unroll 1
          for (int u = 0; u < 6; u++) { const int i = (0x205413 >> (4 * u)) & 7; if (u == 4) mbar_wait(sb + B_TE, 1); p_b(i, i, i < 4 ? 1 : 0); }
#pragma unroll 1
          for (int u = 0; u < 6; u++) {
            const int i = (0x542130 >> (4 * u)) & 7;
            if (!(u & 1)) mbar_wait(sb + B_TE + 8 + 4 * u, 1);
            p_a2(i);
          }
        } else {
#pragma unroll 1
          for (int u = 0; u < 6; u++) { const int i = (0x025413 >> (4 * u)) & 7; if (u == 0 || u == 3) mbar_wait(sb + B_QE + 8 * (u / 3), 1); p_b(i, i, 0); }
          mbar_wait(sb + B_QE + 24, 1);
          e_expect_tx(sb + B_RF, 32768);
          tma_ld3(sb + RES, &prm.m[l == 0 ? M_X0R : M_XSR], 0, pm * 128, 2 * pn, sb + B_RF);
          p_a2(0);
          bar_sync(NB_DONE, 96);
          e_arrive_both(sb + B_PA);
          p_a2(1); p_a2(2);
          mbar_wait(sb + B_PA, (l >> 1) & 1);
#pragma unroll 1
          for (int i = 3; i < 6; i++) { if (i == 4) mbar_wait(sb + B_PF + 8, 0); p_a(i, i); }
        }
        uint32_t s = 0, lap = 1;
#pragma unroll 1
        for (int i = 6; i < 16; i++) {
          p_b(i, s, ((s < 4 ? l : 0) + lap) & 1);
          p_a(i, s);
          if (++s == 6) { s = 0; lap++; }
        }
        const CUtensorMap* mn = &prm.m[M_WQA + ((l + 1) & 1)];
        if (l < 3) {
          mbar_wait(sb + B_PE + 8 * 4, 1); mbar_wait(sb + B_PE + 8 * 5, 1);
          tma_ld3(sb + 32768, mn, bn * 64, 2 * pn * 64, 0, sb + B_QL);
          mbar_wait(sb + B_PE + 8 * 0, l & 1);
          tma_ld3(sb + QSTG + 32768, mn, bn * 64, (2 * pn + 1) * 64, 0, sb + B_QL);
          mbar_wait(sb + B_PE + 8 * 1, l & 1);
          e_expect_tx(sb + B_QF + 16, QSTG);
          tma_ld3(sb + 2 * QSTG + 32768, mn, bn * 64, ((2 * pn) ^ 2) * 64, 0, sb + B_QF + 16);
        }
        if (l < 3) { bar_sync(NB_X, 288); e_expect_tx(sb + B_QL, 49152); }
      }
      if (blockIdx.x == 0 && lane_id() == 0) *(volatile uint32_t*)&g_epoch = ep1;
    } else {
      const int hw = w - 1;
      cluster_wait();
      mbar_wait(sb + B_QF, 0);
#pragma unroll 1
      for (int l = 0; l < 4; l++) {
        IDS();
        if (hw == 2 && l > 0) watch(cnt_x(l, bm) + (lane & 7), ep1 * 2, 0xFFu, l, sb + W_X);
        if (l == 0) {
#pragma unroll 1
          for (int r = 2 * hw; r < 16; r += 6) {
            const uint4* p = (const uint4*)(prm.x0 + (size_t)(b * 16 + r) * 1024) + lane;
            float s1[2] = {0.f, 0.f}, s2[2] = {0.f, 0.f};
#pragma unroll
            for (int i = 0; i < 8; i++) {
              const uint4 v = __ldg(p + 32 * i);
              const uint32_t u[4] = {v.x, v.y, v.z, v.w};
#pragma unroll
              for (int k = 0; k < 4; k++) { const float a = bf_lo(u[k]), c = bf_hi(u[k]); s1[i >> 2] += a + c; s2[i >> 2] = fmaf(a, a, fmaf(c, c, s2[i >> 2])); }
            }
#pragma unroll
            for (int o = 16; o; o >>= 1)
#pragma unroll
              for (int rr = 0; rr < 2; rr++) { s1[rr] += __shfl_xor_sync(~0u, s1[rr], o); s2[rr] += __shfl_xor_sync(~0u, s2[rr], o); }
            if (lane == 0) *(float4*)&g_stats[b * 16 + r] = make_float4(s1[0], s2[0], s1[1], s2[1]);
          }
        }
        if (l == 1) { uint32_t rdy = 0; await_bit<true>(sb + W_X, 1, pn, rdy); mbar_hint(sb + B_QF + 8, 0); }
        if (l < 2) {
          float cs[8];
#pragma unroll
          for (int i = 0; i < 8; i++) cs[i] = 0.f;
          const uint4* wp = (const uint4*)(prm.wq[l] + (size_t)(bm * 128 + (lane >> 3)) * 3072 + hw * 1024 + bn * 64) + (lane & 7);
#pragma unroll 8
          for (int i = 0; i < 32; i++) {
            const uint4 v = __ldg(wp + (size_t)i * 4 * 384);
            cs[0] += bf_lo(v.x); cs[1] += bf_hi(v.x); cs[2] += bf_lo(v.y); cs[3] += bf_hi(v.y);
            cs[4] += bf_lo(v.z); cs[5] += bf_hi(v.z); cs[6] += bf_lo(v.w); cs[7] += bf_hi(v.w);
          }
#pragma unroll
          for (int i = 0; i < 8; i++) { cs[i] += __shfl_xor_sync(~0u, cs[i], 8); cs[i] += __shfl_xor_sync(~0u, cs[i], 16); }
          if (lane < 8) {
            float4* d = (float4*)(g_csp + ((l * 16 + bn) * 8 + bm) * 192 + hw * 64 + lane * 8);
            d[0] = make_float4(cs[0], cs[1], cs[2], cs[3]); d[1] = make_float4(cs[4], cs[5], cs[6], cs[7]);
          }
          __syncwarp();
          asm volatile("fence.acq_rel.gpu;" ::: "memory");
          e_red_relaxed(cnt_cs(l, bn));
          if (l == 0) e_red_relaxed(cnt_x(0, bm) + pn);
          poll_ge(lane < 8 && l == 0 ? cnt_x(0, bm) + lane : cnt_cs(l, bn), ep1 * (lane < 8 && l == 0 ? 6 : 24));
        }
        if (l > 0) {
          uint32_t rdy = 0;
#pragma unroll 1
          for (int j = 0; j < 8; j++) await_bit<true>(sb + W_X, l, j, rdy);
        }
#pragma unroll 1
        for (int it = hw * 32 + lane; it < 176; it += 96) {
          const bool rows = it < 128;
          const float4* p = rows ? (const float4*)(g_stats + bm * 256) + it : (const float4*)(g_csp + ((l & 1) * 16 + bn) * 8 * 192) + (it - 128);
          const int stride = rows ? 1024 : 48, np = rows && l == 0 ? 1 : 8;
          float4 a = make_float4(0.f, 0.f, 0.f, 0.f);
#pragma unroll
          for (int k = 0; k < 8; k++) if (k < np) { const float4 v = __ldcg(p + k * stride); a.x += v.x; a.y += v.y; a.z += v.z; a.w += v.w; }
          if (rows) {
            const float m0 = a.x * (1.f / 1024.f), m1 = a.z * (1.f / 1024.f);
            const float v0 = fmaxf(a.y * (1.f / 1024.f) - m0 * m0, 0.f), v1 = fmaxf(a.w * (1.f / 1024.f) - m1 * m1, 0.f);
            const float r0 = __fdividef(1.f, bf_round(sqrtf(bf_round(bf_round(v0) + 1e-5f)))), r1 = __fdividef(1.f, bf_round(sqrtf(bf_round(bf_round(v1) + 1e-5f))));
            a = make_float4(r0, -bf_round(m0) * r0, r1, -bf_round(m1) * r1);
          }
          *(float4*)(smem + ROWST + it * 16) = a;
        }
        __syncwarp();
        if (lane == 0) asm volatile("red.release.cta.shared.add.u32 [%0], 0x100;" ::"r"(sb + W_X) : "memory");
        if (hw == 2) {
          if (!(l & 1)) {
            bar_sync(NB_ST, 288);
            const volatile unsigned long long* hp = g_halo + ((size_t)(l >> 1) * 128 + b - 16) * 1024 + lane;
#pragma unroll 1
            for (int h = 0; h < 2; h++) {
              uint32_t t[16];
#pragma unroll
              for (int i = 0; i < 16; i++) t[i] = 0;
#pragma unroll 1
              for (uint32_t n = bm ? 0 : 100000u; n < 100000u; n++) {
                uint32_t miss = 0;
#pragma unroll
                for (int i = 0; i < 16; i++) {
                  const unsigned long long v = hp[h * 512 + i * 32];
                  t[i] = (uint32_t)v; miss |= (uint32_t)(v >> 32) ^ ep1;
                }
                if (__all_sync(~0u, !miss)) break;
              }
              const uint32_t r = (lane & 7) + ((lane >> 3) & 1) * 8, rv = lane >> 2;
#pragma unroll
              for (int jj = 0; jj < 2; jj++) stsm4(sb + KSC + r * 128 + (((4 * h + 2 * jj + (lane >> 4)) ^ (r & 7)) << 4), t[4 * jj], t[4 * jj + 1], t[4 * jj + 2], t[4 * jj + 3]);
              const uint32_t ad = sb + VSC + rv * 128 + (((4 * h + (lane & 3)) ^ (rv & 7)) << 4);
              sts128(ad, t[8], t[10], t[12], t[14]); sts128(ad + 1024, t[9], t[11], t[13], t[15]);
              bar_arrive(NB_HALO + h, 64);
            }
          } else {
            mbar_hint(sb + B_TF + 8, 0);
            poll_ge(cnt_kv(l >> 1, bn) + (lane & 7), ep1 * 2);
            const uint4 v = __ldcg((const uint4*)(g_kn + ((l >> 1) * 128 + bn * 8) * 16) + lane);
            const uint32_t mx = max(max(v.x, v.y), max(v.z, v.w));
            const uint32_t m0 = __reduce_max_sync(~0u, (lane & 2) ? 0u : mx), m1 = __reduce_max_sync(~0u, (lane & 2) ? mx : 0u);
            if (lane == 0) *(uint2*)(smem + ROWST) = make_uint2(m0, m1);
            __syncwarp();
            bar_arrive(NB_KN, 160); bar_arrive(NB_KN + 1, 160);
          }
        } else {
#pragma unroll 1
          for (int h = 0; h < 2; h++) {
            bar_sync(NB_SIG + 2 * h + hw, 160);
            if (h == 1 && !(l & 1)) bar_arrive(NB_DONE, 96);
            e_red(cnt_o(l, 2 * bm + hw, h) + (bn >> 1));
            if (h == 1 && l == 1) e_red(cnt_ad(bn));
          }
        }
        if (hw == 2) watch(cnt_o(l, pm, (lane >> 3) & 1) + (lane & 7), ep1 * 2, 0xFFFFu, l + 1, sb + W_O);
        if (hw == 0 && l < 3) {
          bar_sync(NB_X0, 288);
          e_red(cnt_x(l + 1, bm) + pn);
        }
      }
    }
  } else {
    asm volatile("setmaxnreg.inc.sync.aligned.u32 224;");
    const uint32_t zero = prm.zero;
    cluster_wait();
#pragma unroll 1
    for (int l = 0; l < 4; l++) {
      {
        float acc[2][96];
#pragma unroll
        for (int i = 0; i < 96; i++) { acc[0][i] = 0.f; acc[1][i] = 0.f; }
        fence_regs(acc[0]); fence_regs(acc[1]);
        const bool early = l > 0 && wg == ((cta_id() >> 3) & 1);
        const uint32_t ep1 = *(volatile uint32_t*)&g_epoch + 1;
#pragma unroll 1
        for (int kt = 0; kt < 16; kt++) {
          const int s = kt & 3;
          if (l > 0 && kt == 0) mbar_wait(sb + B_QL, (l + 1) & 1);
          if (!(early && kt < 2)) mbar_wait(sb + B_QF + 8 * s, (kt >> 2) & 1);
          const uint64_t da = mkdesc(sb + s * QSTG + wg * 16384, 16, 1024, 1), db = mkdesc(sb + s * QSTG + 32768, 8192, 1024, 1);
          wg_fence();
#pragma unroll
          for (int k = 0; k < 4; k++)
#pragma unroll
            for (int m = 0; m < 2; m++) wgmma_m64n192k16_ss_tb(acc[m], da + m * 512 + k * 2, db + k * 128, 1);
          wg_commit();
          wg_wait<1>();
          if (early && (kt == 1 || kt == 2)) mbar_wait(sb + B_QF + 8 * (kt - 1), 0);
          if (kt > 0 && w == 0) e_arrive_both(sb + B_QE + 8 * ((kt - 1) & 3));
        }
#pragma unroll 1
        for (uint32_t n = 0; n < 4000000u; n++) {
          uint32_t v;
          asm volatile("ld.acquire.cta.shared.u32 %0, [%1];" : "=r"(v) : "r"(sb + W_X) : "memory");
          if ((v >> 8) == (uint32_t)(l * 256 + 3)) break;
        }
        IDS();
        const int g = lane >> 2, qd = lane & 3;
        float2 st[2][2];
#pragma unroll
        for (int m = 0; m < 2; m++)
#pragma unroll
          for (int hh = 0; hh < 2; hh++) st[m][hh] = lds64f(sb + ROWST + (wg * 128 + m * 64 + w * 16 + g + 8 * hh) * 8);
        float2 cs[4];
        auto load_cs = [&](int gi) {
#pragma unroll
          for (int j = 0; j < 4; j++) cs[j] = lds64f(sb + COLS + (gi * 32 + j * 8 + 2 * qd) * 4);
        };
        load_cs(2);
        wg_wait<0>();
        fence_regs(acc[0]); fence_regs(acc[1]);
        if (w == 0) e_arrive_both(sb + B_QE + 8 * 3);
        if (!(l & 1)) bar_arrive(NB_ST, 288);
        auto norm_tile = [&](int gi, int m, float sc, uint32_t (&t)[8], float (&nrm)[2]) {
          const float r0 = st[m][0].x * sc, s0 = st[m][0].y * sc, r1 = st[m][1].x * sc, s1 = st[m][1].y * sc;
          float n0 = 0.f, n1 = 0.f;
#pragma unroll
          for (int j = 0; j < 4; j++) {
            const float* a = &acc[m][16 * gi + 4 * j];
            const float v0 = fmaf(a[0], r0, s0 * cs[j].x), v1 = fmaf(a[1], r0, s0 * cs[j].y);
            const float v2 = fmaf(a[2], r1, s1 * cs[j].x), v3 = fmaf(a[3], r1, s1 * cs[j].y);
            n0 = fmaf(v0, v0, fmaf(v1, v1, n0)); n1 = fmaf(v2, v2, fmaf(v3, v3, n1));
            t[2 * j] = pack2(v0, v1); t[2 * j + 1] = pack2(v2, v3);
          }
          nrm[0] = n0; nrm[1] = n1;
        };
        auto norm_group = [&](int gi, float sc, uint32_t (&t)[2][8], float (&nrm)[2][2]) { norm_tile(gi, 0, sc, t[0], nrm[0]); norm_tile(gi, 1, sc, t[1], nrm[1]); };
        uint32_t q[2][2][8];
        const uint32_t srow = (lane & 7) + ((lane >> 3) & 1) * 8;
        const uint32_t row0 = wg * 128 + w * 16;
        auto put_o = [&](int h, int m, const float (&o)[16], float i0, float i1) {
          IDS();
          bf16* op = g_os + (size_t)(bm * 256 + row0 + m * 64 + (lane >> 2)) * 1024 + h * 512 + bn * 32 + (lane & 3) * 8;
          *(uint4*)op = make_uint4(pack2(o[0] * i0, o[1] * i0), pack2(o[4] * i0, o[5] * i0), pack2(o[8] * i0, o[9] * i0), pack2(o[12] * i0, o[13] * i0));
          *(uint4*)(op + 8 * 1024) = make_uint4(pack2(o[2] * i1, o[3] * i1), pack2(o[6] * i1, o[7] * i1), pack2(o[10] * i1, o[11] * i1), pack2(o[14] * i1, o[15] * i1));
        };
        if (!(l & 1)) {
          auto put_kv = [&](int gi, uint32_t r0, const uint32_t (&t)[8]) {
            if (gi < 4) {
              const uint32_t r = r0 + srow;
#pragma unroll
              for (int jj = 0; jj < 2; jj++) stsm4(sb + KSC + r * 128 + (((4 * (gi - 2) + 2 * jj + (lane >> 4)) ^ (r & 7)) << 4), t[4 * jj], t[4 * jj + 1], t[4 * jj + 2], t[4 * jj + 3]);
            } else {
              const uint32_t r = r0 + g, ad = sb + VSC + r * 128 + (((4 * (gi - 4) + qd) ^ (r & 7)) << 4);
              sts128(ad, t[0], t[2], t[4], t[6]); sts128(ad + 1024, t[1], t[3], t[5], t[7]);
            }
          };
          const bool send = wg == 1 && w == 3 && bm < 7;
          unsigned long long* hp = g_halo + ((size_t)(l >> 1) * 128 + b) * 1024 + lane;
          uint32_t t[4][2][8];
#pragma unroll
          for (int mm = 0; mm < 2; mm++)
#pragma unroll
            for (int u = 0; u < 4; u++) {
              float nrm[2];
              norm_tile(2 + (u >> 1) + 2 * (u & 1), 1 - mm, 1.f, t[u][1 - mm], nrm);
              load_cs(u == 0 ? 4 : u == 1 ? 3 : u == 2 ? 5 : mm == 0 ? 2 : 0);
              if (mm == 0 && send) {
#pragma unroll
                for (int i = 0; i < 8; i++) st_tagged(hp + (u * 8 + i) * 32, t[u][1][i], ep1);
              }
            }
          mbar_wait(sb + B_QE + 24, 1);
#pragma unroll
          for (int u = 0; u < 4; u++) { put_kv(2 + (u >> 1) + 2 * (u & 1), 16 + row0, t[u][0]); put_kv(2 + (u >> 1) + 2 * (u & 1), 16 + row0 + 64, t[u][1]); }
          { float nrm[2][2]; norm_group(0, 1.f, q[0], nrm); }
          bar_sync(NB_SC, 256);
          const bool e = g & 1, sel = 2 * qd + (g & 1) >= g + 2, first = bm == 0 && row0 == 0;
#pragma unroll 1
          for (int h = 0; h < 2; h++) {
            if (row0 == 0) bar_sync(NB_HALO + h, 64);
            float s[2][4][4];
            uint32_t vf[2][4][4], pf[2][2][4];
#pragma unroll
            for (int m = 0; m < 2; m++)
#pragma unroll
              for (int nt = 0; nt < 4; nt++) {
                uint32_t kf[4];
                const uint32_t r = row0 + m * 64 + 8 * nt + (lane & 7), ch = 4 * h + (lane >> 3);
                ldsm4(sb + KSC + r * 128 + ((ch ^ (r & 7)) << 4), kf);
                s[m][nt][0] = s[m][nt][1] = s[m][nt][2] = s[m][nt][3] = 0.f;
                mma16816(s[m][nt], q[0][m][0], q[0][m][1], q[0][m][2], q[0][m][3], kf[0], kf[1]);
                mma16816(s[m][nt], q[0][m][4], q[0][m][5], q[0][m][6], q[0][m][7], kf[2], kf[3]);
              }
#pragma unroll
            for (int m = 0; m < 2; m++)
#pragma unroll
              for (int i = 0; i < 4; i++) {
                const uint32_t r = row0 + m * 64 + 16 * (i >> 1) + srow, ch = 4 * h + 2 * (i & 1) + (lane >> 4);
                ldsm4t(sb + VSC + r * 128 + ((ch ^ (r & 7)) << 4), vf[m][i]);
              }
            float va[4], vb[4], mx[4];
#pragma unroll
            for (int i = 0; i < 4; i++) {
              const int m = i >> 1, hh = i & 1;
              const float a = e ? s[m][hh + 1][2 * hh + 1] : s[m][hh + 1][2 * hh];
              const float lo = e ? s[m][hh][2 * hh + 1] : s[m][hh][2 * hh], hi = e ? s[m][hh + 2][2 * hh + 1] : s[m][hh + 2][2 * hh];
              const uint32_t t = pack2(a, sel ? lo : hi);
              const uint32_t u = pack2(bf_lo(t) * 0.17677669529663687f, bf_hi(t) * 0.17677669529663687f);
              va[i] = (m == 0 && hh == 0 && first) ? -INFINITY : bf_lo(u);
              vb[i] = (m == 0 && first && sel) ? -INFINITY : bf_hi(u);
              mx[i] = fmaxf(va[i], vb[i]);
            }
#pragma unroll
            for (int i = 0; i < 4; i++) mx[i] = fmaxf(mx[i], __shfl_xor_sync(~0u, mx[i], 1));
#pragma unroll
            for (int i = 0; i < 4; i++) mx[i] = fmaxf(mx[i], __shfl_xor_sync(~0u, mx[i], 2));
#pragma unroll
            for (int i = 0; i < 4; i++) {
              va[i] = ex2((va[i] - mx[i]) * 1.4426950408889634f); vb[i] = ex2((vb[i] - mx[i]) * 1.4426950408889634f);
              mx[i] = va[i] + vb[i];
            }
#pragma unroll
            for (int i = 0; i < 4; i++) mx[i] += __shfl_xor_sync(~0u, mx[i], 1);
#pragma unroll
            for (int i = 0; i < 4; i++) mx[i] += __shfl_xor_sync(~0u, mx[i], 2);
#pragma unroll
            for (int i = 0; i < 4; i++) {
              const int m = i >> 1, hh = i & 1;
              const float inv = rcp(mx[i]);
              const uint32_t t = pack2(va[i] * inv, vb[i] * inv);
              const uint32_t pa = e ? t << 16 : t & 0xFFFFu, pb = e ? t & 0xFFFF0000u : t >> 16;
              pf[m][hh][hh + 1] = pa; pf[m][hh][hh] = sel ? pb : 0u; pf[m][hh][hh + 2] = sel ? 0u : pb; pf[m][hh][3 - 3 * hh] = 0u;
            }
#pragma unroll
            for (int m = 0; m < 2; m++) {
              float o[4][4];
#pragma unroll
              for (int j = 0; j < 4; j++) o[j][0] = o[j][1] = o[j][2] = o[j][3] = 0.f;
#pragma unroll
              for (int i = 0; i < 4; i++) {
                const int kk = i >> 1, jj = 2 * (i & 1);
                mma16816(o[jj], pf[m][0][2 * kk], pf[m][1][2 * kk], pf[m][0][2 * kk + 1], pf[m][1][2 * kk + 1], vf[m][i][0], vf[m][i][1]);
                mma16816(o[jj + 1], pf[m][0][2 * kk], pf[m][1][2 * kk], pf[m][0][2 * kk + 1], pf[m][1][2 * kk + 1], vf[m][i][2], vf[m][i][3]);
              }
              const float of[16] = {o[0][0], o[0][1], o[0][2], o[0][3], o[1][0], o[1][1], o[1][2], o[1][3], o[2][0], o[2][1], o[2][2], o[2][3], o[3][0], o[3][1], o[3][2], o[3][3]};
              put_o(h, m, of, 1.f, 1.f);
            }
            bar_arrive(NB_SIG + 2 * h + wg, 160);
            if (h == 0) {
              float nrm[2][2];
              load_cs(1);
              norm_group(1, 1.f, q[0], nrm);
            }
          }
        } else {
          uint32_t qn[2];
          {
            auto max_norm = [&](const float (&nrm)[2][2]) {
              const bool o1 = qd & 1, o2 = qd & 2;
              const float a = (o1 ? nrm[1][0] : nrm[0][0]) + __shfl_xor_sync(~0u, o1 ? nrm[0][0] : nrm[1][0], 1);
              const float c = (o1 ? nrm[1][1] : nrm[0][1]) + __shfl_xor_sync(~0u, o1 ? nrm[0][1] : nrm[1][1], 1);
              const float d = (o2 ? c : a) + __shfl_xor_sync(~0u, o2 ? a : c, 2);
              return f16_class(__reduce_max_sync(~0u, __float_as_uint(d)));
            };
            auto norm_vals = [&](int gi, float sc) {
              float nrm[2][2];
#pragma unroll
              for (int m = 0; m < 2; m++) {
                const float r0 = st[m][0].x * sc, s0 = st[m][0].y * sc, r1 = st[m][1].x * sc, s1 = st[m][1].y * sc;
                float n0 = 0.f, n1 = 0.f;
#pragma unroll
                for (int j = 0; j < 4; j++) {
                  float* a = &acc[m][16 * gi + 4 * j];
                  a[0] = fmaf(a[0], r0, s0 * cs[j].x); a[1] = fmaf(a[1], r0, s0 * cs[j].y);
                  a[2] = fmaf(a[2], r1, s1 * cs[j].x); a[3] = fmaf(a[3], r1, s1 * cs[j].y);
                  n0 = fmaf(a[0], a[0], fmaf(a[1], a[1], n0)); n1 = fmaf(a[2], a[2], fmaf(a[3], a[3], n1));
                }
                nrm[m][0] = n0; nrm[m][1] = n1;
              }
              return max_norm(nrm);
            };
            auto pack_vals = [&](int gi, uint32_t cls, uint32_t (&t)[2][8]) {
              if (cls != NOT_F16) {
#pragma unroll
                for (int i = 0; i < 16; i++) t[i >> 3][i & 7] = pack2h(acc[i >> 3][16 * gi + 2 * (i & 7)], acc[i >> 3][16 * gi + 2 * (i & 7) + 1]);
              } else {
#pragma unroll
                for (int i = 0; i < 16; i++) t[i >> 3][i & 7] = pack2(acc[i >> 3][16 * gi + 2 * (i & 7)], acc[i >> 3][16 * gi + 2 * (i & 7) + 1]);
              }
            };
#pragma unroll
            for (int h = 0; h < 2; h++) {
              uint32_t t[2][8], tv[2][8];
              const uint32_t kb = sb + (h ? 0 : T0);
              if (h) load_cs(3);
              const uint32_t kn = norm_vals(2 + h, 1.f);
              load_cs(4 + h);
              float nv[2][2];
              norm_group(4 + h, 1.f, tv, nv);
              load_cs(h);
              if (lane == 0) g_kn[((l >> 1) * 128 + bn * 8 + bm) * 16 + 8 * h + wg * 4 + w] = __uint_as_float(kn);
              pack_vals(2 + h, kn, t);
              if (h == 1) pack_vals(0, qn[0], q[0]);
              if (h == 0) mbar_wait(sb + B_QE + 24, 1);
#pragma unroll
              for (int i = 0; i < 4; i++) {
                const uint32_t r = row0 + (i >> 1) * 64 + srow;
                stsm4(kb + r * 64 + (((2 * (i & 1) + (lane >> 4)) ^ ((r >> 1) & 3)) << 4), t[i >> 1][4 * (i & 1)], t[i >> 1][4 * (i & 1) + 1], t[i >> 1][4 * (i & 1) + 2], t[i >> 1][4 * (i & 1) + 3]);
              }
#pragma unroll
              for (int m = 0; m < 2; m++) {
                const uint32_t r = row0 + m * 64 + g, ad = kb + 16384 + r * 64 + ((qd ^ ((r >> 1) & 3)) << 4);
                sts128(ad, tv[m][0], tv[m][2], tv[m][4], tv[m][6]); sts128(ad + 512, tv[m][1], tv[m][3], tv[m][5], tv[m][7]);
              }
              fence_async_smem();
              bar_arrive(NB_KV + 12 * h, 288);
              qn[h] = norm_vals(h, QSCALE);
            }
            pack_vals(1, qn[1], q[1]);
          }
          const bool elected = w == 0 && lane == 0;
          const uint64_t kd0 = mkdesc(sb + T0, 16, 512, 2);
          const uint64_t vd0 = mkdesc(sb + T0 + 16384, ONES - (T0 + 16384), 512, 2);
          constexpr uint64_t VSTEP = 64 - (64ull << 16);
#pragma unroll 1
          for (int pass = 0; pass < 2; pass++) {
            float o[2][20], SA[2][16];
            uint32_t SB[2][8], PA[4], PB[4];
#pragma unroll
            for (int m = 0; m < 2; m++) {
#pragma unroll
              for (int i = 0; i < 20; i++) o[m][i] = 0.f;
#pragma unroll
              for (int i = 0; i < 16; i++) SA[m][i] = 0.f;
#pragma unroll
              for (int i = 0; i < 8; i++) SB[m][i] = 0u;
              fence_regs(o[m]); fence_regs(SA[m]); fence_regs(SB[m]);
            }
#pragma unroll
            for (int i = 0; i < 4; i++) PA[i] = PB[i] = zero;
            auto qk = [&](int b, int k, uint64_t d) {
              wgmma_m64n32k16_rs_nb_h(SA[b], q[0][0][4 * k], q[0][0][4 * k + 1], q[0][0][4 * k + 2], q[0][0][4 * k + 3], d + 2 * k, k ? 1 : zero);
              wgmma_m64n32k16_rs_nb_hh(SB[b], q[0][1][4 * k], q[0][1][4 * k + 1], q[0][1][4 * k + 2], q[0][1][4 * k + 3], d + 2 * k, k ? 1 : zero);
            };
            auto pv = [&](int m, const uint32_t (&Px)[4], uint64_t vd) { wgmma_m64n40k16_rs_tb(o[m], Px[0], Px[1], Px[2], Px[3], vd, 1); };
            mbar_wait(sb + B_TF, 0);
            wg_fence(); qk(0, 0, kd0); qk(0, 1, kd0); wg_commit();
            wg_wait<0>(); fence_regs(SA[0]); fence_regs(SB[0]);
#pragma unroll 1
            for (int j = 0; j < 8; j++) {
              const uint32_t s = j & 3, sn = j < 7 ? (j + 1) & 3 : s, sp = j > 0 ? (j + 3) & 3 : s;
              const uint64_t kd = kd0 + s * 2048, vd = vd0 + s * (32 * VSTEP), kdn = kd0 + sn * 2048, vdp = vd0 + sp * (32 * VSTEP) + 15 * VSTEP;
              bool landed = false;
#pragma unroll
              for (int r = 0; r < 16; r++) {
                const int c = r >> 1, ro = r & 1, cn = c + 1;
                if (r == 14 && !landed) mbar_wait(sb + B_TF + 8 * sn, ((j + 1) >> 2) & 1);
                wg_fence();
                qk(cn & 1, ro, cn < 8 ? kd + cn * 128 : kdn);
                if (ro) wg_commit();
                const uint64_t vx = r > 0 ? vd + (r - 1) * VSTEP : vdp;
                pv(0, PA, vx); pv(1, PB, vx);
                wg_commit();
                if (r == 12) landed = mbar_test(sb + B_TF + 8 * sn, ((j + 1) >> 2) & 1) || j == 7;
#pragma unroll
                for (int i = 0; i < 4; i++) {
                  PA[i] = pack2(ex2(SA[c & 1][8 * ro + 2 * i]), ex2(SA[c & 1][8 * ro + 2 * i + 1]));
                  PB[i] = exp2_h2(SB[c & 1][4 * ro + i]);
                }
                if (r == 15) wg_wait<0>(); else wg_wait<1>();
                if (ro) { fence_regs(SA[cn & 1]); fence_regs(SB[cn & 1]); }
                if (r == 2 && elected && j > 0) mbar_arrive(sb + B_TE + 8 * sp);
              }
            }
            int badm = 0;
            wg_fence(); pv(0, PA, vd0 + 3 * (32 * VSTEP) + 15 * VSTEP); pv(1, PB, vd0 + 3 * (32 * VSTEP) + 15 * VSTEP); wg_commit();
            if (pass == 0) bar_sync(NB_KN + wg, 160);
            const float bound = __uint_as_float(qn[0]) * *(volatile float*)(smem + ROWST + 4 * pass);
            wg_wait<0>(); fence_regs(o[0]); fence_regs(o[1]);
            if (w == 0) e_arrive(sb + B_TE + 8 * 3);
#pragma unroll
            for (int m = 0; m < 2; m++) {
              float chk[4] = {0.f, 0.f, 0.f, 0.f};
#pragma unroll
              for (int i = 0; i < 20; i++) chk[i & 3] = fmaf(o[m][i], 0.f, chk[i & 3]);
              const bool bad = !(bound <= 112.f * 112.f) || !(o[m][16] >= 9.3e-10f) || !(o[m][18] >= 9.3e-10f) || ((chk[0] + chk[1]) + (chk[2] + chk[3]) != 0.f);
              badm |= __any_sync(~0u, bad) << m;
              const float of[16] = {o[m][0], o[m][1], o[m][2], o[m][3], o[m][4], o[m][5], o[m][6], o[m][7], o[m][8], o[m][9], o[m][10], o[m][11], o[m][12], o[m][13], o[m][14], o[m][15]};
              put_o(pass, m, of, rcp(o[m][16]), rcp(o[m][18]));
            }
            if (badm) {
#pragma unroll 1
              for (int m = 0; m < 2; m++) if ((badm >> m) & 1) {
                uint32_t qq[8]; float res[20];
#pragma unroll
                for (int i = 0; i < 8; i++) { qq[i] = m ? q[0][1][i] : q[0][0][i]; if (qn[0] != NOT_F16) qq[i] = h2_to_bf2(qq[i]); }
                attn_slow(qq, 2 * (cta_id() & 15) + pass, g_kn + ((l >> 1) * 128 + (cta_id() & 15) * 8) * 16 + 8 * pass, res, lane_id());
                const float of[16] = {res[0], res[1], res[2], res[3], res[4], res[5], res[6], res[7], res[8], res[9], res[10], res[11], res[12], res[13], res[14], res[15]};
                put_o(pass, m, of, rcp(res[16]), rcp(res[18]));
              }
            }
            bar_arrive(NB_SIG + 2 * pass + wg, 160);
            qn[0] = qn[1];
#pragma unroll
            for (int m = 0; m < 2; m++)
#pragma unroll
              for (int i = 0; i < 8; i++) q[0][m][i] = q[1][m][i];
          }
        }
      }
      {
        float acc[64];
#pragma unroll
        for (int i = 0; i < 64; i++) acc[i] = 0.f;
        fence_regs(acc);
        uint32_t s = 0, lap = 0;
#pragma unroll 1
        for (int kt = 0; kt < 16; kt++) {
          mbar_wait(sb + B_PF + 8 * s, ((s < 4 ? l : 0) + lap) & 1);
          const uint64_t da = mkdesc(sb + pslot_a(s, l) + wg * 8192, 16, 1024, 1), db = mkdesc(sb + pslot_b(s), 8192, 1024, 1);
          wg_fence();
#pragma unroll
          for (int k = 0; k < 4; k++) wgmma_m64n128k16_ss_tb(acc, da + k * 2, db + k * 128, 1);
          wg_commit();
          wg_wait<1>();
          if (kt > 0 && w == 0) e_arrive_both(sb + B_PE + 8 * (s ? s - 1 : 5));
          if (++s == 6) { s = 0; lap++; }
        }
        IDS();
        const int g = lane >> 2, qd = lane & 3;
        const int r0 = wg * 64 + w * 16;
        const uint32_t r = r0 + (lane & 7) + ((lane >> 3) & 1) * 8;
        uint32_t x[8][4];
        mbar_wait(sb + B_RF, l & 1);
#pragma unroll
        for (int jj = 0; jj < 8; jj++) ldsm4(sb + RES + (jj >> 2) * 16384 + r * 128 + ((((2 * jj + (lane >> 4)) & 7) ^ (r & 7)) << 4), x[jj]);
        wg_wait<0>();
        fence_regs(acc);
        if (w == 0) e_arrive_both(sb + B_PE + 8 * 3);
        bar_sync(NB_SC, 256);
        const CUtensorMap* mo = &prm.m[l == 3 ? M_OUT : M_XST];
#pragma unroll
        for (int jj = 0; jj < 8; jj++) {
#pragma unroll
          for (int i = 0; i < 4; i++) x[jj][i] = add_bf16x2(x[jj][i], pack2(acc[8 * jj + 2 * i], acc[8 * jj + 2 * i + 1]));
          stsm4(sb + (jj >> 2) * QSTG + po * 16384 + r * 128 + ((((2 * jj + (lane >> 4)) & 7) ^ (r & 7)) << 4), x[jj][0], x[jj][1], x[jj][2], x[jj][3]);
          if ((jj & 3) == 3) { fence_async_smem(); __syncwarp(); tma_st(mo, pn * 128 + (jj >> 2) * 64, pm * 128 + r0, sb + (jj >> 2) * QSTG + po * 16384 + r0 * 128); }
        }
        bulk_commit();
        if (l < 3) {
          bar_arrive(NB_X, 288);
          float s1[2] = {0.f, 0.f}, s2[2] = {0.f, 0.f};
#pragma unroll
          for (int i = 0; i < 32; i++) {
            const float a = bf_lo(x[i >> 2][i & 3]), c = bf_hi(x[i >> 2][i & 3]);
            s1[i & 1] += a + c; s2[i & 1] = fmaf(a, a, fmaf(c, c, s2[i & 1]));
          }
#pragma unroll
          for (int hh = 0; hh < 2; hh++) { s1[hh] += __shfl_xor_sync(~0u, s1[hh], 1); s2[hh] += __shfl_xor_sync(~0u, s2[hh], 1); }
#pragma unroll
          for (int hh = 0; hh < 2; hh++) {
            s1[hh] += __shfl_xor_sync(~0u, s1[hh], 2); s2[hh] += __shfl_xor_sync(~0u, s2[hh], 2);
            if (qd == 0) g_stats[pn * 2048 + pm * 128 + r0 + g + 8 * hh] = make_float2(s1[hh], s2[hh]);
          }
        }
        bulk_wait_n<0>();
        if (l < 3) bar_arrive(NB_X0, 288);
      }
    }
  }
  asm volatile("barrier.cluster.arrive.relaxed.aligned;\nbarrier.cluster.wait.aligned;" ::: "memory");
}

typedef CUresult (*EncodeFn)(CUtensorMap*, CUtensorMapDataType, cuuint32_t, void*, const cuuint64_t*, const cuuint64_t*, const cuuint32_t*,
                             const cuuint32_t*, CUtensorMapInterleave, CUtensorMapSwizzle, CUtensorMapL2promotion, CUtensorMapFloatOOBfill);

static void make_map(EncodeFn fn, CUtensorMap* m, const void* ptr, int rank, const uint64_t* dims, const uint64_t* strides, const uint32_t* box, CUtensorMapSwizzle sw) {
  cuuint64_t d[5], st[4];
  cuuint32_t bx[5], es[5];
  for (int i = 0; i < rank; i++) { d[i] = dims[i]; bx[i] = box[i]; es[i] = 1; if (i) st[i - 1] = strides[i - 1] * 2; }
  fn(m, CU_TENSOR_MAP_DATA_TYPE_BFLOAT16, rank, (void*)ptr, d, st, bx, es, CU_TENSOR_MAP_INTERLEAVE_NONE, sw,
     CU_TENSOR_MAP_L2_PROMOTION_L2_128B, CU_TENSOR_MAP_FLOAT_OOB_FILL_NONE);
}
static void map2(EncodeFn fn, CUtensorMap* m, const void* ptr, uint64_t inner, uint64_t outer, uint32_t bi, uint32_t bo, CUtensorMapSwizzle sw) {
  const uint64_t d[2] = {inner, outer}, st[1] = {inner};
  const uint32_t bx[2] = {bi, bo};
  make_map(fn, m, ptr, 2, d, st, bx, sw);
}

extern "C" void kernel_launch(void* const* d_in, const int* in_sizes, int n_in, void* d_out, int out_size) {
  (void)in_sizes; (void)n_in; (void)out_size;
  static EncodeFn enc = nullptr;
  static void *xs, *os, *kk, *vv;
  if (!enc) {
    void* p = nullptr;
    cudaDriverEntryPointQueryResult qr;
    cudaGetDriverEntryPoint("cuTensorMapEncodeTiled", &p, cudaEnableDefault, &qr);
    enc = (EncodeFn)p;
    cudaGetSymbolAddress(&xs, g_xs); cudaGetSymbolAddress(&os, g_os); cudaGetSymbolAddress(&kk, g_k); cudaGetSymbolAddress(&vv, g_v);
    cudaFuncSetAttribute(fused_kernel, cudaFuncAttributeMaxDynamicSharedMemorySize, SMEM_BYTES);
  }
  Params prm;
  const CUtensorMapSwizzle S128 = CU_TENSOR_MAP_SWIZZLE_128B, S64 = CU_TENSOR_MAP_SWIZZLE_64B;
  map2(enc, &prm.m[M_X0A], d_in[0], 1024, 2048, 64, 256, S128);
  map2(enc, &prm.m[M_XSA], xs, 1024, 2048, 64, 256, S128);
  for (int t = 0; t < 2; t++) {
    const uint64_t d3[3] = {1024, 1024, 3}, s3[2] = {3072, 1024};
    const uint32_t b3[3] = {64, 64, 3};
    make_map(enc, &prm.m[M_WQA + t], d_in[1 + 3 * t], 3, d3, s3, b3, S128);
    const uint64_t d5[5] = {64, 32, 2, 16, 16}, s5[4] = {1024, 32 * 1024, 64 * 1024, 64};
    const uint32_t b5[5] = {64, 32, 1, 2, 2};
    make_map(enc, &prm.m[M_WOA + t], d_in[2 + 3 * t], 5, d5, s5, b5, S128);
    const uint64_t dr[3] = {64, 2048, 16}, sr[2] = {1024, 64};
    const uint32_t br[3] = {64, 128, 2};
    make_map(enc, &prm.m[M_X0R + t], t ? xs : d_in[0], 3, dr, sr, br, S128);
  }
  map2(enc, &prm.m[M_OS], os, 1024, 2048, 64, 64, S128);
  map2(enc, &prm.m[M_K], kk, 32, 65536, 32, 256, S64);
  map2(enc, &prm.m[M_V], vv, 32, 65536, 32, 256, S64);
  map2(enc, &prm.m[M_XSO], xs, 1024, 2048, 64, 128, S128);
  map2(enc, &prm.m[M_X0H], d_in[0], 1024, 2048, 64, 128, S128);
  map2(enc, &prm.m[M_XST], xs, 1024, 2048, 64, 16, S128);
  map2(enc, &prm.m[M_OUT], d_out, 1024, 2048, 64, 16, S128);
  prm.x0 = (const bf16*)d_in[0];
  prm.wq[0] = (const bf16*)d_in[1]; prm.wq[1] = (const bf16*)d_in[4];
  prm.zero = 0;
  for (int i = 0; i < 128; i++) prm.map[i] = remap(i);
  fused_kernel<<<128, 384, SMEM_BYTES>>>(prm);
}
```

```cpp
#include <cuda_runtime.h>
#include <cuda_bf16.h>
#include <cuda.h>
#include <stdint.h>

typedef __nv_bfloat16 bf16;

__device__ __forceinline__ void wgmma_m64n192k16_ss_tb(float (&d)[96], uint64_t da, uint64_t db, int scale_d) {
  asm volatile("{\n.reg .pred p;\nsetp.ne.b32 p, %98, 0;\n"
    "wgmma.mma_async.sync.aligned.m64n192k16.f32.bf16.bf16 "
    "{%0, %1, %2, %3, %4, %5, %6, %7, %8, %9, %10, %11, %12, %13, %14, %15, "
    "%16, %17, %18, %19, %20, %21, %22, %23, %24, %25, %26, %27, %28, %29, %30, %31, "
    "%32, %33, %34, %35, %36, %37, %38, %39, %40, %41, %42, %43, %44, %45, %46, %47, "
    "%48, %49, %50, %51, %52, %53, %54, %55, %56, %57, %58, %59, %60, %61, %62, %63, "
    "%64, %65, %66, %67, %68, %69, %70, %71, %72, %73, %74, %75, %76, %77, %78, %79, "
    "%80, %81, %82, %83, %84, %85, %86, %87, %88, %89, %90, %91, %92, %93, %94, %95}, "
    "%96, %97, p, 1, 1, 0, 1;\n}\n"
    : "+f"(d[0]), "+f"(d[1]), "+f"(d[2]), "+f"(d[3]), "+f"(d[4]), "+f"(d[5]), "+f"(d[6]), "+f"(d[7]),
      "+f"(d[8]), "+f"(d[9]), "+f"(d[10]), "+f"(d[11]), "+f"(d[12]), "+f"(d[13]), "+f"(d[14]), "+f"(d[15]),
      "+f"(d[16]), "+f"(d[17]), "+f"(d[18]), "+f"(d[19]), "+f"(d[20]), "+f"(d[21]), "+f"(d[22]), "+f"(d[23]),
      "+f"(d[24]), "+f"(d[25]), "+f"(d[26]), "+f"(d[27]), "+f"(d[28]), "+f"(d[29]), "+f"(d[30]), "+f"(d[31]),
      "+f"(d[32]), "+f"(d[33]), "+f"(d[34]), "+f"(d[35]), "+f"(d[36]), "+f"(d[37]), "+f"(d[38]), "+f"(d[39]),
      "+f"(d[40]), "+f"(d[41]), "+f"(d[42]), "+f"(d[43]), "+f"(d[44]), "+f"(d[45]), "+f"(d[46]), "+f"(d[47]),
      "+f"(d[48]), "+f"(d[49]), "+f"(d[50]), "+f"(d[51]), "+f"(d[52]), "+f"(d[53]), "+f"(d[54]), "+f"(d[55]),
      "+f"(d[56]), "+f"(d[57]), "+f"(d[58]), "+f"(d[59]), "+f"(d[60]), "+f"(d[61]), "+f"(d[62]), "+f"(d[63]),
      "+f"(d[64]), "+f"(d[65]), "+f"(d[66]), "+f"(d[67]), "+f"(d[68]), "+f"(d[69]), "+f"(d[70]), "+f"(d[71]),
      "+f"(d[72]), "+f"(d[73]), "+f"(d[74]), "+f"(d[75]), "+f"(d[76]), "+f"(d[77]), "+f"(d[78]), "+f"(d[79]),
      "+f"(d[80]), "+f"(d[81]), "+f"(d[82]), "+f"(d[83]), "+f"(d[84]), "+f"(d[85]), "+f"(d[86]), "+f"(d[87]),
      "+f"(d[88]), "+f"(d[89]), "+f"(d[90]), "+f"(d[91]), "+f"(d[92]), "+f"(d[93]), "+f"(d[94]), "+f"(d[95])
    : "l"(da), "l"(db), "r"(scale_d));
}

__device__ __forceinline__ void wgmma_m64n128k16_ss_tb(float (&d)[64], uint64_t da, uint64_t db, int scale_d) {
  asm volatile("{\n.reg .pred p;\nsetp.ne.b32 p, %66, 0;\n"
    "wgmma.mma_async.sync.aligned.m64n128k16.f32.bf16.bf16 "
    "{%0, %1, %2, %3, %4, %5, %6, %7, %8, %9, %10, %11, %12, %13, %14, %15, "
    "%16, %17, %18, %19, %20, %21, %22, %23, %24, %25, %26, %27, %28, %29, %30, %31, "
    "%32, %33, %34, %35, %36, %37, %38, %39, %40, %41, %42, %43, %44, %45, %46, %47, "
    "%48, %49, %50, %51, %52, %53, %54, %55, %56, %57, %58, %59, %60, %61, %62, %63}, "
    "%64, %65, p, 1, 1, 0, 1;\n}\n"
    : "+f"(d[0]), "+f"(d[1]), "+f"(d[2]), "+f"(d[3]), "+f"(d[4]), "+f"(d[5]), "+f"(d[6]), "+f"(d[7]),
      "+f"(d[8]), "+f"(d[9]), "+f"(d[10]), "+f"(d[11]), "+f"(d[12]), "+f"(d[13]), "+f"(d[14]), "+f"(d[15]),
      "+f"(d[16]), "+f"(d[17]), "+f"(d[18]), "+f"(d[19]), "+f"(d[20]), "+f"(d[21]), "+f"(d[22]), "+f"(d[23]),
      "+f"(d[24]), "+f"(d[25]), "+f"(d[26]), "+f"(d[27]), "+f"(d[28]), "+f"(d[29]), "+f"(d[30]), "+f"(d[31]),
      "+f"(d[32]), "+f"(d[33]), "+f"(d[34]), "+f"(d[35]), "+f"(d[36]), "+f"(d[37]), "+f"(d[38]), "+f"(d[39]),
      "+f"(d[40]), "+f"(d[41]), "+f"(d[42]), "+f"(d[43]), "+f"(d[44]), "+f"(d[45]), "+f"(d[46]), "+f"(d[47]),
      "+f"(d[48]), "+f"(d[49]), "+f"(d[50]), "+f"(d[51]), "+f"(d[52]), "+f"(d[53]), "+f"(d[54]), "+f"(d[55]),
      "+f"(d[56]), "+f"(d[57]), "+f"(d[58]), "+f"(d[59]), "+f"(d[60]), "+f"(d[61]), "+f"(d[62]), "+f"(d[63])
    : "l"(da), "l"(db), "r"(scale_d));
}

__device__ __forceinline__ void wgmma_m64n32k16_rs_nb_h(float (&d)[16], uint32_t a0, uint32_t a1, uint32_t a2, uint32_t a3, uint64_t db, int scale_d) {
  asm volatile("{\n.reg .pred p;\nsetp.ne.b32 p, %21, 0;\n"
    "wgmma.mma_async.sync.aligned.m64n32k16.f32.f16.f16 "
    "{%0, %1, %2, %3, %4, %5, %6, %7, %8, %9, %10, %11, %12, %13, %14, %15}, "
    "{%16, %17, %18, %19}, %20, p, 1, 1, 0;\n}\n"
    : "+f"(d[0]), "+f"(d[1]), "+f"(d[2]), "+f"(d[3]), "+f"(d[4]), "+f"(d[5]), "+f"(d[6]), "+f"(d[7]),
      "+f"(d[8]), "+f"(d[9]), "+f"(d[10]), "+f"(d[11]), "+f"(d[12]), "+f"(d[13]), "+f"(d[14]), "+f"(d[15])
    : "r"(a0), "r"(a1), "r"(a2), "r"(a3), "l"(db), "r"(scale_d));
}

__device__ __forceinline__ void wgmma_m64n32k16_rs_nb_hh(uint32_t (&d)[8], uint32_t a0, uint32_t a1, uint32_t a2, uint32_t a3, uint64_t db, int scale_d) {
  asm volatile("{\n.reg .pred p;\nsetp.ne.b32 p, %13, 0;\n"
    "wgmma.mma_async.sync.aligned.m64n32k16.f16.f16.f16 "
    "{%0, %1, %2, %3, %4, %5, %6, %7}, "
    "{%8, %9, %10, %11}, %12, p, 1, 1, 0;\n}\n"
    : "+r"(d[0]), "+r"(d[1]), "+r"(d[2]), "+r"(d[3]), "+r"(d[4]), "+r"(d[5]), "+r"(d[6]), "+r"(d[7])
    : "r"(a0), "r"(a1), "r"(a2), "r"(a3), "l"(db), "r"(scale_d));
}

__device__ __forceinline__ void wgmma_m64n64k16_rs_nb_h(float (&d)[32], uint32_t a0, uint32_t a1, uint32_t a2, uint32_t a3, uint64_t db, int scale_d) {
  asm volatile("{\n.reg .pred p;\nsetp.ne.b32 p, %37, 0;\n"
    "wgmma.mma_async.sync.aligned.m64n64k16.f32.f16.f16 "
    "{%0, %1, %2, %3, %4, %5, %6, %7, %8, %9, %10, %11, %12, %13, %14, %15, "
    "%16, %17, %18, %19, %20, %21, %22, %23, %24, %25, %26, %27, %28, %29, %30, %31}, "
    "{%32, %33, %34, %35}, %36, p, 1, 1, 0;\n}\n"
    : "+f"(d[0]), "+f"(d[1]), "+f"(d[2]), "+f"(d[3]), "+f"(d[4]), "+f"(d[5]), "+f"(d[6]), "+f"(d[7]),
      "+f"(d[8]), "+f"(d[9]), "+f"(d[10]), "+f"(d[11]), "+f"(d[12]), "+f"(d[13]), "+f"(d[14]), "+f"(d[15]),
      "+f"(d[16]), "+f"(d[17]), "+f"(d[18]), "+f"(d[19]), "+f"(d[20]), "+f"(d[21]), "+f"(d[22]), "+f"(d[23]),
      "+f"(d[24]), "+f"(d[25]), "+f"(d[26]), "+f"(d[27]), "+f"(d[28]), "+f"(d[29]), "+f"(d[30]), "+f"(d[31])
    : "r"(a0), "r"(a1), "r"(a2), "r"(a3), "l"(db), "r"(scale_d));
}

__device__ __forceinline__ void wgmma_m64n64k16_rs_nb_hh(uint32_t (&d)[16], uint32_t a0, uint32_t a1, uint32_t a2, uint32_t a3, uint64_t db, int scale_d) {
  asm volatile("{\n.reg .pred p;\nsetp.ne.b32 p, %21, 0;\n"
    "wgmma.mma_async.sync.aligned.m64n64k16.f16.f16.f16 "
    "{%0, %1, %2, %3, %4, %5, %6, %7, %8, %9, %10, %11, %12, %13, %14, %15}, "
    "{%16, %17, %18, %19}, %20, p, 1, 1, 0;\n}\n"
    : "+r"(d[0]), "+r"(d[1]), "+r"(d[2]), "+r"(d[3]), "+r"(d[4]), "+r"(d[5]), "+r"(d[6]), "+r"(d[7]),
      "+r"(d[8]), "+r"(d[9]), "+r"(d[10]), "+r"(d[11]), "+r"(d[12]), "+r"(d[13]), "+r"(d[14]), "+r"(d[15])
    : "r"(a0), "r"(a1), "r"(a2), "r"(a3), "l"(db), "r"(scale_d));
}

__device__ __forceinline__ void wgmma_m64n40k16_rs_tb(float (&d)[20], uint32_t a0, uint32_t a1, uint32_t a2, uint32_t a3, uint64_t db, int scale_d) {
  asm volatile("{\n.reg .pred p;\nsetp.ne.b32 p, %25, 0;\n"
    "wgmma.mma_async.sync.aligned.m64n40k16.f32.bf16.bf16 "
    "{%0, %1, %2, %3, %4, %5, %6, %7, %8, %9, %10, %11, %12, %13, %14, %15, "
    "%16, %17, %18, %19}, "
    "{%20, %21, %22, %23}, %24, p, 1, 1, 1;\n}\n"
    : "+f"(d[0]), "+f"(d[1]), "+f"(d[2]), "+f"(d[3]), "+f"(d[4]), "+f"(d[5]), "+f"(d[6]), "+f"(d[7]),
      "+f"(d[8]), "+f"(d[9]), "+f"(d[10]), "+f"(d[11]), "+f"(d[12]), "+f"(d[13]), "+f"(d[14]), "+f"(d[15]),
      "+f"(d[16]), "+f"(d[17]), "+f"(d[18]), "+f"(d[19])
    : "r"(a0), "r"(a1), "r"(a2), "r"(a3), "l"(db), "r"(scale_d));
}

#define DEVINL __device__ __forceinline__
DEVINL void pin(uint32_t z) { asm volatile("{\n.reg .pred p;\nsetp.ne.u32 p, %0, 0;\nPIN:\n@p bra.uni PIN;\n}" ::"r"(z) : "memory"); }
DEVINL void wg_fence() { asm volatile("wgmma.fence.sync.aligned;" ::: "memory"); }
DEVINL void wg_commit() { asm volatile("wgmma.commit_group.sync.aligned;" ::: "memory"); }
template <int N> DEVINL void wg_wait() { asm volatile("wgmma.wait_group.sync.aligned %0;" ::"n"(N) : "memory"); }
DEVINL uint64_t mkdesc(uint32_t addr, uint32_t lbo, uint32_t sbo, int sw) {
  return (uint64_t)((addr & 0x3FFFF) >> 4) | ((uint64_t)(lbo >> 4) << 16) | ((uint64_t)(sbo >> 4) << 32) | ((uint64_t)sw << 62);
}
DEVINL void mbar_init(uint32_t bar, uint32_t cnt) { asm volatile("mbarrier.init.shared::cta.b64 [%0], %1;" ::"r"(bar), "r"(cnt) : "memory"); }
DEVINL void mbar_arrive(uint32_t bar) { asm volatile("mbarrier.arrive.shared::cta.b64 _, [%0];" ::"r"(bar) : "memory"); }
DEVINL bool mbar_try(uint32_t bar, uint32_t parity) {
  uint32_t ok;
  asm volatile("{\n.reg .pred p;\nmbarrier.try_wait.parity.shared::cta.b64 p, [%1], %2;\nselp.u32 %0, 1, 0, p;\n}" : "=r"(ok) : "r"(bar), "r"(parity) : "memory");
  return ok;
}
DEVINL bool mbar_test(uint32_t bar, uint32_t parity) {
  uint32_t ok;
  asm volatile("{\n.reg .pred p;\nmbarrier.test_wait.parity.shared::cta.b64 p, [%1], %2;\nselp.u32 %0, 1, 0, p;\n}" : "=r"(ok) : "r"(bar), "r"(parity) : "memory");
  return ok;
}
DEVINL void mbar_hint(uint32_t bar, uint32_t parity) {
#pragma unroll 1
  for (uint32_t n = 0; n < 16u; n++) if (mbar_try(bar, parity)) break;
}
DEVINL void mbar_wait(uint32_t bar, uint32_t parity) {
#pragma unroll 1
  for (uint32_t n = 0; n < 100000u; n++) if (mbar_try(bar, parity)) break;
}
#define EL(txt) "{\n.reg .pred pe;\nelect.sync _|pe, 0xffffffff;\n@pe " txt "\n}"
DEVINL void e_expect_tx(uint32_t bar, uint32_t bytes) { asm volatile(EL("mbarrier.arrive.expect_tx.shared::cta.b64 _, [%0], %1;") ::"r"(bar), "r"(bytes) : "memory"); }
DEVINL void e_arrive(uint32_t bar) { asm volatile(EL("mbarrier.arrive.shared::cta.b64 _, [%0];") ::"r"(bar) : "memory"); }
DEVINL void e_red(uint32_t* p) { asm volatile(EL("red.release.gpu.global.add.u32 [%0], 1;") ::"l"(p) : "memory"); }
DEVINL void e_red_relaxed(uint32_t* p) { asm volatile(EL("red.relaxed.gpu.global.add.u32 [%0], 1;") ::"l"(p) : "memory"); }
DEVINL void tma_ld(uint32_t dst, const CUtensorMap* m, int c0, int c1, uint32_t bar) {
  asm volatile(EL("cp.async.bulk.tensor.2d.shared::cluster.global.mbarrier::complete_tx::bytes [%0], [%1, {%3, %4}], [%2];")
               ::"r"(dst), "l"(m), "r"(bar), "r"(c0), "r"(c1) : "memory");
}
DEVINL void tma_ld3(uint32_t dst, const CUtensorMap* m, int c0, int c1, int c2, uint32_t bar) {
  asm volatile(EL("cp.async.bulk.tensor.3d.shared::cluster.global.mbarrier::complete_tx::bytes [%0], [%1, {%3, %4, %5}], [%2];")
               ::"r"(dst), "l"(m), "r"(bar), "r"(c0), "r"(c1), "r"(c2) : "memory");
}
DEVINL void tma_ld5(uint32_t dst, const CUtensorMap* m, int c2, int c3, int c4, uint32_t bar) {
  asm volatile(EL("cp.async.bulk.tensor.5d.shared::cluster.global.mbarrier::complete_tx::bytes [%0], [%1, {0, 0, %3, %4, %5}], [%2];")
               ::"r"(dst), "l"(m), "r"(bar), "r"(c2), "r"(c3), "r"(c4) : "memory");
}
DEVINL void tma_ld_mc(uint32_t dst, const CUtensorMap* m, int c0, int c1, uint32_t bar) {
  asm volatile(EL("cp.async.bulk.tensor.2d.shared::cluster.global.mbarrier::complete_tx::bytes.multicast::cluster [%0], [%1, {%3, %4}], [%2], %5;")
               ::"r"(dst), "l"(m), "r"(bar), "r"(c0), "r"(c1), "h"((uint16_t)3) : "memory");
}
DEVINL void e_arrive_both(uint32_t bar) {
  asm volatile("{\n.reg .pred pe;\n.reg .b32 r0, r1;\nelect.sync _|pe, 0xffffffff;\nmapa.shared::cluster.u32 r0, %0, 0;\nmapa.shared::cluster.u32 r1, %0, 1;\n"
               "@pe mbarrier.arrive.shared::cluster.b64 _, [r0];\n@pe mbarrier.arrive.shared::cluster.b64 _, [r1];\n}" ::"r"(bar) : "memory");
}
DEVINL void tma_st(const CUtensorMap* m, int c0, int c1, uint32_t src) {
  asm volatile(EL("cp.async.bulk.tensor.2d.global.shared::cta.bulk_group [%0, {%2, %3}], [%1];") ::"l"(m), "r"(src), "r"(c0), "r"(c1) : "memory");
}
DEVINL void bulk_commit() { asm volatile("cp.async.bulk.commit_group;" ::: "memory"); }
template <int N> DEVINL void bulk_wait_n() { asm volatile("cp.async.bulk.wait_group %0;\nbar.warp.sync 0xffffffff;" ::"n"(N) : "memory"); }
DEVINL void l2_prefetch(const void* g, uint32_t bytes) { asm volatile(EL("cp.async.bulk.prefetch.L2.global [%0], %1;") ::"l"(g), "r"(bytes) : "memory"); }
DEVINL void fence_async_smem() { asm volatile("fence.proxy.async.shared::cta;" ::: "memory"); }
DEVINL void fence_async_gl() { asm volatile("fence.proxy.async.global;" ::: "memory"); }
DEVINL void cluster_wait() { asm volatile("barrier.cluster.wait.aligned;" ::: "memory"); }
DEVINL void bar_sync(int id, int n) { asm volatile("bar.sync %0, %1;" ::"r"(id), "r"(n) : "memory"); }
DEVINL void bar_arrive(int id, int n) { asm volatile("bar.arrive %0, %1;" ::"r"(id), "r"(n) : "memory"); }
DEVINL uint32_t ld_acquire(const uint32_t* p) { uint32_t v; asm volatile("ld.acquire.gpu.global.u32 %0, [%1];" : "=r"(v) : "l"(p) : "memory"); return v; }
DEVINL void watch(const uint32_t* p, uint32_t target, uint32_t all, uint32_t tag, uint32_t slot) {
  uint32_t seen = 0;
#pragma unroll 1
  for (uint32_t n = 0; n < 200000u && seen != all; n++) {
    const uint32_t m = __ballot_sync(~0u, (int)(ld_acquire(p) - target) >= 0) & all;
    if (m != seen) { seen = m; asm volatile("st.release.cta.shared.u32 [%0], %1;" ::"r"(slot), "r"(tag << 16 | m) : "memory"); }
  }
}
template <bool RELAXED = false> DEVINL void await_bit(uint32_t slot, uint32_t tag, int j, uint32_t& rdy) {
  if ((rdy >> j) & 1) return;
#pragma unroll 1
  for (uint32_t n = 0; n < 8000000u; n++) {
    uint32_t v;
    asm volatile("ld.acquire.cta.shared.u32 %0, [%1];" : "=r"(v) : "r"(slot) : "memory");
    if ((v >> 16) == tag && ((v >> j) & 1)) { rdy = v; break; }
    if (RELAXED) __nanosleep(200);
  }
  asm volatile("fence.proxy.async.global;" ::: "memory");
}
DEVINL void poll_ge(const uint32_t* p, uint32_t target) {
#pragma unroll 1
  for (uint32_t n = 0; n < 200000u; n++) if (__all_sync(~0u, (int)(ld_acquire(p) - target) >= 0)) break;
}
DEVINL int lane_id() { int v; asm volatile("mov.u32 %0, %%laneid;" : "=r"(v)); return v; }
__host__ DEVINL int remap(int v) {
  const int c = v >> 1, u = c - 36, r = (u * 37) >> 8;
  const int L = c < 4 ? 32 + 8 * c : c < 36 ? c - 4 : 33 + u + r;
  return 2 * L + (v & 1);
}
DEVINL int block_id() { int v; asm volatile("mov.u32 %0, %%ctaid.x;" : "=r"(v)); return v; }
#define cta_id() prm.map[block_id()]
#define IDS() const int lane = lane_id(), b = cta_id(), bm = b >> 4, bn = b & 15, rank = b & 1, pm = 2 * bm + (bn >> 3), pn = bn & 7, po = pm & 1; \
  (void)lane; (void)bm; (void)bn; (void)rank; (void)pm; (void)pn; (void)po
DEVINL void st_tagged(unsigned long long* p, uint32_t v, uint32_t tag) {
  asm volatile("{\n.reg .b64 t;\nmov.b64 t, {%1, %2};\nst.relaxed.gpu.global.b64 [%0], t;\n}" ::"l"(p), "r"(v), "r"(tag) : "memory");
}
DEVINL float ex2(float x) { float y; asm("ex2.approx.ftz.f32 %0, %1;" : "=f"(y) : "f"(x)); return y; }
DEVINL float rcp(float x) { float y; asm("rcp.approx.ftz.f32 %0, %1;" : "=f"(y) : "f"(x)); return y; }
DEVINL uint32_t pack2(float lo, float hi) { uint32_t r; asm("cvt.rn.bf16x2.f32 %0, %1, %2;" : "=r"(r) : "f"(hi), "f"(lo)); return r; }
DEVINL float bf_lo(uint32_t w) { return __uint_as_float(w << 16); }
DEVINL float bf_hi(uint32_t w) { return __uint_as_float(w & 0xFFFF0000u); }
DEVINL float bf_round(float x) { return bf_lo(pack2(x, 0.f)); }
DEVINL uint32_t add_bf16x2(uint32_t a, uint32_t b) { uint32_t r; asm("add.rn.bf16x2 %0, %1, %2;" : "=r"(r) : "r"(a), "r"(b)); return r; }
DEVINL void stsm4(uint32_t addr, uint32_t a, uint32_t b, uint32_t c, uint32_t d) {
  asm volatile("stmatrix.sync.aligned.m8n8.x4.shared.b16 [%0], {%1, %2, %3, %4};" ::"r"(addr), "r"(a), "r"(b), "r"(c), "r"(d) : "memory");
}
DEVINL void ldsm4(uint32_t addr, uint32_t (&r)[4]) {
  asm volatile("ldmatrix.sync.aligned.m8n8.x4.shared.b16 {%0, %1, %2, %3}, [%4];" : "=r"(r[0]), "=r"(r[1]), "=r"(r[2]), "=r"(r[3]) : "r"(addr) : "memory");
}
DEVINL void ldsm4t(uint32_t addr, uint32_t (&r)[4]) {
  asm volatile("ldmatrix.sync.aligned.m8n8.x4.trans.shared.b16 {%0, %1, %2, %3}, [%4];" : "=r"(r[0]), "=r"(r[1]), "=r"(r[2]), "=r"(r[3]) : "r"(addr) : "memory");
}
DEVINL void sts128(uint32_t addr, uint32_t a, uint32_t b, uint32_t c, uint32_t d) {
  asm volatile("st.shared.v4.b32 [%0], {%1, %2, %3, %4};" ::"r"(addr), "r"(a), "r"(b), "r"(c), "r"(d) : "memory");
}
DEVINL float4 lds128f(uint32_t addr) { float4 v; asm volatile("ld.shared.v4.f32 {%0, %1, %2, %3}, [%4];" : "=f"(v.x), "=f"(v.y), "=f"(v.z), "=f"(v.w) : "r"(addr) : "memory"); return v; }
DEVINL float lds32f(uint32_t addr) { float v; asm volatile("ld.shared.f32 %0, [%1];" : "=f"(v) : "r"(addr) : "memory"); return v; }
DEVINL float2 lds64f(uint32_t addr) { float2 v; asm volatile("ld.shared.v2.f32 {%0, %1}, [%2];" : "=f"(v.x), "=f"(v.y) : "r"(addr) : "memory"); return v; }
DEVINL void mma16816(float (&d)[4], uint32_t a0, uint32_t a1, uint32_t a2, uint32_t a3, uint32_t b0, uint32_t b1) {
  asm("mma.sync.aligned.m16n8k16.row.col.f32.bf16.bf16.f32 {%0, %1, %2, %3}, {%4, %5, %6, %7}, {%8, %9}, {%0, %1, %2, %3};"
               : "+f"(d[0]), "+f"(d[1]), "+f"(d[2]), "+f"(d[3]) : "r"(a0), "r"(a1), "r"(a2), "r"(a3), "r"(b0), "r"(b1));
}
DEVINL void mma16816h(float (&d)[4], uint32_t a0, uint32_t a1, uint32_t a2, uint32_t a3, uint32_t b0, uint32_t b1) {
  asm("mma.sync.aligned.m16n8k16.row.col.f32.f16.f16.f32 {%0, %1, %2, %3}, {%4, %5, %6, %7}, {%8, %9}, {%0, %1, %2, %3};"
               : "+f"(d[0]), "+f"(d[1]), "+f"(d[2]), "+f"(d[3]) : "r"(a0), "r"(a1), "r"(a2), "r"(a3), "r"(b0), "r"(b1));
}
template <int N> DEVINL void fence_regs(uint32_t (&d)[N]) {
#pragma unroll
  for (int i = 0; i < N; i++) asm volatile("" : "+r"(d[i])::"memory");
}
template <int N> DEVINL void fence_regs(float (&d)[N]) {
#pragma unroll
  for (int i = 0; i < N; i++) asm volatile("" : "+f"(d[i])::"memory");
}

__device__ __align__(1024) bf16 g_xs[2048 * 1024];
__device__ __align__(1024) bf16 g_os[2048 * 1024];
__device__ __align__(1024) bf16 g_k[32 * 2048 * 32];
__device__ __align__(1024) bf16 g_v[32 * 2048 * 32];
__device__ __align__(128) float2 g_stats[8 * 2048];
__device__ __align__(16) float g_csp[2 * 16 * 8 * 192];
__device__ __align__(128) float g_kn[2 * 128 * 32];
__device__ unsigned long long g_halo[2 * 128 * 32 * 32];
__device__ __align__(128) uint32_t g_cnt[256 * 32];
__device__ uint32_t g_epoch;

DEVINL uint32_t* cnt_x(int l, int bm) { return g_cnt + (l * 8 + bm) * 32; }
DEVINL uint32_t* cnt_o(int l, int pm, int h) { return g_cnt + (32 + (l * 16 + pm) * 2 + h) * 32; }
DEVINL uint32_t* cnt_kv(int lb, int bn) { return g_cnt + (160 + lb * 16 + bn) * 32; }
DEVINL uint32_t* cnt_ad(int bn) { return g_cnt + (192 + bn) * 32; }
DEVINL uint32_t* cnt_cs(int t, int bn) { return g_cnt + (208 + t * 16 + bn) * 32; }

DEVINL int qord(int i, int l, int pn) { return l == 0 ? i : i < 4 ? ((2 * pn) ^ (i & 2)) + (i & 1) : i - 4 < 2 * (pn & 6) ? i - 4 : i; }
struct Params {
  CUtensorMap m[17];
  const bf16* x0;
  const bf16* wq[2];
  uint32_t zero;
  int map[128];
};
enum { M_X0A = 0, M_XSA, M_WQA, M_WQB, M_WOA, M_WOB, M_OS, M_K, M_V, M_X0R, M_XSR, M_XSO, M_OUT, M_XST, M_X0H, M_K4, M_V4, M_COUNT };

constexpr uint32_t QSTG = 57344;
constexpr uint32_t T0 = 65536, TSTG = 32768;
constexpr uint32_t ONES = 230400;
constexpr uint32_t PSTG = 32768, RES = 196608;
constexpr uint32_t ASC = 17408;
constexpr uint32_t ROWST = 229376, COLS = 231424, BARS = 232192, SMEM_BYTES = 232448;
constexpr uint32_t B_QF = BARS, B_QE = BARS + 32, B_TF = BARS + 64, B_TE = BARS + 96, B_PF = BARS + 128, B_PE = BARS + 176,
                   B_RF = BARS + 224, W_X = BARS + 232, W_O = BARS + 236, B_QL = BARS + 240, B_PA = BARS + 248;
enum { NB_ST = 1, NB_KV = 2  , NB_DONE = 3, NB_SC = 4, NB_SIG = 5  , NB_KN = 9  , NB_X = 11, NB_HALO = 12  , NB_X0 = 15 };

DEVINL uint32_t pslot_b(uint32_t s, int l) { return ((((l & 1) ? 0x320415u : 0x6A789Bu) >> (4 * s)) & 15) * 16384u; }
DEVINL uint32_t pslot_a(uint32_t s, int l) { return ((((l & 1) ? 0xBA7896u : 0x320415u) >> (4 * s)) & 15) * 16384u; }

#define G1 2
#define G2 0
#define G3 2
#define KC (11 + 2 * wg)
#define NQ 32
#define OA 0x10
#define OB 0x10
#define LAG 2
#define QK_A wgmma_m64n32k16_rs_nb_h
#define QK_B wgmma_m64n32k16_rs_nb_hh
constexpr float QSCALE = 0.17677669529663687f * 1.4426950408889634f;

DEVINL uint32_t hfma2(uint32_t a, uint32_t b, uint32_t c) { uint32_t r; asm("fma.rn.f16x2 %0, %1, %2, %3;" : "=r"(r) : "r"(a), "r"(b), "r"(c)); return r; }
DEVINL uint32_t pack2h(float lo, float hi) { uint32_t r; asm("cvt.rn.f16x2.f32 %0, %1, %2;" : "=r"(r) : "f"(hi), "f"(lo)); return r; }
DEVINL uint32_t h2_to_bf2(uint32_t h) {
  float a, b;
  asm("{\n.reg .b16 l, h;\nmov.b32 {l, h}, %2;\ncvt.f32.f16 %0, l;\ncvt.f32.f16 %1, h;\n}" : "=f"(a), "=f"(b) : "r"(h));
  return pack2(a, b);
}
DEVINL uint32_t exp2_h2(uint32_t s) {
  const uint32_t r = hfma2(s, 0x00800080u, 0x007E007Eu);
  const uint32_t g = hfma2(hfma2(r, 0xF800F800u, 0x33FD33FDu), 0x44004400u, s);
  return r * 128u + hfma2(hfma2(g, g, 0x0DE10DE1u), g, 0x00300030u);
}
constexpr uint32_t NOT_F16 = 0x7FC00000u, K_LO = 0x35000000u  ;
DEVINL uint32_t f16_class(uint32_t norm2, uint32_t lo) { return norm2 - lo > 0x4E800000u - lo ? NOT_F16 : norm2; }

DEVINL void attn_slow(const uint32_t (&q)[8], float up, int head, const float* kn, float (&res)[20], int lane) {
  const int g = lane >> 2, qd = lane & 3;
  const bf16* kb = g_k + (size_t)head * 2048 * 32;
  const bf16* vb = g_v + (size_t)head * 2048 * 32;
  float o[4][4], m0 = -INFINITY, m1 = -INFINITY, l0 = 0.f, l1 = 0.f;
#pragma unroll
  for (int j = 0; j < 4; j++) { o[j][0] = o[j][1] = o[j][2] = o[j][3] = 0.f; }
#pragma unroll 1
  for (int k0 = 0; k0 < 2048; k0 += 16) {
    float s[2][4];
    const bool kh = __float_as_uint(__ldcg(kn + (k0 >> 8) * 32 + ((k0 >> 6) & 1) * 8 + ((k0 >> 7) & 1) * 4 + ((k0 >> 4) & 3))) != NOT_F16;
#pragma unroll
    for (int nt = 0; nt < 2; nt++) {
      s[nt][0] = s[nt][1] = s[nt][2] = s[nt][3] = 0.f;
      const uint32_t* kp = (const uint32_t*)(kb + (size_t)(k0 + nt * 8 + g) * 32) + qd;
      uint32_t kf[4];
#pragma unroll
      for (int i = 0; i < 4; i++) { kf[i] = __ldcg(kp + 4 * i); if (kh) kf[i] = h2_to_bf2(kf[i]); }
      mma16816(s[nt], q[0], q[1], q[2], q[3], kf[0], kf[1]);
      mma16816(s[nt], q[4], q[5], q[6], q[7], kf[2], kf[3]);
      s[nt][0] *= up; s[nt][1] *= up; s[nt][2] *= up; s[nt][3] *= up;
    }
    float a0 = fmaxf(fmaxf(s[0][0], s[0][1]), fmaxf(s[1][0], s[1][1]));
    float a1 = fmaxf(fmaxf(s[0][2], s[0][3]), fmaxf(s[1][2], s[1][3]));
    a0 = fmaxf(a0, __shfl_xor_sync(~0u, a0, 1)); a0 = fmaxf(a0, __shfl_xor_sync(~0u, a0, 2));
    a1 = fmaxf(a1, __shfl_xor_sync(~0u, a1, 1)); a1 = fmaxf(a1, __shfl_xor_sync(~0u, a1, 2));
    const float n0 = fmaxf(m0, a0), n1 = fmaxf(m1, a1);
    const float c0 = (m0 == n0) ? 1.f : ex2(m0 - n0), c1 = (m1 == n1) ? 1.f : ex2(m1 - n1);
    m0 = n0; m1 = n1;
    const uint32_t p0 = pack2(ex2(s[0][0] - n0), ex2(s[0][1] - n0)), p1 = pack2(ex2(s[0][2] - n1), ex2(s[0][3] - n1));
    const uint32_t p2 = pack2(ex2(s[1][0] - n0), ex2(s[1][1] - n0)), p3 = pack2(ex2(s[1][2] - n1), ex2(s[1][3] - n1));
    l0 = l0 * c0 + bf_lo(p0) + bf_hi(p0) + bf_lo(p2) + bf_hi(p2);
    l1 = l1 * c1 + bf_lo(p1) + bf_hi(p1) + bf_lo(p3) + bf_hi(p3);
#pragma unroll
    for (int j = 0; j < 4; j++) {
      o[j][0] *= c0; o[j][1] *= c0; o[j][2] *= c1; o[j][3] *= c1;
      const unsigned short* vp = (const unsigned short*)(vb + (size_t)(k0 + 2 * qd) * 32 + j * 8 + g);
      const uint32_t b0 = (uint32_t)__ldcg(vp) | ((uint32_t)__ldcg(vp + 32) << 16);
      const uint32_t b1 = (uint32_t)__ldcg(vp + 256) | ((uint32_t)__ldcg(vp + 288) << 16);
      mma16816(o[j], p0, p1, p2, p3, b0, b1);
    }
  }
  l0 += __shfl_xor_sync(~0u, l0, 1); l0 += __shfl_xor_sync(~0u, l0, 2);
  l1 += __shfl_xor_sync(~0u, l1, 1); l1 += __shfl_xor_sync(~0u, l1, 2);
#pragma unroll
  for (int j = 0; j < 4; j++) { res[4 * j] = o[j][0]; res[4 * j + 1] = o[j][1]; res[4 * j + 2] = o[j][2]; res[4 * j + 3] = o[j][3]; }
  res[16] = l0; res[18] = l1;
}

__global__ void __cluster_dims__(2, 1, 1) __launch_bounds__(384, 1) fused_kernel(const __grid_constant__ Params prm) {
  extern __shared__ __align__(1024) char smem[];
  const uint32_t sb = (uint32_t)__cvta_generic_to_shared(smem);
  const int tid = threadIdx.x, lane = tid & 31;
  const int wg = __shfl_sync(0xffffffffu, tid >> 7, 0);
  const int w = __shfl_sync(0xffffffffu, (tid >> 5) & 3, 0);
  const int bm = remap(blockIdx.x) >> 4, bn = remap(blockIdx.x) & 15;

  auto first_tile = [&](int kt) {
    e_expect_tx(sb + B_QF + 8 * kt, QSTG);
    tma_ld(sb + kt * QSTG, &prm.m[M_X0A], kt * 64, bm * 256, sb + B_QF + 8 * kt);
    tma_ld3(sb + kt * QSTG + 32768, &prm.m[M_WQA], bn * 64, kt * 64, 0, sb + B_QF + 8 * kt);
  };
  if (wg < 2) {
  } else if (w == 0) {
    if (lane < 4) { mbar_init(sb + B_QF + 8 * lane, 1); asm volatile("fence.mbarrier_init.release.cluster;" ::: "memory"); }
    __syncwarp();
    first_tile(0);
  } else if (w == 1) {
    if (lane == 25) *(uint2*)(smem + W_X) = make_uint2(0u, 0u);
    else if (lane < 28) {
      mbar_init(sb + B_QE + 8 * lane, lane < 4 ? 4 : lane < 8 ? 1 : lane < 12 ? 2 : lane < 18 ? 1 : lane < 24 ? 4 : lane < 27 ? 1 : 2);
      asm volatile("fence.mbarrier_init.release.cluster;" ::: "memory");
    }
  } else if (w == 2 && lane < M_COUNT) {
    asm volatile("prefetch.tensormap [%0];" ::"l"(&prm.m[lane]) : "memory");
  }
  __syncthreads();
  asm volatile("barrier.cluster.arrive.relaxed.aligned;" ::: "memory");

  if (wg == 2) {
    asm volatile("setmaxnreg.dec.sync.aligned.u32 56;");
    const uint32_t ep1 = *(volatile uint32_t*)&g_epoch + 1;
    if (w == 0) {
      first_tile(1);
      mbar_wait(sb + B_QF, 0);
      first_tile(2); first_tile(3);
#pragma unroll 1
      for (int kt = 4; kt < 16; kt++) l2_prefetch(prm.wq[0] + kt * 196608 + blockIdx.x * 1536, 3072);
      cluster_wait();
#pragma unroll 1
      for (int l = 0; l < 4; l++) {
        IDS();
        const CUtensorMap* mw = &prm.m[M_WQA + (l & 1)];
        const CUtensorMap* mx = &prm.m[l == 0 ? M_X0A : M_XSA];
        const CUtensorMap* mh = &prm.m[l == 0 ? M_X0H : M_XSO];
        const CUtensorMap* mo = &prm.m[M_WOA + (l & 1)];
        auto q_b = [&](int i) {
          const int s = i & 3;
          mbar_wait(sb + B_QE + 8 * s, ((i >> 2) & 1) ^ 1);
          e_expect_tx(sb + B_QF + 8 * s, QSTG);
          tma_ld3(sb + s * QSTG + 32768, mw, bn * 64, qord(i, l, pn) * 64, 0, sb + B_QF + 8 * s);
        };
        uint32_t rdy = l ? 0u : ~0u;
        auto q_a = [&](int i) {
          const int kt = qord(i, l, pn);
          await_bit(sb + W_X, l, kt >> 1, rdy);
          if (i < 4) tma_ld(sb + i * QSTG, mx, kt * 64, bm * 256, sb + B_QF + 8 * i);
          else tma_ld_mc(sb + (i & 3) * QSTG + rank * 16384, mh, kt * 64, bm * 256 + rank * 128, sb + B_QF + 8 * (i & 3));
        };
        if (l > 0) {
          await_bit(sb + W_X, l, pn, rdy);
#pragma unroll 1
          for (int i = 0; i < 2; i++) {
            e_expect_tx(sb + B_QF + 8 * i, 16384);
            tma_ld(sb + i * QSTG + (po ^ 1) * 16384, &prm.m[M_XSO], (2 * pn + i) * 64, (pm ^ 1) * 128, sb + B_QF + 8 * i);
          }
          mbar_wait(sb + B_QF, 0);
          q_a(2);
          mbar_wait(sb + B_QF + 8, 0);
        }
#pragma unroll 1
        for (int i = l ? 3 : 4; i < 16; i++) {
          q_b(i); q_a(i);
        }
        if (l & 1) {
          if (l == 3) poll_ge(cnt_ad(bn), ep1 * 16);
          const int krow = 2 * bn * 2048 + bm * 256;
          uint32_t* kvc = cnt_kv(l >> 1, bn);
#pragma unroll 1
          for (int m = 1; m >= 0; m--) {
            bar_sync(m ? NB_ST : NB_KV, 288);
#pragma unroll
            for (int i = 0; i < 4; i++) tma_st(&prm.m[M_K4 + (i >> 1)], 0, krow + (i & 1) * 128 + m * 64, sb + T0 + i * 8192 + m * 4096);
            if (m) {
              sts128(sb + ONES + lane * 32, 0x3f803f80u, 0x3f803f80u, 0x3f803f80u, 0x3f803f80u);
              sts128(sb + ONES + lane * 32 + 16, 0x3f803f80u, 0x3f803f80u, 0x3f803f80u, 0x3f803f80u);
              fence_async_smem();
              __syncwarp();
            }
          }
          e_arrive(sb + B_TF);
          bulk_commit(); bulk_wait_n<0>();
          e_red(kvc + bm);
          bar_sync(NB_KV + 12, 288);
          tma_st(&prm.m[M_K], 0, krow + 2048, sb);
          tma_st(&prm.m[M_V], 0, krow + 2048, sb + 16384);
          bulk_commit();
          uint32_t seen = 0;
#pragma unroll 1
          for (int it = 1; it < 16; it++) {
            const int s = it & 3, blk = it;
            if (it == 4) { bulk_wait_n<0>(); e_red(kvc + bm); }
            if (it == 12) { e_expect_tx(sb + B_RF, 32768); tma_ld3(sb + RES, &prm.m[M_XSR], 0, pm * 128, 2 * pn, sb + B_RF); }
            if (it == 2 || it == 3) mbar_wait(sb + B_TF + 8 * (it - 1), 0);
            mbar_wait(sb + B_TE + 8 * s, ((it >> 2) & 1) ^ 1);
            if (it < 8) {
#pragma unroll 1
              for (uint32_t n = 0; n < 200000u && !((seen >> it) & 1); n++)
                seen = __ballot_sync(~0u, (int)(ld_acquire(kvc + ((bm + lane) & 7)) - (ep1 * 2 - 1)) >= 0);
              fence_async_gl();
            } else if (it == 8) { poll_ge(kvc + (lane & 7), ep1 * 2); fence_async_gl(); }
            const int row = (2 * bn + (it >> 3)) * 2048 + ((bm + blk) & 7) * 256;
            e_expect_tx(sb + B_TF + 8 * s, 32768);
            tma_ld(sb + T0 + s * TSTG, &prm.m[M_K], 0, row, sb + B_TF + 8 * s);
            tma_ld(sb + T0 + s * TSTG + 16384, &prm.m[M_V], 0, row, sb + B_TF + 8 * s);
          }
        }
        auto p_b = [&](int i, uint32_t s, uint32_t par) {
          mbar_wait(sb + B_PE + 8 * s, par ^ 1);
          e_expect_tx(sb + B_PF + 8 * s, PSTG);
          tma_ld5(sb + pslot_b(s, l), mo, i >> 3, 2 * (i & 7), 2 * pn, sb + B_PF + 8 * s);
        };
        auto p_a = [&](int i, uint32_t s) {
          await_bit(sb + W_O, l + 1, i, rdy);
          tma_ld_mc(sb + pslot_a(s, l) + rank * 8192, &prm.m[M_OS], i * 64, pm * 128 + rank * 64, sb + B_PF + 8 * s);
        };
        auto p_a2 = [&](int i) {
          await_bit(sb + W_O, l + 1, i, rdy);
          tma_ld(sb + pslot_a(i, l), &prm.m[M_OS], i * 64, pm * 128, sb + B_PF + 8 * i);
          tma_ld(sb + pslot_a(i, l) + 8192, &prm.m[M_OS], i * 64, pm * 128 + 64, sb + B_PF + 8 * i);
        };
        rdy = 0;
        if (l & 1) {
#pragma unroll 1
          for (int u = 0; u < 6; u++) { const int i = (0x205413 >> (4 * u)) & 7; if (u == 4) mbar_wait(sb + B_TE, 1); p_b(i, i, i < 4 ? 1 : 0); }
#pragma unroll 1
          for (int u = 0; u < 6; u++) {
            const int i = (0x542130 >> (4 * u)) & 7;
            if (!(u & 1)) mbar_wait(sb + B_TE + 8 + 4 * u, 1);
            p_a2(i);
          }
        } else {
#pragma unroll 1
          for (int u = 0; u < 6; u++) { const int i = (0x403215 >> (4 * u)) & 7; if (u < 2 || u == 4) mbar_wait(sb + B_QE + (u ? u & 4 ? 24 : 16 : 8), 1); p_b(i, i, 0); }
          e_expect_tx(sb + B_RF, 32768);
          tma_ld3(sb + RES, &prm.m[l == 0 ? M_X0R : M_XSR], 0, pm * 128, 2 * pn, sb + B_RF);
          p_a2(0);
          bar_sync(NB_DONE, 96);
          e_arrive_both(sb + B_PA);
          p_a2(1); p_a2(2);
          mbar_wait(sb + B_PA, (l >> 1) & 1);
#pragma unroll 1
          for (int i = 3; i < 6; i++) { if (i == 4) mbar_wait(sb + B_PF + 8, 0); p_a(i, i); }
        }
        uint32_t s = 0, lap = 1;
#pragma unroll 1
        for (int i = 6; i < 16; i++) {
          p_b(i, s, ((s < 4 ? l : 0) + lap) & 1);
          p_a(i, s);
          if (++s == 6) { s = 0; lap++; }
        }
        const CUtensorMap* mn = &prm.m[M_WQA + ((l + 1) & 1)];
        if (l < 3) {
          mbar_wait(sb + B_PE + 8 * 4, 1); mbar_wait(sb + B_PE + 8 * 5, 1);
          tma_ld3(sb + 32768, mn, bn * 64, 2 * pn * 64, 0, sb + B_QL);
          mbar_wait(sb + B_PE + 8 * 0, l & 1);
          tma_ld3(sb + QSTG + 32768, mn, bn * 64, (2 * pn + 1) * 64, 0, sb + B_QL);
          mbar_wait(sb + B_PE + 8 * 1, l & 1);
          e_expect_tx(sb + B_QF + 16, QSTG);
          tma_ld3(sb + 2 * QSTG + 32768, mn, bn * 64, ((2 * pn) ^ 2) * 64, 0, sb + B_QF + 16);
        }
        if (l < 3) { bar_sync(NB_X, 288); e_expect_tx(sb + B_QL, 49152); }
      }
      if (blockIdx.x == 0 && lane_id() == 0) *(volatile uint32_t*)&g_epoch = ep1;
    } else {
      const int hw = w - 1;
      cluster_wait();
      mbar_wait(sb + B_QF, 0);
#pragma unroll 1
      for (int l = 0; l < 4; l++) {
        IDS();
        if (hw == 2 && l > 0) watch(cnt_x(l, bm) + (lane & 7), ep1 * 2, 0xFFu, l, sb + W_X);
        if (l == 0) {
#pragma unroll 1
          for (int r = 2 * hw; r < 16; r += 6) {
            const uint4* p = (const uint4*)(prm.x0 + (size_t)(b * 16 + r) * 1024) + lane;
            float s1[2] = {0.f, 0.f}, s2[2] = {0.f, 0.f};
#pragma unroll
            for (int i = 0; i < 8; i++) {
              const uint4 v = __ldg(p + 32 * i);
              const uint32_t u[4] = {v.x, v.y, v.z, v.w};
#pragma unroll
              for (int k = 0; k < 4; k++) { const float a = bf_lo(u[k]), c = bf_hi(u[k]); s1[i >> 2] += a + c; s2[i >> 2] = fmaf(a, a, fmaf(c, c, s2[i >> 2])); }
            }
#pragma unroll
            for (int o = 16; o; o >>= 1)
#pragma unroll
              for (int rr = 0; rr < 2; rr++) { s1[rr] += __shfl_xor_sync(~0u, s1[rr], o); s2[rr] += __shfl_xor_sync(~0u, s2[rr], o); }
            if (lane == 0) *(float4*)&g_stats[b * 16 + r] = make_float4(s1[0], s2[0], s1[1], s2[1]);
          }
        }
        if (l == 1) { uint32_t rdy = 0; await_bit<true>(sb + W_X, 1, pn, rdy); mbar_hint(sb + B_QF + 8, 0); }
        if (l < 2) {
          float cs[8];
#pragma unroll
          for (int i = 0; i < 8; i++) cs[i] = 0.f;
          const uint4* wp = (const uint4*)(prm.wq[l] + (size_t)(bm * 128 + (lane >> 3)) * 3072 + hw * 1024 + bn * 64) + (lane & 7);
#pragma unroll 8
          for (int i = 0; i < 32; i++) {
            const uint4 v = __ldg(wp + (size_t)i * 4 * 384);
            cs[0] += bf_lo(v.x); cs[1] += bf_hi(v.x); cs[2] += bf_lo(v.y); cs[3] += bf_hi(v.y);
            cs[4] += bf_lo(v.z); cs[5] += bf_hi(v.z); cs[6] += bf_lo(v.w); cs[7] += bf_hi(v.w);
          }
#pragma unroll
          for (int i = 0; i < 8; i++) { cs[i] += __shfl_xor_sync(~0u, cs[i], 8); cs[i] += __shfl_xor_sync(~0u, cs[i], 16); }
          if (lane < 8) {
            float4* d = (float4*)(g_csp + ((l * 16 + bn) * 8 + bm) * 192 + hw * 64 + lane * 8);
            d[0] = make_float4(cs[0], cs[1], cs[2], cs[3]); d[1] = make_float4(cs[4], cs[5], cs[6], cs[7]);
          }
          __syncwarp();
          asm volatile("fence.acq_rel.gpu;" ::: "memory");
          e_red_relaxed(cnt_cs(l, bn));
          if (l == 0) e_red_relaxed(cnt_x(0, bm) + pn);
          poll_ge(lane < 8 && l == 0 ? cnt_x(0, bm) + lane : cnt_cs(l, bn), ep1 * (lane < 8 && l == 0 ? 6 : 24));
        }
        if (l > 0) {
          uint32_t rdy = 0;
#pragma unroll 1
          for (int j = 0; j < 8; j++) await_bit<true>(sb + W_X, l, j, rdy);
        }
#pragma unroll 1
        for (int it = hw * 32 + lane; it < 176; it += 96) {
          const bool rows = it < 128;
          const float4* p = rows ? (const float4*)(g_stats + bm * 256) + it : (const float4*)(g_csp + ((l & 1) * 16 + bn) * 8 * 192) + (it - 128);
          const int stride = rows ? 1024 : 48, np = rows && l == 0 ? 1 : 8;
          float4 a = make_float4(0.f, 0.f, 0.f, 0.f);
#pragma unroll
          for (int k = 0; k < 8; k++) if (k < np) { const float4 v = __ldcg(p + k * stride); a.x += v.x; a.y += v.y; a.z += v.z; a.w += v.w; }
          if (rows) {
            const float m0 = a.x * (1.f / 1024.f), m1 = a.z * (1.f / 1024.f);
            const float v0 = fmaxf(a.y * (1.f / 1024.f) - m0 * m0, 0.f), v1 = fmaxf(a.w * (1.f / 1024.f) - m1 * m1, 0.f);
            const float r0 = __fdividef(1.f, bf_round(sqrtf(bf_round(bf_round(v0) + 1e-5f)))), r1 = __fdividef(1.f, bf_round(sqrtf(bf_round(bf_round(v1) + 1e-5f))));
            a = make_float4(r0, -bf_round(m0), r1, -bf_round(m1));
          }
          if (rows) *(float4*)(smem + ROWST + it * 16) = a;
          else {
            float2* d = (float2*)(smem + COLS) + ((it - 128) >> 2) * 8 + (it & 1) * 4 + ((it >> 1) & 1);
            d[0] = make_float2(a.y, a.x); d[2] = make_float2(a.w, a.z);
          }
        }
        __syncwarp();
        if (lane == 0) asm volatile("red.release.cta.shared.add.u32 [%0], 0x100;" ::"r"(sb + W_X) : "memory");
        if (hw == 2) {
          if (!(l & 1)) {
            bar_sync(NB_ST, 288);
            const volatile unsigned long long* hp = g_halo + ((size_t)(l >> 1) * 128 + b - 16) * 1024 + lane;
#pragma unroll 1
            for (int h = 0; h < 2; h++) {
              uint32_t t[16];
#pragma unroll
              for (int i = 0; i < 16; i++) t[i] = 0;
#pragma unroll 1
              for (uint32_t n = bm ? 0 : 100000u; n < 100000u; n++) {
                uint32_t miss = 0;
#pragma unroll
                for (int i = 0; i < 16; i++) {
                  const unsigned long long v = hp[h * 512 + i * 32];
                  t[i] = (uint32_t)v; miss |= (uint32_t)(v >> 32) ^ ep1;
                }
                if (__all_sync(~0u, !miss)) break;
              }
              const uint32_t r = (lane & 7) + ((lane >> 3) & 1) * 8, rv = lane >> 2;
#pragma unroll
              for (int jj = 0; jj < 2; jj++) stsm4(sb + 2 * h * ASC + r * 64 + (((2 * jj + (lane >> 4)) ^ ((r >> 1) & 3)) << 4), t[4 * jj], t[4 * jj + 1], t[4 * jj + 2], t[4 * jj + 3]);
              const uint32_t ad = sb + (2 * h + 1) * ASC + rv * 64 + (((lane & 3) ^ ((rv >> 1) & 3)) << 4);
              sts128(ad, t[8], t[10], t[12], t[14]); sts128(ad + 512, t[9], t[11], t[13], t[15]);
              bar_arrive(NB_HALO + h, 64);
            }
          } else {
            mbar_hint(sb + B_TF + 8, 0);
            poll_ge(cnt_kv(l >> 1, bn) + (lane & 7), ep1 * 2);
            const uint4* kp = (const uint4*)(g_kn + ((l >> 1) * 128 + bn * 8) * 32) + 2 * lane;
            const uint4 v = __ldcg(kp), u = __ldcg(kp + 1);
            const uint32_t mx = max(max(max(v.x, v.y), max(v.z, v.w)), max(max(u.x, u.y), max(u.z, u.w)));
            const uint32_t m0 = __reduce_max_sync(~0u, (lane & 2) ? 0u : mx), m1 = __reduce_max_sync(~0u, (lane & 2) ? mx : 0u);
            if (lane == 0) *(uint2*)(smem + ROWST) = make_uint2(m0, m1);
            __syncwarp();
            bar_arrive(NB_KN, 160); bar_arrive(NB_KN + 1, 160);
          }
        } else {
#pragma unroll 1
          for (int h = 0; h < 2; h++) {
            bar_sync(NB_SIG + 2 * h + hw, 160);
            if (h == 1 && !(l & 1)) bar_arrive(NB_DONE, 96);
            e_red(cnt_o(l, 2 * bm + hw, h) + (bn >> 1));
            if (h == 1 && l == 1) e_red(cnt_ad(bn));
          }
        }
        if (hw == 2) watch(cnt_o(l, pm, (lane >> 3) & 1) + (lane & 7), ep1 * 2, 0xFFFFu, l + 1, sb + W_O);
        if (hw == 0 && l < 3) {
          bar_sync(NB_X0, 288);
          e_red(cnt_x(l + 1, bm) + pn);
        }
      }
    }
  } else {
    asm volatile("setmaxnreg.inc.sync.aligned.u32 224;");
    const uint32_t zero = prm.zero;
    cluster_wait();
#pragma unroll 1
    for (int l = 0; l < 4; l++) {
      {
        float acc[2][96];
#pragma unroll
        for (int i = 0; i < 96; i++) { acc[0][i] = 0.f; acc[1][i] = 0.f; }
        fence_regs(acc[0]); fence_regs(acc[1]);
        const bool early = l > 0 && wg == ((cta_id() >> 3) & 1);
        const uint32_t ep1 = *(volatile uint32_t*)&g_epoch + 1;
#pragma unroll 1
        for (int kt = 0; kt < 14; kt++) {
          const int s = kt & 3;
          if (l > 0 && kt == 0) mbar_wait(sb + B_QL, (l + 1) & 1);
          if (!(early && kt < 2)) mbar_wait(sb + B_QF + 8 * s, (kt >> 2) & 1);
          const uint64_t da = mkdesc(sb + s * QSTG + wg * 16384, 16, 1024, 1), db = mkdesc(sb + s * QSTG + 32768, 8192, 1024, 1);
          wg_fence();
#pragma unroll
          for (int k = 0; k < 4; k++)
#pragma unroll
            for (int m = 0; m < 2; m++) wgmma_m64n192k16_ss_tb(acc[m], da + m * 512 + k * 2, db + k * 128, 1);
          wg_commit();
          wg_wait<1>();
          if (early && (kt == 1 || kt == 2)) mbar_wait(sb + B_QF + 8 * (kt - 1), 0);
          if (kt > 0 && w == 0) e_arrive_both(sb + B_QE + 8 * ((kt - 1) & 3));
          if (kt == KC) {
#pragma unroll 1
            for (uint32_t n = 0; n < 4000000u; n++) {
              uint32_t v;
              asm volatile("ld.acquire.cta.shared.u32 %0, [%1];" : "=r"(v) : "r"(sb + W_X) : "memory");
              if ((v >> 8) == (uint32_t)(l * 256 + 3)) break;
            }
            const int lane = lane_id();
            float nm[4];
#pragma unroll
            for (int i = 0; i < 4; i++) nm[i] = lds32f(sb + ROWST + (wg * 128 + w * 16 + (lane >> 2) + (i >> 1) * 64 + (i & 1) * 8) * 8 + 4);
            wg_wait<0>();
            fence_regs(acc[0]); fence_regs(acc[1]);
#pragma unroll
            for (int j = 0; j < 12; j++) {
              const float4 c = lds128f(sb + COLS + j * 64 + (lane & 3) * 16);
#pragma unroll
              for (int m = 0; m < 2; m++) {
                float* a = &acc[m][8 * j];
                a[0] = fmaf(nm[2 * m], c.y, a[0]); a[1] = fmaf(nm[2 * m], c.x, a[1]); a[2] = fmaf(nm[2 * m + 1], c.y, a[2]); a[3] = fmaf(nm[2 * m + 1], c.x, a[3]);
                a[4] = fmaf(nm[2 * m], c.w, a[4]); a[5] = fmaf(nm[2 * m], c.z, a[5]); a[6] = fmaf(nm[2 * m + 1], c.w, a[6]); a[7] = fmaf(nm[2 * m + 1], c.z, a[7]);
              }
            }
            fence_regs(acc[0]); fence_regs(acc[1]);
          }
        }
        auto part = [&](int s, int m, int k0, int k1) {
          const uint64_t da = mkdesc(sb + s * QSTG + wg * 16384 + m * 8192, 16, 1024, 1), db = mkdesc(sb + s * QSTG + 32768, 8192, 1024, 1);
          pin(zero);
          wg_fence();
#pragma unroll
          for (int k = k0; k < k1; k++) wgmma_m64n192k16_ss_tb(acc[m], da + k * 2, db + k * 128, 1);
          wg_commit();
          pin(zero);
        };
        mbar_wait(sb + B_QF + 16, 1);
        part(2, 1, 0, 4);
        wg_wait<1>();
        if (w == 0) e_arrive_both(sb + B_QE + 8);
        if (!(l & 1)) bar_arrive(NB_ST, 288);
        mbar_wait(sb + B_QF + 24, 1);
        part(3, 1, 0, 4);
        part(2, 0, 0, G1);
        IDS();
        const int g = lane >> 2, qd = lane & 3;
        float rs[2][2];
#pragma unroll
        for (int i = 0; i < 4; i++) rs[i >> 1][i & 1] = lds32f(sb + ROWST + (wg * 128 + w * 16 + g + (i >> 1) * 64 + (i & 1) * 8) * 8);
        auto scale = [&](int gi, int m, float sc) {
          const float r0 = rs[m][0] * sc, r1 = rs[m][1] * sc;
#pragma unroll
          for (int i = 0; i < 16; i++) acc[m][16 * gi + i] *= (i & 2) ? r1 : r0;
        };
        auto pack_b = [&](int gi, int m, uint32_t (&t)[8]) {
#pragma unroll
          for (int i = 0; i < 8; i++) t[i] = pack2(acc[m][16 * gi + 2 * i], acc[m][16 * gi + 2 * i + 1]);
        };
        auto norm_tile = [&](int gi, int m, uint32_t (&t)[8]) { scale(gi, m, 1.f); pack_b(gi, m, t); };
        auto pack_h = [&](int gi, int m, uint32_t (&t)[8]) {
#pragma unroll
          for (int i = 0; i < 8; i++) t[i] = pack2h(acc[m][16 * gi + 2 * i], acc[m][16 * gi + 2 * i + 1]);
        };
        uint32_t q[2][2][8], qn[2][2];
        const uint32_t srow = (lane & 7) + ((lane >> 3) & 1) * 8;
        const uint32_t row0 = wg * 128 + w * 16;
        auto put_kv = [&](int h, int v, int m, const uint32_t (&t)[8]) {
          const uint32_t base = sb + ((l & 1) ? (h ? 0 : T0) + v * 16384 : (2 * h + v) * ASC + 1024) + (row0 + m * 64) * 64;
          if (!v) {
#pragma unroll
            for (int jj = 0; jj < 2; jj++) stsm4(base + srow * 64 + (((2 * jj + (lane >> 4)) ^ ((srow >> 1) & 3)) << 4), t[4 * jj], t[4 * jj + 1], t[4 * jj + 2], t[4 * jj + 3]);
          } else {
            const uint32_t ad = base + g * 64 + ((qd ^ (g >> 1)) << 4);
            sts128(ad, t[0], t[2], t[4], t[6]); sts128(ad + 512, t[1], t[3], t[5], t[7]);
          }
        };
        auto send_halo = [&](int h, int v, const uint32_t (&t)[8]) {
          unsigned long long* hp = g_halo + ((size_t)(l >> 1) * 128 + b) * 1024 + h * 512 + v * 256 + lane;
#pragma unroll
          for (int i = 0; i < 8; i++) st_tagged(hp + i * 32, t[i], ep1);
        };
        auto put_kn = [&](int h, int m, uint32_t kn) {
          if (lane == 0) g_kn[((l >> 1) * 128 + bn * 8 + bm) * 32 + 16 * h + 8 * m + wg * 4 + w] = __uint_as_float(kn);
        };
        auto conv_tile1 = [&](int h) {
          uint32_t t[8], tv[8], kn = NOT_F16;
          norm_tile(4 + h, 1, tv);
          put_kv(h, 1, 1, tv);
          scale(2 + h, 1, 1.f);
          if (h == 0) { if (G1 < 4) part(2, 0, G1, 4); if (G2) part(3, 0, 0, G2); } else if (G3 < 4) part(3, 0, G3, 4);
          if (l & 1) {
            float n[2] = {0.f, 0.f};
#pragma unroll
            for (int i = 0; i < 16; i++) n[(i >> 1) & 1] = fmaf(acc[1][32 + 16 * h + i], acc[1][32 + 16 * h + i], n[(i >> 1) & 1]);
            const float a = ((qd & 1) ? n[1] : n[0]) + __shfl_xor_sync(~0u, (qd & 1) ? n[0] : n[1], 1);
            scale(h, 1, QSCALE / 128.f);
            kn = f16_class(__reduce_max_sync(~0u, __float_as_uint(a + __shfl_xor_sync(~0u, a, 2))), K_LO);
            put_kn(h, 1, kn);
          } else scale(h, 1, 1.f);
          if (kn == NOT_F16) pack_b(2 + h, 1, t); else pack_h(2 + h, 1, t);
          put_kv(h, 0, 1, t);
          if (!(l & 1) && row0 == 176 && bm < 7) { send_halo(h, 0, t); send_halo(h, 1, tv); }
        };
        mbar_wait(sb + B_QE + 8, 1);
        wg_wait<1>();
        fence_regs(acc[1]);
        conv_tile1(0);
        if (G2 < G3) part(3, 0, G2, G3);
        if (l & 1) { fence_async_smem(); bar_arrive(NB_ST, 288); }
        conv_tile1(1);
        wg_wait<(G2 > 0) + (G2 < G3) + (G3 < 4)>();
        if (w == 0) e_arrive_both(sb + B_QE + 16);
        wg_wait<0>();
        fence_regs(acc[0]);
        if (w == 0) e_arrive_both(sb + B_QE + 24);
        auto put_o = [&](int h, int m, const float (&o)[16], float i0, float i1) {
          IDS();
          bf16* op = g_os + (size_t)(bm * 256 + row0 + m * 64 + (lane >> 2)) * 1024 + h * 512 + bn * 32 + (lane & 3) * 8;
          *(uint4*)op = make_uint4(pack2(o[0] * i0, o[1] * i0), pack2(o[4] * i0, o[5] * i0), pack2(o[8] * i0, o[9] * i0), pack2(o[12] * i0, o[13] * i0));
          *(uint4*)(op + 8 * 1024) = make_uint4(pack2(o[2] * i1, o[3] * i1), pack2(o[6] * i1, o[7] * i1), pack2(o[10] * i1, o[11] * i1), pack2(o[14] * i1, o[15] * i1));
        };
        if (!(l & 1)) {
#pragma unroll
          for (int u = 0; u < 4; u++) {
            uint32_t t[8];
            norm_tile(4 - 2 * (u & 1) + (u >> 1), 0, t);
            put_kv(u >> 1, ~u & 1, 0, t);
          }
          norm_tile(0, 0, q[0][0]); pack_b(0, 1, q[0][1]);
          bar_sync(NB_SC, 256);
          const bool e = g & 1, sel = 2 * qd + (g & 1) >= g + 2, first = bm == 0 && row0 == 0;
#pragma unroll 1
          for (int h = 0; h < 2; h++) {
            if (row0 == 0) bar_sync(NB_HALO + h, 64);
            float s[2][4][4];
            uint32_t vf[2][4][4], pf[2][2][4];
#pragma unroll
            for (int m = 0; m < 2; m++)
#pragma unroll
              for (int nt = 0; nt < 4; nt++) {
                uint32_t kf[4];
                const uint32_t r = row0 + m * 64 + 8 * nt + (lane & 7);
                ldsm4(sb + 2 * h * ASC + r * 64 + (((lane >> 3) ^ ((r >> 1) & 3)) << 4), kf);
                s[m][nt][0] = s[m][nt][1] = s[m][nt][2] = s[m][nt][3] = 0.f;
                mma16816(s[m][nt], q[0][m][0], q[0][m][1], q[0][m][2], q[0][m][3], kf[0], kf[1]);
                mma16816(s[m][nt], q[0][m][4], q[0][m][5], q[0][m][6], q[0][m][7], kf[2], kf[3]);
              }
#pragma unroll
            for (int m = 0; m < 2; m++)
#pragma unroll
              for (int i = 0; i < 4; i++) {
                const uint32_t r = row0 + m * 64 + 16 * (i >> 1) + srow, ch = 2 * (i & 1) + (lane >> 4);
                ldsm4t(sb + (2 * h + 1) * ASC + r * 64 + ((ch ^ ((r >> 1) & 3)) << 4), vf[m][i]);
              }
            float va[4], vb[4], mx[4];
#pragma unroll
            for (int i = 0; i < 4; i++) {
              const int m = i >> 1, hh = i & 1;
              const float a = e ? s[m][hh + 1][2 * hh + 1] : s[m][hh + 1][2 * hh];
              const float lo = e ? s[m][hh][2 * hh + 1] : s[m][hh][2 * hh], hi = e ? s[m][hh + 2][2 * hh + 1] : s[m][hh + 2][2 * hh];
              const uint32_t t = pack2(a, sel ? lo : hi);
              const uint32_t u = pack2(bf_lo(t) * 0.17677669529663687f, bf_hi(t) * 0.17677669529663687f);
              va[i] = (m == 0 && hh == 0 && first) ? -INFINITY : bf_lo(u);
              vb[i] = (m == 0 && first && sel) ? -INFINITY : bf_hi(u);
              mx[i] = fmaxf(va[i], vb[i]);
            }
#pragma unroll
            for (int i = 0; i < 4; i++) mx[i] = fmaxf(mx[i], __shfl_xor_sync(~0u, mx[i], 1));
#pragma unroll
            for (int i = 0; i < 4; i++) mx[i] = fmaxf(mx[i], __shfl_xor_sync(~0u, mx[i], 2));
#pragma unroll
            for (int i = 0; i < 4; i++) {
              va[i] = ex2((va[i] - mx[i]) * 1.4426950408889634f); vb[i] = ex2((vb[i] - mx[i]) * 1.4426950408889634f);
              mx[i] = va[i] + vb[i];
            }
#pragma unroll
            for (int i = 0; i < 4; i++) mx[i] += __shfl_xor_sync(~0u, mx[i], 1);
#pragma unroll
            for (int i = 0; i < 4; i++) mx[i] += __shfl_xor_sync(~0u, mx[i], 2);
#pragma unroll
            for (int i = 0; i < 4; i++) {
              const int m = i >> 1, hh = i & 1;
              const float inv = rcp(mx[i]);
              const uint32_t t = pack2(va[i] * inv, vb[i] * inv);
              const uint32_t pa = e ? t << 16 : t & 0xFFFFu, pb = e ? t & 0xFFFF0000u : t >> 16;
              pf[m][hh][hh + 1] = pa; pf[m][hh][hh] = sel ? pb : 0u; pf[m][hh][hh + 2] = sel ? 0u : pb; pf[m][hh][3 - 3 * hh] = 0u;
            }
#pragma unroll
            for (int m = 0; m < 2; m++) {
              float o[4][4];
#pragma unroll
              for (int j = 0; j < 4; j++) o[j][0] = o[j][1] = o[j][2] = o[j][3] = 0.f;
#pragma unroll
              for (int i = 0; i < 4; i++) {
                const int kk = i >> 1, jj = 2 * (i & 1);
                mma16816(o[jj], pf[m][0][2 * kk], pf[m][1][2 * kk], pf[m][0][2 * kk + 1], pf[m][1][2 * kk + 1], vf[m][i][0], vf[m][i][1]);
                mma16816(o[jj + 1], pf[m][0][2 * kk], pf[m][1][2 * kk], pf[m][0][2 * kk + 1], pf[m][1][2 * kk + 1], vf[m][i][2], vf[m][i][3]);
              }
              const float of[16] = {o[0][0], o[0][1], o[0][2], o[0][3], o[1][0], o[1][1], o[1][2], o[1][3], o[2][0], o[2][1], o[2][2], o[2][3], o[3][0], o[3][1], o[3][2], o[3][3]};
              put_o(h, m, of, 1.f, 1.f);
            }
            bar_arrive(NB_SIG + 2 * h + wg, 160);
            if (h == 0) {
              norm_tile(1, 0, q[0][0]); pack_b(1, 1, q[0][1]);
            }
          }
        } else {
          auto conv_h = [&](int gi, int m, uint32_t (&t)[8]) {
            pack_h(gi, m, t);
            float d0[4] = {0.f, 0.f, 0.f, 0.f}, d1[4] = {0.f, 0.f, 0.f, 0.f};
            mma16816h(d0, t[0], t[1], t[2], t[3], t[0], t[2]); mma16816h(d1, t[0], t[1], t[2], t[3], t[1], t[3]);
            mma16816h(d0, t[4], t[5], t[6], t[7], t[4], t[6]); mma16816h(d1, t[4], t[5], t[6], t[7], t[5], t[7]);
            return (uint32_t)__reduce_max_sync(~0u, max(max(__float_as_int(d0[0]), __float_as_int(d0[1])), max(__float_as_int(d1[2]), __float_as_int(d1[3]))));
          };
#pragma unroll
          for (int h = 0; h < 2; h++) {
            uint32_t t[8], tv[8];
            scale(2 + h, 0, 1.f);
            const uint32_t kn = f16_class(conv_h(2 + h, 0, t), K_LO);
            if (h) {
#pragma unroll
              for (int i = 0; i < 2; i++) {
                scale(i, 0, QSCALE);
                qn[i][0] = f16_class(conv_h(i, 0, q[i][0]), K_LO);
                qn[i][1] = f16_class(conv_h(i, 1, q[i][1]), K_LO);
              }
            }
            norm_tile(4 + h, 0, tv);
            put_kv(h, 1, 0, tv);
            put_kn(h, 0, kn);
            if (kn == NOT_F16) pack_b(2 + h, 0, t);
            put_kv(h, 0, 0, t);
            fence_async_smem();
            bar_arrive(NB_KV + 12 * h, 288);
            if (h == 0) mbar_wait(sb + B_QF + 24, 1);
          }
          if (max(max(qn[0][0], qn[0][1]), max(qn[1][0], qn[1][1])) == NOT_F16) {
#pragma unroll
            for (int i = 0; i < 4; i++) if (qn[i >> 1][i & 1] == NOT_F16) pack_b(i >> 1, i & 1, q[i >> 1][i & 1]);
          }
          const bool elected = w == 0 && lane == 0;
          const uint64_t kd0 = mkdesc(sb + T0, 16, 512, 2);
          const uint64_t vd0 = mkdesc(sb + T0 + 16384, ONES - (T0 + 16384), 512, 2);
          constexpr uint64_t VSTEP = 64 - (64ull << 16);
#pragma unroll 1
          for (int pass = 0; pass < 2; pass++) {
            constexpr int RPC = NQ / 16, NC = 256 / NQ;
            float o[2][20], SA[2][NQ / 2];
            uint32_t SB[2][NQ / 4], PA[4], PB[4];
#pragma unroll
            for (int m = 0; m < 2; m++) {
#pragma unroll
              for (int i = 0; i < 20; i++) o[m][i] = 0.f;
#pragma unroll
              for (int i = 0; i < NQ / 2; i++) SA[m][i] = 0.f;
#pragma unroll
              for (int i = 0; i < NQ / 4; i++) SB[m][i] = 0u;
              fence_regs(o[m]); fence_regs(SA[m]); fence_regs(SB[m]);
            }
#pragma unroll
            for (int i = 0; i < 4; i++) PA[i] = PB[i] = zero;
            auto qka = [&](int b, int k, uint64_t d) { QK_A(SA[b], q[0][0][4 * k], q[0][0][4 * k + 1], q[0][0][4 * k + 2], q[0][0][4 * k + 3], d + 2 * k, k ? 1 : zero); };
            auto qkb = [&](int b, int k, uint64_t d) { QK_B(SB[b], q[0][1][4 * k], q[0][1][4 * k + 1], q[0][1][4 * k + 2], q[0][1][4 * k + 3], d + 2 * k, k ? 1 : zero); };
            auto pv = [&](int m, const uint32_t (&Px)[4], uint64_t vd) { wgmma_m64n40k16_rs_tb(o[m], Px[0], Px[1], Px[2], Px[3], vd, 1); };
            mbar_wait(sb + B_TF, 0);
            wg_fence(); qka(0, 0, kd0); qkb(0, 0, kd0); qka(0, 1, kd0); qkb(0, 1, kd0); wg_commit();
            wg_wait<0>(); fence_regs(SA[0]); fence_regs(SB[0]);
#pragma unroll 1
            for (int j = 0; j < 8; j++) {
              const uint32_t s = j & 3, sn = j < 7 ? (j + 1) & 3 : s, sp = j > 0 ? (j + 3) & 3 : s;
              const uint64_t kd = kd0 + s * 2048, vd = vd0 + s * (32 * VSTEP), kdn = kd0 + sn * 2048, vdp = vd0 + sp * (32 * VSTEP) + 15 * VSTEP;
              bool landed = false;
#pragma unroll
              for (int r = 0; r < 16; r++) {
                const int c = r / RPC, ro = r % RPC, cn = c + 1;
                if (r == 16 - RPC && !landed) mbar_wait(sb + B_TF + 8 * sn, ((j + 1) >> 2) & 1);
                wg_fence();
                const uint64_t kx = cn < NC ? kd + cn * NQ * 4 : kdn, vx = r > 0 ? vd + (r - 1) * VSTEP : vdp;
                if (LAG & 4) { pv(0, PA, vx); pv(1, PB, vx); }
#pragma unroll
                for (int k = 0; k < 2; k++) {
                  if (ro == ((OA >> (4 * k)) & 15)) qka(cn & 1, k, kx);
                  if (ro == ((OB >> (4 * k)) & 15)) qkb(cn & 1, k, kx);
                }
                if (!(LAG & 4)) {
                  if (ro == RPC - 1 || (LAG & 1)) wg_commit();
                  if (LAG & 8) { pv(1, PB, vx); pv(0, PA, vx); } else { pv(0, PA, vx); pv(1, PB, vx); }
                }
                wg_commit();
                if (r == 14 - RPC) landed = mbar_test(sb + B_TF + 8 * sn, ((j + 1) >> 2) & 1) || j == 7;
#pragma unroll
                for (int i = 0; i < 4; i++) {
                  if (LAG & 16) PB[i] = exp2_h2(SB[c & 1][4 * ro + i]);
                  PA[i] = pack2(ex2(SA[c & 1][8 * ro + 2 * i]), ex2(SA[c & 1][8 * ro + 2 * i + 1]));
                  if (!(LAG & 16)) PB[i] = exp2_h2(SB[c & 1][4 * ro + i]);
                }
                if (r == 15 || ((LAG & 4) && ro == RPC - 1 && ((OA >> 4) == ro || (OB >> 4) == ro))) wg_wait<0>(); else if (ro == RPC - 1 || !(LAG & 2)) wg_wait<1>();
                if (ro == RPC - 1) { fence_regs(SA[cn & 1]); fence_regs(SB[cn & 1]); }
                if (r == RPC && elected && j > 0) mbar_arrive(sb + B_TE + 8 * sp);
              }
            }
            int badm = 0;
            wg_fence(); pv(0, PA, vd0 + 3 * (32 * VSTEP) + 15 * VSTEP); pv(1, PB, vd0 + 3 * (32 * VSTEP) + 15 * VSTEP); wg_commit();
            if (pass == 0) bar_sync(NB_KN + wg, 160);
            const float kmax = *(volatile float*)(smem + ROWST + 4 * pass);
            wg_wait<0>(); fence_regs(o[0]); fence_regs(o[1]);
            if (w == 0) e_arrive(sb + B_TE + 8 * 3);
#pragma unroll
            for (int m = 0; m < 2; m++) {
              float chk[4] = {0.f, 0.f, 0.f, 0.f};
#pragma unroll
              for (int i = 0; i < 20; i++) chk[i & 3] = fmaf(o[m][i], 0.f, chk[i & 3]);
              const bool bad = !(__uint_as_float(qn[0][m]) * kmax <= (m ? 0.875f * 0.875f : 112.f * 112.f)) || !(o[m][16] >= 9.3e-10f) || !(o[m][18] >= 9.3e-10f) || ((chk[0] + chk[1]) + (chk[2] + chk[3]) != 0.f);
              badm |= __any_sync(~0u, bad) << m;
              const float of[16] = {o[m][0], o[m][1], o[m][2], o[m][3], o[m][4], o[m][5], o[m][6], o[m][7], o[m][8], o[m][9], o[m][10], o[m][11], o[m][12], o[m][13], o[m][14], o[m][15]};
              put_o(pass, m, of, rcp(o[m][16]), rcp(o[m][18]));
            }
            if (badm) {
#pragma unroll 1
              for (int m = 0; m < 2; m++) if ((badm >> m) & 1) {
                uint32_t qq[8]; float res[20];
#pragma unroll
                for (int i = 0; i < 8; i++) { qq[i] = m ? q[0][1][i] : q[0][0][i]; if ((m ? qn[0][1] : qn[0][0]) != NOT_F16) qq[i] = h2_to_bf2(qq[i]); }
                attn_slow(qq, m ? 128.f : 1.f, 2 * (cta_id() & 15) + pass, g_kn + ((l >> 1) * 128 + (cta_id() & 15) * 8) * 32 + 16 * pass, res, lane_id());
                const float of[16] = {res[0], res[1], res[2], res[3], res[4], res[5], res[6], res[7], res[8], res[9], res[10], res[11], res[12], res[13], res[14], res[15]};
                put_o(pass, m, of, rcp(res[16]), rcp(res[18]));
              }
            }
            bar_arrive(NB_SIG + 2 * pass + wg, 160);
            qn[0][0] = qn[1][0]; qn[0][1] = qn[1][1];
#pragma unroll
            for (int m = 0; m < 2; m++)
#pragma unroll
              for (int i = 0; i < 8; i++) q[0][m][i] = q[1][m][i];
          }
        }
      }
      {
        float acc[64];
#pragma unroll
        for (int i = 0; i < 64; i++) acc[i] = 0.f;
        fence_regs(acc);
        uint32_t s = 0, lap = 0;
#pragma unroll 1
        for (int kt = 0; kt < 16; kt++) {
          mbar_wait(sb + B_PF + 8 * s, ((s < 4 ? l : 0) + lap) & 1);
          const uint64_t da = mkdesc(sb + pslot_a(s, l) + wg * 8192, 16, 1024, 1), db = mkdesc(sb + pslot_b(s, l), 8192, 1024, 1);
          wg_fence();
#pragma unroll
          for (int k = 0; k < 4; k++) wgmma_m64n128k16_ss_tb(acc, da + k * 2, db + k * 128, 1);
          wg_commit();
          wg_wait<1>();
          if (kt > 0 && w == 0) e_arrive_both(sb + B_PE + 8 * (s ? s - 1 : 5));
          if (++s == 6) { s = 0; lap++; }
        }
        IDS();
        const int g = lane >> 2, qd = lane & 3;
        const int r0 = wg * 64 + w * 16;
        const uint32_t r = r0 + (lane & 7) + ((lane >> 3) & 1) * 8;
        uint32_t x[8][4];
        mbar_wait(sb + B_RF, l & 1);
#pragma unroll
        for (int jj = 0; jj < 8; jj++) ldsm4(sb + RES + (jj >> 2) * 16384 + r * 128 + ((((2 * jj + (lane >> 4)) & 7) ^ (r & 7)) << 4), x[jj]);
        wg_wait<0>();
        fence_regs(acc);
        if (w == 0) e_arrive_both(sb + B_PE + 8 * 3);
        bar_sync(NB_SC, 256);
        const CUtensorMap* mo = &prm.m[l == 3 ? M_OUT : M_XST];
#pragma unroll
        for (int jj = 0; jj < 8; jj++) {
#pragma unroll
          for (int i = 0; i < 4; i++) x[jj][i] = add_bf16x2(x[jj][i], pack2(acc[8 * jj + 2 * i], acc[8 * jj + 2 * i + 1]));
          stsm4(sb + (jj >> 2) * QSTG + po * 16384 + r * 128 + ((((2 * jj + (lane >> 4)) & 7) ^ (r & 7)) << 4), x[jj][0], x[jj][1], x[jj][2], x[jj][3]);
          if ((jj & 3) == 3) { fence_async_smem(); __syncwarp(); tma_st(mo, pn * 128 + (jj >> 2) * 64, pm * 128 + r0, sb + (jj >> 2) * QSTG + po * 16384 + r0 * 128); }
        }
        bulk_commit();
        if (l < 3) {
          bar_arrive(NB_X, 288);
          float s1[2] = {0.f, 0.f}, s2[2] = {0.f, 0.f};
#pragma unroll
          for (int i = 0; i < 32; i++) {
            const float a = bf_lo(x[i >> 2][i & 3]), c = bf_hi(x[i >> 2][i & 3]);
            s1[i & 1] += a + c; s2[i & 1] = fmaf(a, a, fmaf(c, c, s2[i & 1]));
          }
#pragma unroll
          for (int hh = 0; hh < 2; hh++) { s1[hh] += __shfl_xor_sync(~0u, s1[hh], 1); s2[hh] += __shfl_xor_sync(~0u, s2[hh], 1); }
#pragma unroll
          for (int hh = 0; hh < 2; hh++) {
            s1[hh] += __shfl_xor_sync(~0u, s1[hh], 2); s2[hh] += __shfl_xor_sync(~0u, s2[hh], 2);
            if (qd == 0) g_stats[pn * 2048 + pm * 128 + r0 + g + 8 * hh] = make_float2(s1[hh], s2[hh]);
          }
        }
        bulk_wait_n<0>();
        if (l < 3) bar_arrive(NB_X0, 288);
      }
    }
  }
  asm volatile("barrier.cluster.arrive.relaxed.aligned;\nbarrier.cluster.wait.aligned;" ::: "memory");
}

typedef CUresult (*EncodeFn)(CUtensorMap*, CUtensorMapDataType, cuuint32_t, void*, const cuuint64_t*, const cuuint64_t*, const cuuint32_t*,
                             const cuuint32_t*, CUtensorMapInterleave, CUtensorMapSwizzle, CUtensorMapL2promotion, CUtensorMapFloatOOBfill);

static void make_map(EncodeFn fn, CUtensorMap* m, const void* ptr, int rank, const uint64_t* dims, const uint64_t* strides, const uint32_t* box, CUtensorMapSwizzle sw) {
  cuuint64_t d[5], st[4];
  cuuint32_t bx[5], es[5];
  for (int i = 0; i < rank; i++) { d[i] = dims[i]; bx[i] = box[i]; es[i] = 1; if (i) st[i - 1] = strides[i - 1] * 2; }
  fn(m, CU_TENSOR_MAP_DATA_TYPE_BFLOAT16, rank, (void*)ptr, d, st, bx, es, CU_TENSOR_MAP_INTERLEAVE_NONE, sw,
     CU_TENSOR_MAP_L2_PROMOTION_L2_128B, CU_TENSOR_MAP_FLOAT_OOB_FILL_NONE);
}
static void map2(EncodeFn fn, CUtensorMap* m, const void* ptr, uint64_t inner, uint64_t outer, uint32_t bi, uint32_t bo, CUtensorMapSwizzle sw) {
  const uint64_t d[2] = {inner, outer}, st[1] = {inner};
  const uint32_t bx[2] = {bi, bo};
  make_map(fn, m, ptr, 2, d, st, bx, sw);
}

extern "C" void kernel_launch(void* const* d_in, const int* in_sizes, int n_in, void* d_out, int out_size) {
  (void)in_sizes; (void)n_in; (void)out_size;
  static EncodeFn enc = nullptr;
  static void *xs, *os, *kk, *vv;
  if (!enc) {
    void* p = nullptr;
    cudaDriverEntryPointQueryResult qr;
    cudaGetDriverEntryPoint("cuTensorMapEncodeTiled", &p, cudaEnableDefault, &qr);
    enc = (EncodeFn)p;
    cudaGetSymbolAddress(&xs, g_xs); cudaGetSymbolAddress(&os, g_os); cudaGetSymbolAddress(&kk, g_k); cudaGetSymbolAddress(&vv, g_v);
    cudaFuncSetAttribute(fused_kernel, cudaFuncAttributeMaxDynamicSharedMemorySize, SMEM_BYTES);
  }
  Params prm;
  const CUtensorMapSwizzle S128 = CU_TENSOR_MAP_SWIZZLE_128B, S64 = CU_TENSOR_MAP_SWIZZLE_64B;
  map2(enc, &prm.m[M_X0A], d_in[0], 1024, 2048, 64, 256, S128);
  map2(enc, &prm.m[M_XSA], xs, 1024, 2048, 64, 256, S128);
  for (int t = 0; t < 2; t++) {
    const uint64_t d3[3] = {1024, 1024, 3}, s3[2] = {3072, 1024};
    const uint32_t b3[3] = {64, 64, 3};
    make_map(enc, &prm.m[M_WQA + t], d_in[1 + 3 * t], 3, d3, s3, b3, S128);
    const uint64_t d5[5] = {64, 32, 2, 16, 16}, s5[4] = {1024, 32 * 1024, 64 * 1024, 64};
    const uint32_t b5[5] = {64, 32, 1, 2, 2};
    make_map(enc, &prm.m[M_WOA + t], d_in[2 + 3 * t], 5, d5, s5, b5, S128);
    const uint64_t dr[3] = {64, 2048, 16}, sr[2] = {1024, 64};
    const uint32_t br[3] = {64, 128, 2};
    make_map(enc, &prm.m[M_X0R + t], t ? xs : d_in[0], 3, dr, sr, br, S128);
  }
  map2(enc, &prm.m[M_OS], os, 1024, 2048, 64, 64, S128);
  map2(enc, &prm.m[M_K], kk, 32, 65536, 32, 256, S64);
  map2(enc, &prm.m[M_V], vv, 32, 65536, 32, 256, S64);
  map2(enc, &prm.m[M_K4], kk, 32, 65536, 32, 64, S64);
  map2(enc, &prm.m[M_V4], vv, 32, 65536, 32, 64, S64);
  map2(enc, &prm.m[M_XSO], xs, 1024, 2048, 64, 128, S128);
  map2(enc, &prm.m[M_X0H], d_in[0], 1024, 2048, 64, 128, S128);
  map2(enc, &prm.m[M_XST], xs, 1024, 2048, 64, 16, S128);
  map2(enc, &prm.m[M_OUT], d_out, 1024, 2048, 64, 16, S128);
  prm.x0 = (const bf16*)d_in[0];
  prm.wq[0] = (const bf16*)d_in[1]; prm.wq[1] = (const bf16*)d_in[4];
  prm.zero = 0;
  for (int i = 0; i < 128; i++) prm.map[i] = remap(i);
  fused_kernel<<<128, 384, SMEM_BYTES>>>(prm);
}
```

```cpp
#include <cuda_runtime.h>
#include <cuda_bf16.h>
#include <cuda.h>
#include <stdint.h>

typedef __nv_bfloat16 bf16;

__device__ __forceinline__ void wgmma_m64n192k16_ss_tb(float (&d)[96], uint64_t da, uint64_t db, int scale_d) {
  asm volatile("{\n.reg .pred p;\nsetp.ne.b32 p, %98, 0;\n"
    "wgmma.mma_async.sync.aligned.m64n192k16.f32.bf16.bf16 "
    "{%0, %1, %2, %3, %4, %5, %6, %7, %8, %9, %10, %11, %12, %13, %14, %15, "
    "%16, %17, %18, %19, %20, %21, %22, %23, %24, %25, %26, %27, %28, %29, %30, %31, "
    "%32, %33, %34, %35, %36, %37, %38, %39, %40, %41, %42, %43, %44, %45, %46, %47, "
    "%48, %49, %50, %51, %52, %53, %54, %55, %56, %57, %58, %59, %60, %61, %62, %63, "
    "%64, %65, %66, %67, %68, %69, %70, %71, %72, %73, %74, %75, %76, %77, %78, %79, "
    "%80, %81, %82, %83, %84, %85, %86, %87, %88, %89, %90, %91, %92, %93, %94, %95}, "
    "%96, %97, p, 1, 1, 0, 1;\n}\n"
    : "+f"(d[0]), "+f"(d[1]), "+f"(d[2]), "+f"(d[3]), "+f"(d[4]), "+f"(d[5]), "+f"(d[6]), "+f"(d[7]),
      "+f"(d[8]), "+f"(d[9]), "+f"(d[10]), "+f"(d[11]), "+f"(d[12]), "+f"(d[13]), "+f"(d[14]), "+f"(d[15]),
      "+f"(d[16]), "+f"(d[17]), "+f"(d[18]), "+f"(d[19]), "+f"(d[20]), "+f"(d[21]), "+f"(d[22]), "+f"(d[23]),
      "+f"(d[24]), "+f"(d[25]), "+f"(d[26]), "+f"(d[27]), "+f"(d[28]), "+f"(d[29]), "+f"(d[30]), "+f"(d[31]),
      "+f"(d[32]), "+f"(d[33]), "+f"(d[34]), "+f"(d[35]), "+f"(d[36]), "+f"(d[37]), "+f"(d[38]), "+f"(d[39]),
      "+f"(d[40]), "+f"(d[41]), "+f"(d[42]), "+f"(d[43]), "+f"(d[44]), "+f"(d[45]), "+f"(d[46]), "+f"(d[47]),
      "+f"(d[48]), "+f"(d[49]), "+f"(d[50]), "+f"(d[51]), "+f"(d[52]), "+f"(d[53]), "+f"(d[54]), "+f"(d[55]),
      "+f"(d[56]), "+f"(d[57]), "+f"(d[58]), "+f"(d[59]), "+f"(d[60]), "+f"(d[61]), "+f"(d[62]), "+f"(d[63]),
      "+f"(d[64]), "+f"(d[65]), "+f"(d[66]), "+f"(d[67]), "+f"(d[68]), "+f"(d[69]), "+f"(d[70]), "+f"(d[71]),
      "+f"(d[72]), "+f"(d[73]), "+f"(d[74]), "+f"(d[75]), "+f"(d[76]), "+f"(d[77]), "+f"(d[78]), "+f"(d[79]),
      "+f"(d[80]), "+f"(d[81]), "+f"(d[82]), "+f"(d[83]), "+f"(d[84]), "+f"(d[85]), "+f"(d[86]), "+f"(d[87]),
      "+f"(d[88]), "+f"(d[89]), "+f"(d[90]), "+f"(d[91]), "+f"(d[92]), "+f"(d[93]), "+f"(d[94]), "+f"(d[95])
    : "l"(da), "l"(db), "r"(scale_d));
}

__device__ __forceinline__ void wgmma_m64n128k16_ss_tb(float (&d)[64], uint64_t da, uint64_t db, int scale_d) {
  asm volatile("{\n.reg .pred p;\nsetp.ne.b32 p, %66, 0;\n"
    "wgmma.mma_async.sync.aligned.m64n128k16.f32.bf16.bf16 "
    "{%0, %1, %2, %3, %4, %5, %6, %7, %8, %9, %10, %11, %12, %13, %14, %15, "
    "%16, %17, %18, %19, %20, %21, %22, %23, %24, %25, %26, %27, %28, %29, %30, %31, "
    "%32, %33, %34, %35, %36, %37, %38, %39, %40, %41, %42, %43, %44, %45, %46, %47, "
    "%48, %49, %50, %51, %52, %53, %54, %55, %56, %57, %58, %59, %60, %61, %62, %63}, "
    "%64, %65, p, 1, 1, 0, 1;\n}\n"
    : "+f"(d[0]), "+f"(d[1]), "+f"(d[2]), "+f"(d[3]), "+f"(d[4]), "+f"(d[5]), "+f"(d[6]), "+f"(d[7]),
      "+f"(d[8]), "+f"(d[9]), "+f"(d[10]), "+f"(d[11]), "+f"(d[12]), "+f"(d[13]), "+f"(d[14]), "+f"(d[15]),
      "+f"(d[16]), "+f"(d[17]), "+f"(d[18]), "+f"(d[19]), "+f"(d[20]), "+f"(d[21]), "+f"(d[22]), "+f"(d[23]),
      "+f"(d[24]), "+f"(d[25]), "+f"(d[26]), "+f"(d[27]), "+f"(d[28]), "+f"(d[29]), "+f"(d[30]), "+f"(d[31]),
      "+f"(d[32]), "+f"(d[33]), "+f"(d[34]), "+f"(d[35]), "+f"(d[36]), "+f"(d[37]), "+f"(d[38]), "+f"(d[39]),
      "+f"(d[40]), "+f"(d[41]), "+f"(d[42]), "+f"(d[43]), "+f"(d[44]), "+f"(d[45]), "+f"(d[46]), "+f"(d[47]),
      "+f"(d[48]), "+f"(d[49]), "+f"(d[50]), "+f"(d[51]), "+f"(d[52]), "+f"(d[53]), "+f"(d[54]), "+f"(d[55]),
      "+f"(d[56]), "+f"(d[57]), "+f"(d[58]), "+f"(d[59]), "+f"(d[60]), "+f"(d[61]), "+f"(d[62]), "+f"(d[63])
    : "l"(da), "l"(db), "r"(scale_d));
}

__device__ __forceinline__ void wgmma_m64n32k16_rs_nb_h(float (&d)[16], uint32_t a0, uint32_t a1, uint32_t a2, uint32_t a3, uint64_t db, int scale_d) {
  asm volatile("{\n.reg .pred p;\nsetp.ne.b32 p, %21, 0;\n"
    "wgmma.mma_async.sync.aligned.m64n32k16.f32.f16.f16 "
    "{%0, %1, %2, %3, %4, %5, %6, %7, %8, %9, %10, %11, %12, %13, %14, %15}, "
    "{%16, %17, %18, %19}, %20, p, 1, 1, 0;\n}\n"
    : "+f"(d[0]), "+f"(d[1]), "+f"(d[2]), "+f"(d[3]), "+f"(d[4]), "+f"(d[5]), "+f"(d[6]), "+f"(d[7]),
      "+f"(d[8]), "+f"(d[9]), "+f"(d[10]), "+f"(d[11]), "+f"(d[12]), "+f"(d[13]), "+f"(d[14]), "+f"(d[15])
    : "r"(a0), "r"(a1), "r"(a2), "r"(a3), "l"(db), "r"(scale_d));
}

__device__ __forceinline__ void wgmma_m64n32k16_rs_nb_hh(uint32_t (&d)[8], uint32_t a0, uint32_t a1, uint32_t a2, uint32_t a3, uint64_t db, int scale_d) {
  asm volatile("{\n.reg .pred p;\nsetp.ne.b32 p, %13, 0;\n"
    "wgmma.mma_async.sync.aligned.m64n32k16.f16.f16.f16 "
    "{%0, %1, %2, %3, %4, %5, %6, %7}, "
    "{%8, %9, %10, %11}, %12, p, 1, 1, 0;\n}\n"
    : "+r"(d[0]), "+r"(d[1]), "+r"(d[2]), "+r"(d[3]), "+r"(d[4]), "+r"(d[5]), "+r"(d[6]), "+r"(d[7])
    : "r"(a0), "r"(a1), "r"(a2), "r"(a3), "l"(db), "r"(scale_d));
}

__device__ __forceinline__ void wgmma_m64n64k16_rs_nb_h(float (&d)[32], uint32_t a0, uint32_t a1, uint32_t a2, uint32_t a3, uint64_t db, int scale_d) {
  asm volatile("{\n.reg .pred p;\nsetp.ne.b32 p, %37, 0;\n"
    "wgmma.mma_async.sync.aligned.m64n64k16.f32.f16.f16 "
    "{%0, %1, %2, %3, %4, %5, %6, %7, %8, %9, %10, %11, %12, %13, %14, %15, "
    "%16, %17, %18, %19, %20, %21, %22, %23, %24, %25, %26, %27, %28, %29, %30, %31}, "
    "{%32, %33, %34, %35}, %36, p, 1, 1, 0;\n}\n"
    : "+f"(d[0]), "+f"(d[1]), "+f"(d[2]), "+f"(d[3]), "+f"(d[4]), "+f"(d[5]), "+f"(d[6]), "+f"(d[7]),
      "+f"(d[8]), "+f"(d[9]), "+f"(d[10]), "+f"(d[11]), "+f"(d[12]), "+f"(d[13]), "+f"(d[14]), "+f"(d[15]),
      "+f"(d[16]), "+f"(d[17]), "+f"(d[18]), "+f"(d[19]), "+f"(d[20]), "+f"(d[21]), "+f"(d[22]), "+f"(d[23]),
      "+f"(d[24]), "+f"(d[25]), "+f"(d[26]), "+f"(d[27]), "+f"(d[28]), "+f"(d[29]), "+f"(d[30]), "+f"(d[31])
    : "r"(a0), "r"(a1), "r"(a2), "r"(a3), "l"(db), "r"(scale_d));
}

__device__ __forceinline__ void wgmma_m64n64k16_rs_nb_hh(uint32_t (&d)[16], uint32_t a0, uint32_t a1, uint32_t a2, uint32_t a3, uint64_t db, int scale_d) {
  asm volatile("{\n.reg .pred p;\nsetp.ne.b32 p, %21, 0;\n"
    "wgmma.mma_async.sync.aligned.m64n64k16.f16.f16.f16 "
    "{%0, %1, %2, %3, %4, %5, %6, %7, %8, %9, %10, %11, %12, %13, %14, %15}, "
    "{%16, %17, %18, %19}, %20, p, 1, 1, 0;\n}\n"
    : "+r"(d[0]), "+r"(d[1]), "+r"(d[2]), "+r"(d[3]), "+r"(d[4]), "+r"(d[5]), "+r"(d[6]), "+r"(d[7]),
      "+r"(d[8]), "+r"(d[9]), "+r"(d[10]), "+r"(d[11]), "+r"(d[12]), "+r"(d[13]), "+r"(d[14]), "+r"(d[15])
    : "r"(a0), "r"(a1), "r"(a2), "r"(a3), "l"(db), "r"(scale_d));
}

__device__ __forceinline__ void wgmma_m64n40k16_rs_tb(float (&d)[20], uint32_t a0, uint32_t a1, uint32_t a2, uint32_t a3, uint64_t db, int scale_d) {
  asm volatile("{\n.reg .pred p;\nsetp.ne.b32 p, %25, 0;\n"
    "wgmma.mma_async.sync.aligned.m64n40k16.f32.bf16.bf16 "
    "{%0, %1, %2, %3, %4, %5, %6, %7, %8, %9, %10, %11, %12, %13, %14, %15, "
    "%16, %17, %18, %19}, "
    "{%20, %21, %22, %23}, %24, p, 1, 1, 1;\n}\n"
    : "+f"(d[0]), "+f"(d[1]), "+f"(d[2]), "+f"(d[3]), "+f"(d[4]), "+f"(d[5]), "+f"(d[6]), "+f"(d[7]),
      "+f"(d[8]), "+f"(d[9]), "+f"(d[10]), "+f"(d[11]), "+f"(d[12]), "+f"(d[13]), "+f"(d[14]), "+f"(d[15]),
      "+f"(d[16]), "+f"(d[17]), "+f"(d[18]), "+f"(d[19])
    : "r"(a0), "r"(a1), "r"(a2), "r"(a3), "l"(db), "r"(scale_d));
}

#define DEVINL __device__ __forceinline__
DEVINL void pin(uint32_t z) { asm volatile("{\n.reg .pred p;\nsetp.ne.u32 p, %0, 0;\nPIN:\n@p bra.uni PIN;\n}" ::"r"(z) : "memory"); }
DEVINL void wg_fence() { asm volatile("wgmma.fence.sync.aligned;" ::: "memory"); }
DEVINL void wg_commit() { asm volatile("wgmma.commit_group.sync.aligned;" ::: "memory"); }
template <int N> DEVINL void wg_wait() { asm volatile("wgmma.wait_group.sync.aligned %0;" ::"n"(N) : "memory"); }
DEVINL uint64_t mkdesc(uint32_t addr, uint32_t lbo, uint32_t sbo, int sw) {
  return (uint64_t)((addr & 0x3FFFF) >> 4) | ((uint64_t)(lbo >> 4) << 16) | ((uint64_t)(sbo >> 4) << 32) | ((uint64_t)sw << 62);
}
DEVINL void mbar_init(uint32_t bar, uint32_t cnt) { asm volatile("mbarrier.init.shared::cta.b64 [%0], %1;" ::"r"(bar), "r"(cnt) : "memory"); }
DEVINL void mbar_arrive(uint32_t bar) { asm volatile("mbarrier.arrive.shared::cta.b64 _, [%0];" ::"r"(bar) : "memory"); }
DEVINL bool mbar_try(uint32_t bar, uint32_t parity) {
  uint32_t ok;
  asm volatile("{\n.reg .pred p;\nmbarrier.try_wait.parity.shared::cta.b64 p, [%1], %2;\nselp.u32 %0, 1, 0, p;\n}" : "=r"(ok) : "r"(bar), "r"(parity) : "memory");
  return ok;
}
DEVINL bool mbar_test(uint32_t bar, uint32_t parity) {
  uint32_t ok;
  asm volatile("{\n.reg .pred p;\nmbarrier.test_wait.parity.shared::cta.b64 p, [%1], %2;\nselp.u32 %0, 1, 0, p;\n}" : "=r"(ok) : "r"(bar), "r"(parity) : "memory");
  return ok;
}
DEVINL void mbar_hint(uint32_t bar, uint32_t parity) {
#pragma unroll 1
  for (uint32_t n = 0; n < 16u; n++) if (mbar_try(bar, parity)) break;
}
DEVINL void mbar_wait(uint32_t bar, uint32_t parity) {
#pragma unroll 1
  for (uint32_t n = 0; n < 100000u; n++) if (mbar_try(bar, parity)) break;
}
#define EL(txt) "{\n.reg .pred pe;\nelect.sync _|pe, 0xffffffff;\n@pe " txt "\n}"
DEVINL void e_expect_tx(uint32_t bar, uint32_t bytes) { asm volatile(EL("mbarrier.arrive.expect_tx.shared::cta.b64 _, [%0], %1;") ::"r"(bar), "r"(bytes) : "memory"); }
DEVINL void e_arrive(uint32_t bar) { asm volatile(EL("mbarrier.arrive.shared::cta.b64 _, [%0];") ::"r"(bar) : "memory"); }
DEVINL void e_red(uint32_t* p) { asm volatile(EL("red.release.gpu.global.add.u32 [%0], 1;") ::"l"(p) : "memory"); }
DEVINL void e_red_relaxed(uint32_t* p) { asm volatile(EL("red.relaxed.gpu.global.add.u32 [%0], 1;") ::"l"(p) : "memory"); }
DEVINL void tma_ld(uint32_t dst, const CUtensorMap* m, int c0, int c1, uint32_t bar) {
  asm volatile(EL("cp.async.bulk.tensor.2d.shared::cluster.global.mbarrier::complete_tx::bytes [%0], [%1, {%3, %4}], [%2];")
               ::"r"(dst), "l"(m), "r"(bar), "r"(c0), "r"(c1) : "memory");
}
DEVINL void tma_ld3(uint32_t dst, const CUtensorMap* m, int c0, int c1, int c2, uint32_t bar) {
  asm volatile(EL("cp.async.bulk.tensor.3d.shared::cluster.global.mbarrier::complete_tx::bytes [%0], [%1, {%3, %4, %5}], [%2];")
               ::"r"(dst), "l"(m), "r"(bar), "r"(c0), "r"(c1), "r"(c2) : "memory");
}
DEVINL void tma_ld5(uint32_t dst, const CUtensorMap* m, int c2, int c3, int c4, uint32_t bar) {
  asm volatile(EL("cp.async.bulk.tensor.5d.shared::cluster.global.mbarrier::complete_tx::bytes [%0], [%1, {0, 0, %3, %4, %5}], [%2];")
               ::"r"(dst), "l"(m), "r"(bar), "r"(c2), "r"(c3), "r"(c4) : "memory");
}
DEVINL void tma_ld_mc(uint32_t dst, const CUtensorMap* m, int c0, int c1, uint32_t bar) {
  asm volatile(EL("cp.async.bulk.tensor.2d.shared::cluster.global.mbarrier::complete_tx::bytes.multicast::cluster [%0], [%1, {%3, %4}], [%2], %5;")
               ::"r"(dst), "l"(m), "r"(bar), "r"(c0), "r"(c1), "h"((uint16_t)3) : "memory");
}
DEVINL void e_arrive_both(uint32_t bar) {
  asm volatile("{\n.reg .pred pe;\n.reg .b32 r0, r1;\nelect.sync _|pe, 0xffffffff;\nmapa.shared::cluster.u32 r0, %0, 0;\nmapa.shared::cluster.u32 r1, %0, 1;\n"
               "@pe mbarrier.arrive.shared::cluster.b64 _, [r0];\n@pe mbarrier.arrive.shared::cluster.b64 _, [r1];\n}" ::"r"(bar) : "memory");
}
DEVINL void tma_st(const CUtensorMap* m, int c0, int c1, uint32_t src) {
  asm volatile(EL("cp.async.bulk.tensor.2d.global.shared::cta.bulk_group [%0, {%2, %3}], [%1];") ::"l"(m), "r"(src), "r"(c0), "r"(c1) : "memory");
}
DEVINL void bulk_commit() { asm volatile("cp.async.bulk.commit_group;" ::: "memory"); }
template <int N> DEVINL void bulk_wait_n() { asm volatile("cp.async.bulk.wait_group %0;\nbar.warp.sync 0xffffffff;" ::"n"(N) : "memory"); }
DEVINL void l2_prefetch(const void* g, uint32_t bytes) { asm volatile(EL("cp.async.bulk.prefetch.L2.global [%0], %1;") ::"l"(g), "r"(bytes) : "memory"); }
DEVINL void fence_async_smem() { asm volatile("fence.proxy.async.shared::cta;" ::: "memory"); }
DEVINL void fence_async_gl() { asm volatile("fence.proxy.async.global;" ::: "memory"); }
DEVINL void cluster_wait() { asm volatile("barrier.cluster.wait.aligned;" ::: "memory"); }
DEVINL void bar_sync(int id, int n) { asm volatile("bar.sync %0, %1;" ::"r"(id), "r"(n) : "memory"); }
DEVINL void bar_arrive(int id, int n) { asm volatile("bar.arrive %0, %1;" ::"r"(id), "r"(n) : "memory"); }
DEVINL uint32_t ld_acquire(const uint32_t* p) { uint32_t v; asm volatile("ld.acquire.gpu.global.u32 %0, [%1];" : "=r"(v) : "l"(p) : "memory"); return v; }
DEVINL void watch(const uint32_t* p, uint32_t target, uint32_t all, uint32_t tag, uint32_t slot) {
  uint32_t seen = 0;
#pragma unroll 1
  for (uint32_t n = 0; n < 200000u && seen != all; n++) {
    const uint32_t m = __ballot_sync(~0u, (int)(ld_acquire(p) - target) >= 0) & all;
    if (m != seen) { seen = m; asm volatile("st.release.cta.shared.u32 [%0], %1;" ::"r"(slot), "r"(tag << 16 | m) : "memory"); }
  }
}
template <bool RELAXED = false> DEVINL void await_bit(uint32_t slot, uint32_t tag, int j, uint32_t& rdy) {
  if ((rdy >> j) & 1) return;
#pragma unroll 1
  for (uint32_t n = 0; n < 8000000u; n++) {
    uint32_t v;
    asm volatile("ld.acquire.cta.shared.u32 %0, [%1];" : "=r"(v) : "r"(slot) : "memory");
    if ((v >> 16) == tag && ((v >> j) & 1)) { rdy = v; break; }
    if (RELAXED) __nanosleep(200);
  }
  asm volatile("fence.proxy.async.global;" ::: "memory");
}
DEVINL void poll_ge(const uint32_t* p, uint32_t target) {
#pragma unroll 1
  for (uint32_t n = 0; n < 200000u; n++) if (__all_sync(~0u, (int)(ld_acquire(p) - target) >= 0)) break;
}
DEVINL int lane_id() { int v; asm volatile("mov.u32 %0, %%laneid;" : "=r"(v)); return v; }
__host__ DEVINL int remap(int v) {
  const int c = v >> 1, u = c - 36, r = (u * 37) >> 8;
  const int L = c < 4 ? 32 + 8 * c : c < 36 ? c - 4 : 33 + u + r;
  return 2 * L + (v & 1);
}
DEVINL int block_id() { int v; asm volatile("mov.u32 %0, %%ctaid.x;" : "=r"(v)); return v; }
#define cta_id() prm.map[block_id()]
#define IDS() const int lane = lane_id(), b = cta_id(), bm = b >> 4, bn = b & 15, rank = b & 1, pm = 2 * bm + (bn >> 3), pn = bn & 7, po = pm & 1; \
  (void)lane; (void)bm; (void)bn; (void)rank; (void)pm; (void)pn; (void)po
DEVINL void st_tagged(unsigned long long* p, uint32_t v, uint32_t tag) {
  asm volatile("{\n.reg .b64 t;\nmov.b64 t, {%1, %2};\nst.relaxed.gpu.global.b64 [%0], t;\n}" ::"l"(p), "r"(v), "r"(tag) : "memory");
}
DEVINL float ex2(float x) { float y; asm("ex2.approx.ftz.f32 %0, %1;" : "=f"(y) : "f"(x)); return y; }
DEVINL float rcp(float x) { float y; asm("rcp.approx.ftz.f32 %0, %1;" : "=f"(y) : "f"(x)); return y; }
DEVINL uint32_t pack2(float lo, float hi) { uint32_t r; asm("cvt.rn.bf16x2.f32 %0, %1, %2;" : "=r"(r) : "f"(hi), "f"(lo)); return r; }
DEVINL float bf_lo(uint32_t w) { return __uint_as_float(w << 16); }
DEVINL float bf_hi(uint32_t w) { return __uint_as_float(w & 0xFFFF0000u); }
DEVINL float bf_round(float x) { return bf_lo(pack2(x, 0.f)); }
DEVINL uint32_t add_bf16x2(uint32_t a, uint32_t b) { uint32_t r; asm("add.rn.bf16x2 %0, %1, %2;" : "=r"(r) : "r"(a), "r"(b)); return r; }
DEVINL void stsm4(uint32_t addr, uint32_t a, uint32_t b, uint32_t c, uint32_t d) {
  asm volatile("stmatrix.sync.aligned.m8n8.x4.shared.b16 [%0], {%1, %2, %3, %4};" ::"r"(addr), "r"(a), "r"(b), "r"(c), "r"(d) : "memory");
}
DEVINL void ldsm4(uint32_t addr, uint32_t (&r)[4]) {
  asm volatile("ldmatrix.sync.aligned.m8n8.x4.shared.b16 {%0, %1, %2, %3}, [%4];" : "=r"(r[0]), "=r"(r[1]), "=r"(r[2]), "=r"(r[3]) : "r"(addr) : "memory");
}
DEVINL void ldsm4t(uint32_t addr, uint32_t (&r)[4]) {
  asm volatile("ldmatrix.sync.aligned.m8n8.x4.trans.shared.b16 {%0, %1, %2, %3}, [%4];" : "=r"(r[0]), "=r"(r[1]), "=r"(r[2]), "=r"(r[3]) : "r"(addr) : "memory");
}
DEVINL void sts128(uint32_t addr, uint32_t a, uint32_t b, uint32_t c, uint32_t d) {
  asm volatile("st.shared.v4.b32 [%0], {%1, %2, %3, %4};" ::"r"(addr), "r"(a), "r"(b), "r"(c), "r"(d) : "memory");
}
DEVINL float4 lds128f(uint32_t addr) { float4 v; asm volatile("ld.shared.v4.f32 {%0, %1, %2, %3}, [%4];" : "=f"(v.x), "=f"(v.y), "=f"(v.z), "=f"(v.w) : "r"(addr) : "memory"); return v; }
DEVINL float lds32f(uint32_t addr) { float v; asm volatile("ld.shared.f32 %0, [%1];" : "=f"(v) : "r"(addr) : "memory"); return v; }
DEVINL float2 lds64f(uint32_t addr) { float2 v; asm volatile("ld.shared.v2.f32 {%0, %1}, [%2];" : "=f"(v.x), "=f"(v.y) : "r"(addr) : "memory"); return v; }
DEVINL void mma16816(float (&d)[4], uint32_t a0, uint32_t a1, uint32_t a2, uint32_t a3, uint32_t b0, uint32_t b1) {
  asm("mma.sync.aligned.m16n8k16.row.col.f32.bf16.bf16.f32 {%0, %1, %2, %3}, {%4, %5, %6, %7}, {%8, %9}, {%0, %1, %2, %3};"
               : "+f"(d[0]), "+f"(d[1]), "+f"(d[2]), "+f"(d[3]) : "r"(a0), "r"(a1), "r"(a2), "r"(a3), "r"(b0), "r"(b1));
}
DEVINL void mma16816h(float (&d)[4], uint32_t a0, uint32_t a1, uint32_t a2, uint32_t a3, uint32_t b0, uint32_t b1) {
  asm("mma.sync.aligned.m16n8k16.row.col.f32.f16.f16.f32 {%0, %1, %2, %3}, {%4, %5, %6, %7}, {%8, %9}, {%0, %1, %2, %3};"
               : "+f"(d[0]), "+f"(d[1]), "+f"(d[2]), "+f"(d[3]) : "r"(a0), "r"(a1), "r"(a2), "r"(a3), "r"(b0), "r"(b1));
}
template <int N> DEVINL void fence_regs(uint32_t (&d)[N]) {
#pragma unroll
  for (int i = 0; i < N; i++) asm volatile("" : "+r"(d[i])::"memory");
}
template <int N> DEVINL void fence_regs(float (&d)[N]) {
#pragma unroll
  for (int i = 0; i < N; i++) asm volatile("" : "+f"(d[i])::"memory");
}

__device__ __align__(1024) bf16 g_xs[2048 * 1024];
__device__ __align__(1024) bf16 g_os[2048 * 1024];
__device__ __align__(1024) bf16 g_k[32 * 2048 * 32];
__device__ __align__(1024) bf16 g_v[32 * 2048 * 32];
__device__ __align__(128) float2 g_stats[8 * 2048];
__device__ __align__(16) float g_csp[2 * 16 * 8 * 192];
__device__ __align__(128) float g_kn[2 * 128 * 32];
__device__ unsigned long long g_halo[2 * 128 * 32 * 32];
__device__ __align__(128) uint32_t g_cnt[256 * 32];
__device__ uint32_t g_epoch;

DEVINL uint32_t* cnt_x(int l, int bm) { return g_cnt + (l * 8 + bm) * 32; }
DEVINL uint32_t* cnt_o(int l, int pm, int h) { return g_cnt + (32 + (l * 16 + pm) * 2 + h) * 32; }
DEVINL uint32_t* cnt_kv(int lb, int bn) { return g_cnt + (160 + lb * 16 + bn) * 32; }
DEVINL uint32_t* cnt_ad(int bn) { return g_cnt + (192 + bn) * 32; }
DEVINL uint32_t* cnt_cs(int t, int bn) { return g_cnt + (208 + t * 16 + bn) * 32; }

DEVINL int qord(int i, int l, int pn) { return l == 0 ? i : i < 4 ? ((2 * pn) ^ (i & 2)) + (i & 1) : i - 4 < 2 * (pn & 6) ? i - 4 : i; }
struct Params {
  CUtensorMap m[17];
  const bf16* x0;
  const bf16* wq[2];
  uint32_t zero;
  int map[128];
};
enum { M_X0A = 0, M_XSA, M_WQA, M_WQB, M_WOA, M_WOB, M_OS, M_K, M_V, M_X0R, M_XSR, M_XSO, M_OUT, M_XST, M_X0H, M_K4, M_V4, M_COUNT };

constexpr uint32_t QSTG = 57344;
constexpr uint32_t T0 = 65536, TSTG = 32768;
constexpr uint32_t ONES = 230400;
constexpr uint32_t PSTG = 32768, RES = 196608;
constexpr uint32_t ASC = 17408;
constexpr uint32_t ROWST = 229376, COLS = 231424, BARS = 232192, SMEM_BYTES = 232448;
constexpr uint32_t B_QF = BARS, B_QE = BARS + 32, B_TF = BARS + 64, B_TE = BARS + 96, B_PF = BARS + 128, B_PE = BARS + 176,
                   B_RF = BARS + 224, W_X = BARS + 232, W_O = BARS + 236, B_QL = BARS + 240, B_PA = BARS + 248;
enum { NB_ST = 1, NB_KV = 2  , NB_DONE = 3, NB_SC = 4, NB_SIG = 5  , NB_KN = 9  , NB_X = 11, NB_HALO = 12  , NB_X0 = 15 };

DEVINL uint32_t pslot_b(uint32_t s, int l) { return ((((l & 1) ? 0x320415u : 0x468795u) >> (4 * s)) & 15) * 16384u; }
DEVINL uint32_t pslot_a(uint32_t s, int l) { return ((((l & 1) ? 0xBA7896u : 0x32DCBAu) >> (4 * s)) & 15) * 16384u; }

#define G1 2
#define G2 0
#define G3 2
#define KC (11 + 2 * wg)
#define NA2 2
#define RESI 9
#define PERHEAD 1
#define PUBMODE 1
#define NQ 32
#define OA 0x10
#define OB 0x10
#define LAG 2
#define QK_A wgmma_m64n32k16_rs_nb_h
#define QK_B wgmma_m64n32k16_rs_nb_hh
constexpr float QSCALE = 0.17677669529663687f * 1.4426950408889634f;

DEVINL uint32_t hfma2(uint32_t a, uint32_t b, uint32_t c) { uint32_t r; asm("fma.rn.f16x2 %0, %1, %2, %3;" : "=r"(r) : "r"(a), "r"(b), "r"(c)); return r; }
DEVINL uint32_t pack2h(float lo, float hi) { uint32_t r; asm("cvt.rn.f16x2.f32 %0, %1, %2;" : "=r"(r) : "f"(hi), "f"(lo)); return r; }
DEVINL uint32_t h2_to_bf2(uint32_t h) {
  float a, b;
  asm("{\n.reg .b16 l, h;\nmov.b32 {l, h}, %2;\ncvt.f32.f16 %0, l;\ncvt.f32.f16 %1, h;\n}" : "=f"(a), "=f"(b) : "r"(h));
  return pack2(a, b);
}
DEVINL uint32_t exp2_h2(uint32_t s) {
  const uint32_t r = hfma2(s, 0x00800080u, 0x007E007Eu);
  const uint32_t g = hfma2(hfma2(r, 0xF800F800u, 0x33FD33FDu), 0x44004400u, s);
  return r * 128u + hfma2(hfma2(g, g, 0x0DE10DE1u), g, 0x00300030u);
}
constexpr uint32_t NOT_F16 = 0x7FC00000u, K_LO = 0x35000000u  ;
DEVINL uint32_t f16_class(uint32_t norm2, uint32_t lo) { return norm2 - lo > 0x4E800000u - lo ? NOT_F16 : norm2; }

DEVINL void attn_slow(const uint32_t (&q)[8], float up, int head, const float* kn, float (&res)[20], int lane) {
  const int g = lane >> 2, qd = lane & 3;
  const bf16* kb = g_k + (size_t)head * 2048 * 32;
  const bf16* vb = g_v + (size_t)head * 2048 * 32;
  float o[4][4], m0 = -INFINITY, m1 = -INFINITY, l0 = 0.f, l1 = 0.f;
#pragma unroll
  for (int j = 0; j < 4; j++) { o[j][0] = o[j][1] = o[j][2] = o[j][3] = 0.f; }
#pragma unroll 1
  for (int k0 = 0; k0 < 2048; k0 += 16) {
    float s[2][4];
    const bool kh = __float_as_uint(__ldcg(kn + (k0 >> 8) * 32 + ((k0 >> 6) & 1) * 8 + ((k0 >> 7) & 1) * 4 + ((k0 >> 4) & 3))) != NOT_F16;
#pragma unroll
    for (int nt = 0; nt < 2; nt++) {
      s[nt][0] = s[nt][1] = s[nt][2] = s[nt][3] = 0.f;
      const uint32_t* kp = (const uint32_t*)(kb + (size_t)(k0 + nt * 8 + g) * 32) + qd;
      uint32_t kf[4];
#pragma unroll
      for (int i = 0; i < 4; i++) { kf[i] = __ldcg(kp + 4 * i); if (kh) kf[i] = h2_to_bf2(kf[i]); }
      mma16816(s[nt], q[0], q[1], q[2], q[3], kf[0], kf[1]);
      mma16816(s[nt], q[4], q[5], q[6], q[7], kf[2], kf[3]);
      s[nt][0] *= up; s[nt][1] *= up; s[nt][2] *= up; s[nt][3] *= up;
    }
    float a0 = fmaxf(fmaxf(s[0][0], s[0][1]), fmaxf(s[1][0], s[1][1]));
    float a1 = fmaxf(fmaxf(s[0][2], s[0][3]), fmaxf(s[1][2], s[1][3]));
    a0 = fmaxf(a0, __shfl_xor_sync(~0u, a0, 1)); a0 = fmaxf(a0, __shfl_xor_sync(~0u, a0, 2));
    a1 = fmaxf(a1, __shfl_xor_sync(~0u, a1, 1)); a1 = fmaxf(a1, __shfl_xor_sync(~0u, a1, 2));
    const float n0 = fmaxf(m0, a0), n1 = fmaxf(m1, a1);
    const float c0 = (m0 == n0) ? 1.f : ex2(m0 - n0), c1 = (m1 == n1) ? 1.f : ex2(m1 - n1);
    m0 = n0; m1 = n1;
    const uint32_t p0 = pack2(ex2(s[0][0] - n0), ex2(s[0][1] - n0)), p1 = pack2(ex2(s[0][2] - n1), ex2(s[0][3] - n1));
    const uint32_t p2 = pack2(ex2(s[1][0] - n0), ex2(s[1][1] - n0)), p3 = pack2(ex2(s[1][2] - n1), ex2(s[1][3] - n1));
    l0 = l0 * c0 + bf_lo(p0) + bf_hi(p0) + bf_lo(p2) + bf_hi(p2);
    l1 = l1 * c1 + bf_lo(p1) + bf_hi(p1) + bf_lo(p3) + bf_hi(p3);
#pragma unroll
    for (int j = 0; j < 4; j++) {
      o[j][0] *= c0; o[j][1] *= c0; o[j][2] *= c1; o[j][3] *= c1;
      const unsigned short* vp = (const unsigned short*)(vb + (size_t)(k0 + 2 * qd) * 32 + j * 8 + g);
      const uint32_t b0 = (uint32_t)__ldcg(vp) | ((uint32_t)__ldcg(vp + 32) << 16);
      const uint32_t b1 = (uint32_t)__ldcg(vp + 256) | ((uint32_t)__ldcg(vp + 288) << 16);
      mma16816(o[j], p0, p1, p2, p3, b0, b1);
    }
  }
  l0 += __shfl_xor_sync(~0u, l0, 1); l0 += __shfl_xor_sync(~0u, l0, 2);
  l1 += __shfl_xor_sync(~0u, l1, 1); l1 += __shfl_xor_sync(~0u, l1, 2);
#pragma unroll
  for (int j = 0; j < 4; j++) { res[4 * j] = o[j][0]; res[4 * j + 1] = o[j][1]; res[4 * j + 2] = o[j][2]; res[4 * j + 3] = o[j][3]; }
  res[16] = l0; res[18] = l1;
}

__global__ void __cluster_dims__(2, 1, 1) __launch_bounds__(384, 1) fused_kernel(const __grid_constant__ Params prm) {
  extern __shared__ __align__(1024) char smem[];
  const uint32_t sb = (uint32_t)__cvta_generic_to_shared(smem);
  const int tid = threadIdx.x, lane = tid & 31;
  const int wg = __shfl_sync(0xffffffffu, tid >> 7, 0);
  const int w = __shfl_sync(0xffffffffu, (tid >> 5) & 3, 0);
  const int bm = remap(blockIdx.x) >> 4, bn = remap(blockIdx.x) & 15;

  auto first_tile = [&](int kt) {
    e_expect_tx(sb + B_QF + 8 * kt, QSTG);
    tma_ld(sb + kt * QSTG, &prm.m[M_X0A], kt * 64, bm * 256, sb + B_QF + 8 * kt);
    tma_ld3(sb + kt * QSTG + 32768, &prm.m[M_WQA], bn * 64, kt * 64, 0, sb + B_QF + 8 * kt);
  };
  if (wg < 2) {
  } else if (w == 0) {
    if (lane < 4) { mbar_init(sb + B_QF + 8 * lane, 1); asm volatile("fence.mbarrier_init.release.cluster;" ::: "memory"); }
    __syncwarp();
    first_tile(0);
  } else if (w == 1) {
    if (lane == 25) *(uint2*)(smem + W_X) = make_uint2(0u, 0u);
    else if (lane < 28) {
      mbar_init(sb + B_QE + 8 * lane, lane < 4 ? 4 : lane < 8 ? 1 : lane < 12 ? 2 : lane < 18 ? 1 : lane < 24 ? 4 : lane < 27 ? 1 : 2);
      asm volatile("fence.mbarrier_init.release.cluster;" ::: "memory");
    }
  } else if (w == 2 && lane < M_COUNT) {
    asm volatile("prefetch.tensormap [%0];" ::"l"(&prm.m[lane]) : "memory");
  }
  __syncthreads();
  asm volatile("barrier.cluster.arrive.relaxed.aligned;" ::: "memory");

  if (wg == 2) {
    asm volatile("setmaxnreg.dec.sync.aligned.u32 56;");
    const uint32_t ep1 = *(volatile uint32_t*)&g_epoch + 1;
    if (w == 0) {
      first_tile(1);
      mbar_wait(sb + B_QF, 0);
      first_tile(2); first_tile(3);
#pragma unroll 1
      for (int kt = 4; kt < 16; kt++) l2_prefetch(prm.wq[0] + kt * 196608 + blockIdx.x * 1536, 3072);
      cluster_wait();
#pragma unroll 1
      for (int l = 0; l < 4; l++) {
        IDS();
        const CUtensorMap* mw = &prm.m[M_WQA + (l & 1)];
        const CUtensorMap* mx = &prm.m[l == 0 ? M_X0A : M_XSA];
        const CUtensorMap* mh = &prm.m[l == 0 ? M_X0H : M_XSO];
        const CUtensorMap* mo = &prm.m[M_WOA + (l & 1)];
        auto q_b = [&](int i) {
          const int s = i & 3;
          mbar_wait(sb + B_QE + 8 * s, ((i >> 2) & 1) ^ 1);
          e_expect_tx(sb + B_QF + 8 * s, QSTG);
          tma_ld3(sb + s * QSTG + 32768, mw, bn * 64, qord(i, l, pn) * 64, 0, sb + B_QF + 8 * s);
        };
        uint32_t rdy = l ? 0u : ~0u;
        auto q_a = [&](int i) {
          const int kt = qord(i, l, pn);
          await_bit(sb + W_X, l, kt >> 1, rdy);
          if (i < 4) tma_ld(sb + i * QSTG, mx, kt * 64, bm * 256, sb + B_QF + 8 * i);
          else tma_ld_mc(sb + (i & 3) * QSTG + rank * 16384, mh, kt * 64, bm * 256 + rank * 128, sb + B_QF + 8 * (i & 3));
        };
        if (l > 0) {
          await_bit(sb + W_X, l, pn, rdy);
#pragma unroll 1
          for (int i = 0; i < 2; i++) {
            e_expect_tx(sb + B_QF + 8 * i, 16384);
            tma_ld(sb + i * QSTG + (po ^ 1) * 16384, &prm.m[M_XSO], (2 * pn + i) * 64, (pm ^ 1) * 128, sb + B_QF + 8 * i);
          }
          mbar_wait(sb + B_QF, 0);
          q_a(2);
          mbar_wait(sb + B_QF + 8, 0);
        }
#pragma unroll 1
        for (int i = l ? 3 : 4; i < 16; i++) {
          q_b(i); q_a(i);
        }
        if (l & 1) {
          if (l == 3) poll_ge(cnt_ad(bn), ep1 * 16);
          const int krow = 2 * bn * 2048 + bm * 256;
          uint32_t* kvc = cnt_kv(l >> 1, bn);
#pragma unroll 1
          for (int m = 1; m >= 0; m--) {
            bar_sync(m ? NB_ST : NB_KV, 288);
#pragma unroll
            for (int i = 0; i < 4; i++) tma_st(&prm.m[M_K4 + (i >> 1)], 0, krow + (i & 1) * 128 + m * 64, sb + T0 + i * 8192 + m * 4096);
            if (m) {
              sts128(sb + ONES + lane * 32, 0x3f803f80u, 0x3f803f80u, 0x3f803f80u, 0x3f803f80u);
              sts128(sb + ONES + lane * 32 + 16, 0x3f803f80u, 0x3f803f80u, 0x3f803f80u, 0x3f803f80u);
              fence_async_smem();
              __syncwarp();
            }
          }
          e_arrive(sb + B_TF);
          bulk_commit(); bulk_wait_n<0>();
          e_red(kvc + bm);
          bar_sync(NB_KV + 12, 288);
          tma_st(&prm.m[M_K], 0, krow + 2048, sb);
          tma_st(&prm.m[M_V], 0, krow + 2048, sb + 16384);
          bulk_commit();
          uint32_t seen = 0;
#pragma unroll 1
          for (int it = 1; it < 16; it++) {
            const int s = it & 3, blk = it;
            if (it == 4) { bulk_wait_n<0>(); e_red(kvc + bm); }
            if (it == 12) { e_expect_tx(sb + B_RF, 32768); tma_ld3(sb + RES, &prm.m[M_XSR], 0, pm * 128, 2 * pn, sb + B_RF); }
            if (it == 2 || it == 3) mbar_wait(sb + B_TF + 8 * (it - 1), 0);
            mbar_wait(sb + B_TE + 8 * s, ((it >> 2) & 1) ^ 1);
            if (it < 8) {
#pragma unroll 1
              for (uint32_t n = 0; n < 200000u && !((seen >> it) & 1); n++)
                seen = __ballot_sync(~0u, (int)(ld_acquire(kvc + ((bm + lane) & 7)) - (ep1 * 2 - 1)) >= 0);
              fence_async_gl();
            } else if (it == 8) { poll_ge(kvc + (lane & 7), ep1 * 2); fence_async_gl(); }
            const int row = (2 * bn + (it >> 3)) * 2048 + ((bm + blk) & 7) * 256;
            e_expect_tx(sb + B_TF + 8 * s, 32768);
            tma_ld(sb + T0 + s * TSTG, &prm.m[M_K], 0, row, sb + B_TF + 8 * s);
            tma_ld(sb + T0 + s * TSTG + 16384, &prm.m[M_V], 0, row, sb + B_TF + 8 * s);
          }
        }
        auto p_b = [&](int i, uint32_t s, uint32_t par) {
          mbar_wait(sb + B_PE + 8 * s, par ^ 1);
          e_expect_tx(sb + B_PF + 8 * s, PSTG);
          tma_ld5(sb + pslot_b(s, l), mo, i >> 3, 2 * (i & 7), 2 * pn, sb + B_PF + 8 * s);
        };
        auto p_a = [&](int i, uint32_t s) {
          await_bit(sb + W_O, l + 1, i, rdy);
          tma_ld_mc(sb + pslot_a(s, l) + rank * 8192, &prm.m[M_OS], i * 64, pm * 128 + rank * 64, sb + B_PF + 8 * s);
        };
        auto p_a2 = [&](int i) {
          await_bit(sb + W_O, l + 1, i, rdy);
          tma_ld(sb + pslot_a(i, l), &prm.m[M_OS], i * 64, pm * 128, sb + B_PF + 8 * i);
          tma_ld(sb + pslot_a(i, l) + 8192, &prm.m[M_OS], i * 64, pm * 128 + 64, sb + B_PF + 8 * i);
        };
        rdy = 0;
        if (l & 1) {
#pragma unroll 1
          for (int u = 0; u < 6; u++) { const int i = (0x205413 >> (4 * u)) & 7; if (u == 4) mbar_wait(sb + B_TE, 1); p_b(i, i, i < 4 ? 1 : 0); }
#pragma unroll 1
          for (int u = 0; u < 6; u++) {
            const int i = (0x542130 >> (4 * u)) & 7;
            if (!(u & 1)) mbar_wait(sb + B_TE + 8 + 4 * u, 1);
            p_a2(i);
          }
        } else {
#pragma unroll 1
          for (int u = 0; u < 5; u++) { const int i = (0x32140 >> (4 * u)) & 7; if (!(u & 5)) mbar_wait(sb + B_QE + 8 + 4 * u, 1); p_b(i, i, 0); }
          mbar_wait(sb + B_QE + 24, 1);
#pragma unroll 1
          for (int i = 0; i < 4; i++) { if (i < NA2) p_a2(i); else p_a(i, i); }
          bar_sync(NB_DONE, 96);
          e_arrive_both(sb + B_PA);
          p_b(5, 5, 0);
          mbar_wait(sb + B_PA, (l >> 1) & 1);
          p_a(4, 4); p_a(5, 5);
        }
        uint32_t s = 0, lap = 1;
#pragma unroll 1
        for (int i = 6; i < 16; i++) {
          if (i == RESI && !(l & 1)) { e_expect_tx(sb + B_RF, 32768); tma_ld3(sb, &prm.m[l == 0 ? M_X0R : M_XSR], 0, pm * 128, 2 * pn, sb + B_RF); }
          p_b(i, s, ((s < 4 ? l : 0) + lap) & 1);
          p_a(i, s);
          if (++s == 6) { s = 0; lap++; }
        }
        const CUtensorMap* mn = &prm.m[M_WQA + ((l + 1) & 1)];
        if (l < 3) {
          mbar_wait(sb + B_PE + 8 * 4, 1); mbar_wait(sb + B_PE + 8 * 5, 1);
          tma_ld3(sb + 32768, mn, bn * 64, 2 * pn * 64, 0, sb + B_QL);
          mbar_wait(sb + B_PE + 8 * 0, l & 1);
          tma_ld3(sb + QSTG + 32768, mn, bn * 64, (2 * pn + 1) * 64, 0, sb + B_QL);
          mbar_wait(sb + B_PE + 8 * 1, l & 1);
          e_expect_tx(sb + B_QF + 16, QSTG);
          tma_ld3(sb + 2 * QSTG + 32768, mn, bn * 64, ((2 * pn) ^ 2) * 64, 0, sb + B_QF + 16);
        }
        if (l < 3) { bar_sync(NB_X, 288); e_expect_tx(sb + B_QL, 49152); }
      }
      if (blockIdx.x == 0 && lane_id() == 0) *(volatile uint32_t*)&g_epoch = ep1;
    } else {
      const int hw = w - 1;
      cluster_wait();
      mbar_wait(sb + B_QF, 0);
#pragma unroll 1
      for (int l = 0; l < 4; l++) {
        IDS();
        if (hw == 2 && l > 0) watch(cnt_x(l, bm) + (lane & 7), ep1 * 2, 0xFFu, l, sb + W_X);
        if (l == 0) {
#pragma unroll 1
          for (int r = 2 * hw; r < 16; r += 6) {
            const uint4* p = (const uint4*)(prm.x0 + (size_t)(b * 16 + r) * 1024) + lane;
            float s1[2] = {0.f, 0.f}, s2[2] = {0.f, 0.f};
#pragma unroll
            for (int i = 0; i < 8; i++) {
              const uint4 v = __ldg(p + 32 * i);
              const uint32_t u[4] = {v.x, v.y, v.z, v.w};
#pragma unroll
              for (int k = 0; k < 4; k++) { const float a = bf_lo(u[k]), c = bf_hi(u[k]); s1[i >> 2] += a + c; s2[i >> 2] = fmaf(a, a, fmaf(c, c, s2[i >> 2])); }
            }
#pragma unroll
            for (int o = 16; o; o >>= 1)
#pragma unroll
              for (int rr = 0; rr < 2; rr++) { s1[rr] += __shfl_xor_sync(~0u, s1[rr], o); s2[rr] += __shfl_xor_sync(~0u, s2[rr], o); }
            if (lane == 0) *(float4*)&g_stats[b * 16 + r] = make_float4(s1[0], s2[0], s1[1], s2[1]);
          }
        }
        if (l == 1) { uint32_t rdy = 0; await_bit<true>(sb + W_X, 1, pn, rdy); mbar_hint(sb + B_QF + 8, 0); }
        if (l < 2) {
          float cs[8];
#pragma unroll
          for (int i = 0; i < 8; i++) cs[i] = 0.f;
          const uint4* wp = (const uint4*)(prm.wq[l] + (size_t)(bm * 128 + (lane >> 3)) * 3072 + hw * 1024 + bn * 64) + (lane & 7);
#pragma unroll 8
          for (int i = 0; i < 32; i++) {
            const uint4 v = __ldg(wp + (size_t)i * 4 * 384);
            cs[0] += bf_lo(v.x); cs[1] += bf_hi(v.x); cs[2] += bf_lo(v.y); cs[3] += bf_hi(v.y);
            cs[4] += bf_lo(v.z); cs[5] += bf_hi(v.z); cs[6] += bf_lo(v.w); cs[7] += bf_hi(v.w);
          }
#pragma unroll
          for (int i = 0; i < 8; i++) { cs[i] += __shfl_xor_sync(~0u, cs[i], 8); cs[i] += __shfl_xor_sync(~0u, cs[i], 16); }
          if (lane < 8) {
            float4* d = (float4*)(g_csp + ((l * 16 + bn) * 8 + bm) * 192 + hw * 64 + lane * 8);
            d[0] = make_float4(cs[0], cs[1], cs[2], cs[3]); d[1] = make_float4(cs[4], cs[5], cs[6], cs[7]);
          }
          __syncwarp();
          asm volatile("fence.acq_rel.gpu;" ::: "memory");
          e_red_relaxed(cnt_cs(l, bn));
          if (l == 0) e_red_relaxed(cnt_x(0, bm) + pn);
          poll_ge(lane < 8 && l == 0 ? cnt_x(0, bm) + lane : cnt_cs(l, bn), ep1 * (lane < 8 && l == 0 ? 6 : 24));
        }
        if (l > 0) {
          uint32_t rdy = 0;
#pragma unroll 1
          for (int j = 0; j < 8; j++) await_bit<true>(sb + W_X, l, j, rdy);
        }
#pragma unroll 1
        for (int it = hw * 32 + lane; it < 176; it += 96) {
          const bool rows = it < 128;
          const float4* p = rows ? (const float4*)(g_stats + bm * 256) + it : (const float4*)(g_csp + ((l & 1) * 16 + bn) * 8 * 192) + (it - 128);
          const int stride = rows ? 1024 : 48, np = rows && l == 0 ? 1 : 8;
          float4 a = make_float4(0.f, 0.f, 0.f, 0.f);
#pragma unroll
          for (int k = 0; k < 8; k++) if (k < np) { const float4 v = __ldcg(p + k * stride); a.x += v.x; a.y += v.y; a.z += v.z; a.w += v.w; }
          if (rows) {
            const float m0 = a.x * (1.f / 1024.f), m1 = a.z * (1.f / 1024.f);
            const float v0 = fmaxf(a.y * (1.f / 1024.f) - m0 * m0, 0.f), v1 = fmaxf(a.w * (1.f / 1024.f) - m1 * m1, 0.f);
            const float r0 = __fdividef(1.f, bf_round(sqrtf(bf_round(bf_round(v0) + 1e-5f)))), r1 = __fdividef(1.f, bf_round(sqrtf(bf_round(bf_round(v1) + 1e-5f))));
            a = make_float4(r0, -bf_round(m0), r1, -bf_round(m1));
          }
          if (rows) *(float4*)(smem + ROWST + it * 16) = a;
          else {
            float2* d = (float2*)(smem + COLS) + ((it - 128) >> 2) * 8 + (it & 1) * 4 + ((it >> 1) & 1);
            d[0] = make_float2(a.y, a.x); d[2] = make_float2(a.w, a.z);
          }
        }
        __syncwarp();
        if (lane == 0) asm volatile("red.release.cta.shared.add.u32 [%0], 0x100;" ::"r"(sb + W_X) : "memory");
        if (hw == 2) {
          if (!(l & 1)) {
            bar_sync(NB_ST, 288);
            const volatile unsigned long long* hp = g_halo + ((size_t)(l >> 1) * 128 + b - 16) * 1024 + lane;
#pragma unroll 1
            for (int h = 0; h < 2; h++) {
              uint32_t t[16];
#pragma unroll
              for (int i = 0; i < 16; i++) t[i] = 0;
#pragma unroll 1
              for (uint32_t n = bm ? 0 : 100000u; n < 100000u; n++) {
                uint32_t miss = 0;
#pragma unroll
                for (int i = 0; i < 16; i++) {
                  const unsigned long long v = hp[h * 512 + i * 32];
                  t[i] = (uint32_t)v; miss |= (uint32_t)(v >> 32) ^ ep1;
                }
                if (__all_sync(~0u, !miss)) break;
              }
              const uint32_t r = (lane & 7) + ((lane >> 3) & 1) * 8, rv = lane >> 2;
#pragma unroll
              for (int jj = 0; jj < 2; jj++) stsm4(sb + 2 * h * ASC + r * 64 + (((2 * jj + (lane >> 4)) ^ ((r >> 1) & 3)) << 4), t[4 * jj], t[4 * jj + 1], t[4 * jj + 2], t[4 * jj + 3]);
              const uint32_t ad = sb + (2 * h + 1) * ASC + rv * 64 + (((lane & 3) ^ ((rv >> 1) & 3)) << 4);
              sts128(ad, t[8], t[10], t[12], t[14]); sts128(ad + 512, t[9], t[11], t[13], t[15]);
              bar_arrive(NB_HALO + h, 64);
            }
          } else {
            mbar_hint(sb + B_TF + 8, 0);
            poll_ge(cnt_kv(l >> 1, bn) + (lane & 7), ep1 * 2);
            const uint4* kp = (const uint4*)(g_kn + ((l >> 1) * 128 + bn * 8) * 32) + 2 * lane;
            const uint4 v = __ldcg(kp), u = __ldcg(kp + 1);
            const uint32_t mx = max(max(max(v.x, v.y), max(v.z, v.w)), max(max(u.x, u.y), max(u.z, u.w)));
            const uint32_t m0 = __reduce_max_sync(~0u, (lane & 2) ? 0u : mx), m1 = __reduce_max_sync(~0u, (lane & 2) ? mx : 0u);
            if (lane == 0) *(uint2*)(smem + ROWST) = make_uint2(m0, m1);
            __syncwarp();
            bar_arrive(NB_KN, 160); bar_arrive(NB_KN + 1, 160);
          }
        } else {
          bar_sync(NB_SIG + 2 * hw, 160); bar_sync(NB_SIG + 2 * hw + 1, 160);
          if (!(l & 1)) bar_arrive(NB_DONE, 96);
          asm volatile("fence.acq_rel.gpu;" ::: "memory");
          e_red_relaxed(cnt_o(l, 2 * bm, hw) + (bn >> 1));
          e_red_relaxed(cnt_o(l, 2 * bm + 1, hw) + (bn >> 1));
          if (hw == 1 && l == 1) { e_red_relaxed(cnt_ad(bn)); e_red_relaxed(cnt_ad(bn)); }
        }
        if (hw == 2) watch(cnt_o(l, pm, (lane >> 3) & 1) + (lane & 7), ep1 * 2, 0xFFFFu, l + 1, sb + W_O);
        if (hw == 0 && l < 3) {
          bar_sync(NB_X0, 288);
          e_red(cnt_x(l + 1, bm) + pn);
        }
      }
    }
  } else {
    asm volatile("setmaxnreg.inc.sync.aligned.u32 224;");
    const uint32_t zero = prm.zero;
    const uint32_t ep1 = __shfl_sync(~0u, *(volatile uint32_t*)&g_epoch + 1, 0);
    cluster_wait();
#pragma unroll 1
    for (int l = 0; l < 4; l++) {
      {
        float acc[2][96];
#pragma unroll
        for (int i = 0; i < 96; i++) { acc[0][i] = 0.f; acc[1][i] = 0.f; }
        fence_regs(acc[0]); fence_regs(acc[1]);
        const bool early = l > 0 && wg == ((cta_id() >> 3) & 1);
#pragma unroll 1
        for (int kt = 0; kt < 14; kt++) {
          const int s = kt & 3;
          if (l > 0 && kt == 0) mbar_wait(sb + B_QL, (l + 1) & 1);
          if (!(early && kt < 2)) mbar_wait(sb + B_QF + 8 * s, (kt >> 2) & 1);
          const uint64_t da = mkdesc(sb + s * QSTG + wg * 16384, 16, 1024, 1), db = mkdesc(sb + s * QSTG + 32768, 8192, 1024, 1);
          wg_fence();
#pragma unroll
          for (int k = 0; k < 4; k++)
#pragma unroll
            for (int m = 0; m < 2; m++) wgmma_m64n192k16_ss_tb(acc[m], da + m * 512 + k * 2, db + k * 128, 1);
          wg_commit();
          wg_wait<1>();
          if (early && (kt == 1 || kt == 2)) mbar_wait(sb + B_QF + 8 * (kt - 1), 0);
          if (kt > 0 && w == 0) e_arrive_both(sb + B_QE + 8 * ((kt - 1) & 3));
          if (kt == KC) {
#pragma unroll 1
            for (uint32_t n = 0; n < 4000000u; n++) {
              uint32_t v;
              asm volatile("ld.acquire.cta.shared.u32 %0, [%1];" : "=r"(v) : "r"(sb + W_X) : "memory");
              if ((v >> 8) == (uint32_t)(l * 256 + 3)) break;
            }
            const int lane = lane_id();
            float nm[4];
#pragma unroll
            for (int i = 0; i < 4; i++) nm[i] = lds32f(sb + ROWST + (wg * 128 + w * 16 + (lane >> 2) + (i >> 1) * 64 + (i & 1) * 8) * 8 + 4);
            wg_wait<0>();
            fence_regs(acc[0]); fence_regs(acc[1]);
#pragma unroll
            for (int j = 0; j < 12; j++) {
              const float4 c = lds128f(sb + COLS + j * 64 + (lane & 3) * 16);
#pragma unroll
              for (int m = 0; m < 2; m++) {
                float* a = &acc[m][8 * j];
                a[0] = fmaf(nm[2 * m], c.y, a[0]); a[1] = fmaf(nm[2 * m], c.x, a[1]); a[2] = fmaf(nm[2 * m + 1], c.y, a[2]); a[3] = fmaf(nm[2 * m + 1], c.x, a[3]);
                a[4] = fmaf(nm[2 * m], c.w, a[4]); a[5] = fmaf(nm[2 * m], c.z, a[5]); a[6] = fmaf(nm[2 * m + 1], c.w, a[6]); a[7] = fmaf(nm[2 * m + 1], c.z, a[7]);
              }
            }
            fence_regs(acc[0]); fence_regs(acc[1]);
          }
        }
        auto part = [&](int s, int m, int k0, int k1) {
          const uint64_t da = mkdesc(sb + s * QSTG + wg * 16384 + m * 8192, 16, 1024, 1), db = mkdesc(sb + s * QSTG + 32768, 8192, 1024, 1);
          pin(zero);
          wg_fence();
#pragma unroll
          for (int k = k0; k < k1; k++) wgmma_m64n192k16_ss_tb(acc[m], da + k * 2, db + k * 128, 1);
          wg_commit();
          pin(zero);
        };
        mbar_wait(sb + B_QF + 16, 1);
        part(2, 1, 0, 4);
        wg_wait<1>();
        if (w == 0) e_arrive_both(sb + B_QE + 8);
        if (!(l & 1)) bar_arrive(NB_ST, 288);
        mbar_wait(sb + B_QF + 24, 1);
        part(3, 1, 0, 4);
        part(2, 0, 0, G1);
        IDS();
        const int g = lane >> 2, qd = lane & 3;
        float rs[2][2];
#pragma unroll
        for (int i = 0; i < 4; i++) rs[i >> 1][i & 1] = lds32f(sb + ROWST + (wg * 128 + w * 16 + g + (i >> 1) * 64 + (i & 1) * 8) * 8);
        auto scale = [&](int gi, int m, float sc) {
          const float r0 = rs[m][0] * sc, r1 = rs[m][1] * sc;
#pragma unroll
          for (int i = 0; i < 16; i++) acc[m][16 * gi + i] *= (i & 2) ? r1 : r0;
        };
        auto pack_b = [&](int gi, int m, uint32_t (&t)[8]) {
#pragma unroll
          for (int i = 0; i < 8; i++) t[i] = pack2(acc[m][16 * gi + 2 * i], acc[m][16 * gi + 2 * i + 1]);
        };
        auto norm_tile = [&](int gi, int m, uint32_t (&t)[8]) { scale(gi, m, 1.f); pack_b(gi, m, t); };
        auto pack_h = [&](int gi, int m, uint32_t (&t)[8]) {
#pragma unroll
          for (int i = 0; i < 8; i++) t[i] = pack2h(acc[m][16 * gi + 2 * i], acc[m][16 * gi + 2 * i + 1]);
        };
        uint32_t q[2][2][8], qn[2][2];
        const uint32_t srow = (lane & 7) + ((lane >> 3) & 1) * 8;
        const uint32_t row0 = wg * 128 + w * 16;
        auto put_kv = [&](int h, int v, int m, const uint32_t (&t)[8]) {
          const uint32_t base = sb + ((l & 1) ? (h ? 0 : T0) + v * 16384 : (2 * h + v) * ASC + 1024) + (row0 + m * 64) * 64;
          if (!v) {
#pragma unroll
            for (int jj = 0; jj < 2; jj++) stsm4(base + srow * 64 + (((2 * jj + (lane >> 4)) ^ ((srow >> 1) & 3)) << 4), t[4 * jj], t[4 * jj + 1], t[4 * jj + 2], t[4 * jj + 3]);
          } else {
            const uint32_t ad = base + g * 64 + ((qd ^ (g >> 1)) << 4);
            sts128(ad, t[0], t[2], t[4], t[6]); sts128(ad + 512, t[1], t[3], t[5], t[7]);
          }
        };
        auto send_halo = [&](int h, int v, const uint32_t (&t)[8]) {
          unsigned long long* hp = g_halo + ((size_t)(l >> 1) * 128 + b) * 1024 + h * 512 + v * 256 + lane;
#pragma unroll
          for (int i = 0; i < 8; i++) st_tagged(hp + i * 32, t[i], ep1);
        };
        auto put_kn = [&](int h, int m, uint32_t kn) {
          if (lane == 0) g_kn[((l >> 1) * 128 + bn * 8 + bm) * 32 + 16 * h + 8 * m + wg * 4 + w] = __uint_as_float(kn);
        };
        auto conv_tile1 = [&](int h) {
          uint32_t t[8], tv[8], kn = NOT_F16;
          norm_tile(4 + h, 1, tv);
          put_kv(h, 1, 1, tv);
          scale(2 + h, 1, 1.f);
          if (h == 0) { if (G1 < 4) part(2, 0, G1, 4); if (G2) part(3, 0, 0, G2); } else if (G3 < 4) part(3, 0, G3, 4);
          if (l & 1) {
            float n[2] = {0.f, 0.f};
#pragma unroll
            for (int i = 0; i < 16; i++) n[(i >> 1) & 1] = fmaf(acc[1][32 + 16 * h + i], acc[1][32 + 16 * h + i], n[(i >> 1) & 1]);
            const float a = ((qd & 1) ? n[1] : n[0]) + __shfl_xor_sync(~0u, (qd & 1) ? n[0] : n[1], 1);
            scale(h, 1, QSCALE / 128.f);
            kn = f16_class(__reduce_max_sync(~0u, __float_as_uint(a + __shfl_xor_sync(~0u, a, 2))), K_LO);
            put_kn(h, 1, kn);
          } else scale(h, 1, 1.f);
          if (kn == NOT_F16) pack_b(2 + h, 1, t); else pack_h(2 + h, 1, t);
          put_kv(h, 0, 1, t);
          if (!(l & 1) && row0 == 176 && bm < 7) { send_halo(h, 0, t); send_halo(h, 1, tv); }
        };
        mbar_wait(sb + B_QE + 8, 1);
        wg_wait<1>();
        fence_regs(acc[1]);
        conv_tile1(0);
        if (G2 < G3) part(3, 0, G2, G3);
        if (l & 1) { fence_async_smem(); bar_arrive(NB_ST, 288); }
        conv_tile1(1);
        wg_wait<(G2 > 0) + (G2 < G3) + (G3 < 4)>();
        if (w == 0) e_arrive_both(sb + B_QE + 16);
        wg_wait<0>();
        fence_regs(acc[0]);
        if (w == 0) e_arrive_both(sb + B_QE + 24);
        bf16* const op0 = [&] { IDS(); return g_os + (size_t)(bm * 256 + row0 + (lane >> 2)) * 1024 + bn * 32 + (lane & 3) * 8; }();
        auto put_o = [&](int h, int m, const float (&o)[16], float i0, float i1) {
          bf16* op = op0 + m * 65536 + h * 512;
          const uint4 a = make_uint4(pack2(o[0] * i0, o[1] * i0), pack2(o[4] * i0, o[5] * i0), pack2(o[8] * i0, o[9] * i0), pack2(o[12] * i0, o[13] * i0));
          const uint4 c = make_uint4(pack2(o[2] * i1, o[3] * i1), pack2(o[6] * i1, o[7] * i1), pack2(o[10] * i1, o[11] * i1), pack2(o[14] * i1, o[15] * i1));
          *(uint4*)op = a; *(uint4*)(op + 8 * 1024) = c;
          const uint32_t hi = __vimax3_u16x2(__vimax3_u16x2(a.x, a.y, a.z), __vimax3_u16x2(a.w, c.x, c.y), __vmaxu2(c.z, c.w));
          const uint32_t lo = __vimax3_s16x2(__vimax3_s16x2(a.x, a.y, a.z), __vimax3_s16x2(a.w, c.x, c.y), __vmaxs2(c.z, c.w));
          return __vmaxu2(hi & 0x7FFF7FFFu, lo & 0x7FFF7FFFu);
        };
        if (!(l & 1)) {
          auto conv_kv = [&](int h) {
            uint32_t t[8];
            norm_tile(2 + h, 0, t); put_kv(h, 0, 0, t);
            norm_tile(4 + h, 0, t); put_kv(h, 1, 0, t);
          };
          conv_kv(0);
          if (!PERHEAD) conv_kv(1);
          norm_tile(0, 0, q[0][0]); pack_b(0, 1, q[0][1]);
          bar_sync(NB_SC, 256);
          const bool e = g & 1, sel = 2 * qd + (g & 1) >= g + 2, first = bm == 0 && row0 == 0;
#pragma unroll 1
          for (int h = 0; h < 2; h++) {
            if (row0 == 0) bar_sync(NB_HALO + h, 64);
            float s[2][4][4];
            uint32_t vf[2][4][4], pf[2][2][4];
#pragma unroll
            for (int m = 0; m < 2; m++)
#pragma unroll
              for (int nt = 0; nt < 4; nt++) {
                uint32_t kf[4];
                const uint32_t r = row0 + m * 64 + 8 * nt + (lane & 7);
                ldsm4(sb + 2 * h * ASC + r * 64 + (((lane >> 3) ^ ((r >> 1) & 3)) << 4), kf);
                s[m][nt][0] = s[m][nt][1] = s[m][nt][2] = s[m][nt][3] = 0.f;
                mma16816(s[m][nt], q[0][m][0], q[0][m][1], q[0][m][2], q[0][m][3], kf[0], kf[1]);
                mma16816(s[m][nt], q[0][m][4], q[0][m][5], q[0][m][6], q[0][m][7], kf[2], kf[3]);
              }
#pragma unroll
            for (int m = 0; m < 2; m++)
#pragma unroll
              for (int i = 0; i < 4; i++) {
                const uint32_t r = row0 + m * 64 + 16 * (i >> 1) + srow, ch = 2 * (i & 1) + (lane >> 4);
                ldsm4t(sb + (2 * h + 1) * ASC + r * 64 + ((ch ^ ((r >> 1) & 3)) << 4), vf[m][i]);
              }
            float va[4], vb[4], mx[4];
#pragma unroll
            for (int i = 0; i < 4; i++) {
              const int m = i >> 1, hh = i & 1;
              const float a = e ? s[m][hh + 1][2 * hh + 1] : s[m][hh + 1][2 * hh];
              const float lo = e ? s[m][hh][2 * hh + 1] : s[m][hh][2 * hh], hi = e ? s[m][hh + 2][2 * hh + 1] : s[m][hh + 2][2 * hh];
              const uint32_t t = pack2(a, sel ? lo : hi);
              const uint32_t u = pack2(bf_lo(t) * 0.17677669529663687f, bf_hi(t) * 0.17677669529663687f);
              va[i] = (m == 0 && hh == 0 && first) ? -INFINITY : bf_lo(u);
              vb[i] = (m == 0 && first && sel) ? -INFINITY : bf_hi(u);
              mx[i] = fmaxf(va[i], vb[i]);
            }
#pragma unroll
            for (int i = 0; i < 4; i++) mx[i] = fmaxf(mx[i], __shfl_xor_sync(~0u, mx[i], 1));
#pragma unroll
            for (int i = 0; i < 4; i++) mx[i] = fmaxf(mx[i], __shfl_xor_sync(~0u, mx[i], 2));
#pragma unroll
            for (int i = 0; i < 4; i++) {
              va[i] = ex2((va[i] - mx[i]) * 1.4426950408889634f); vb[i] = ex2((vb[i] - mx[i]) * 1.4426950408889634f);
              mx[i] = va[i] + vb[i];
            }
#pragma unroll
            for (int i = 0; i < 4; i++) mx[i] += __shfl_xor_sync(~0u, mx[i], 1);
#pragma unroll
            for (int i = 0; i < 4; i++) mx[i] += __shfl_xor_sync(~0u, mx[i], 2);
#pragma unroll
            for (int i = 0; i < 4; i++) {
              const int m = i >> 1, hh = i & 1;
              const float inv = rcp(mx[i]);
              const uint32_t t = pack2(va[i] * inv, vb[i] * inv);
              const uint32_t pa = e ? t << 16 : t & 0xFFFFu, pb = e ? t & 0xFFFF0000u : t >> 16;
              pf[m][hh][hh + 1] = pa; pf[m][hh][hh] = sel ? pb : 0u; pf[m][hh][hh + 2] = sel ? 0u : pb; pf[m][hh][3 - 3 * hh] = 0u;
            }
#pragma unroll
            for (int m = 0; m < 2; m++) {
              float o[4][4];
#pragma unroll
              for (int j = 0; j < 4; j++) o[j][0] = o[j][1] = o[j][2] = o[j][3] = 0.f;
#pragma unroll
              for (int i = 0; i < 4; i++) {
                const int kk = i >> 1, jj = 2 * (i & 1);
                mma16816(o[jj], pf[m][0][2 * kk], pf[m][1][2 * kk], pf[m][0][2 * kk + 1], pf[m][1][2 * kk + 1], vf[m][i][0], vf[m][i][1]);
                mma16816(o[jj + 1], pf[m][0][2 * kk], pf[m][1][2 * kk], pf[m][0][2 * kk + 1], pf[m][1][2 * kk + 1], vf[m][i][2], vf[m][i][3]);
              }
              const float of[16] = {o[0][0], o[0][1], o[0][2], o[0][3], o[1][0], o[1][1], o[1][2], o[1][3], o[2][0], o[2][1], o[2][2], o[2][3], o[3][0], o[3][1], o[3][2], o[3][3]};
              put_o(h, m, of, 1.f, 1.f);
            }
            bar_arrive(NB_SIG + 2 * h + wg, 160);
            if (h == 0) {
              if (PERHEAD) conv_kv(1);
              norm_tile(1, 0, q[0][0]); pack_b(1, 1, q[0][1]);
              if (PERHEAD) bar_sync(NB_SC, 256);
            }
          }
        } else {
          auto conv_h = [&](int gi, int m, uint32_t (&t)[8]) {
            pack_h(gi, m, t);
            float d0[4] = {0.f, 0.f, 0.f, 0.f}, d1[4] = {0.f, 0.f, 0.f, 0.f};
            mma16816h(d0, t[0], t[1], t[2], t[3], t[0], t[2]); mma16816h(d1, t[0], t[1], t[2], t[3], t[1], t[3]);
            mma16816h(d0, t[4], t[5], t[6], t[7], t[4], t[6]); mma16816h(d1, t[4], t[5], t[6], t[7], t[5], t[7]);
            return (uint32_t)__reduce_max_sync(~0u, max(max(__float_as_int(d0[0]), __float_as_int(d0[1])), max(__float_as_int(d1[2]), __float_as_int(d1[3]))));
          };
#pragma unroll
          for (int h = 0; h < 2; h++) {
            uint32_t t[8], tv[8];
            scale(2 + h, 0, 1.f);
            const uint32_t kn = f16_class(conv_h(2 + h, 0, t), K_LO);
            if (h) {
#pragma unroll
              for (int i = 0; i < 2; i++) {
                scale(i, 0, QSCALE);
                qn[i][0] = f16_class(conv_h(i, 0, q[i][0]), K_LO);
                qn[i][1] = f16_class(conv_h(i, 1, q[i][1]), K_LO);
              }
            }
            norm_tile(4 + h, 0, tv);
            put_kv(h, 1, 0, tv);
            put_kn(h, 0, kn);
            if (kn == NOT_F16) pack_b(2 + h, 0, t);
            put_kv(h, 0, 0, t);
            fence_async_smem();
            bar_arrive(NB_KV + 12 * h, 288);
            if (h == 0) mbar_wait(sb + B_QF + 24, 1);
          }
          if (max(max(qn[0][0], qn[0][1]), max(qn[1][0], qn[1][1])) == NOT_F16) {
#pragma unroll
            for (int i = 0; i < 4; i++) if (qn[i >> 1][i & 1] == NOT_F16) pack_b(i >> 1, i & 1, q[i >> 1][i & 1]);
          }
          const bool elected = w == 0 && lane == 0;
          const uint64_t kd0 = mkdesc(sb + T0, 16, 512, 2);
          const uint64_t vd0 = mkdesc(sb + T0 + 16384, ONES - (T0 + 16384), 512, 2);
          constexpr uint64_t VSTEP = 64 - (64ull << 16);
          constexpr int RPC = NQ / 16, NC = 256 / NQ;
          float o[2][20], SA[2][NQ / 2];
          uint32_t SB[2][NQ / 4], PA[4], PB[4];
#pragma unroll
          for (int m = 0; m < 2; m++) {
#pragma unroll
            for (int i = 0; i < NQ / 2; i++) SA[m][i] = 0.f;
#pragma unroll
            for (int i = 0; i < NQ / 4; i++) SB[m][i] = 0u;
            fence_regs(SA[m]); fence_regs(SB[m]);
          }
          auto qka = [&](int b, int k, uint64_t d, int h = 0) { QK_A(SA[b], q[h][0][4 * k], q[h][0][4 * k + 1], q[h][0][4 * k + 2], q[h][0][4 * k + 3], d + 2 * k, k ? 1 : zero); };
          auto qkb = [&](int b, int k, uint64_t d, int h = 0) { QK_B(SB[b], q[h][1][4 * k], q[h][1][4 * k + 1], q[h][1][4 * k + 2], q[h][1][4 * k + 3], d + 2 * k, k ? 1 : zero); };
          auto pv = [&](int m, const uint32_t (&Px)[4], uint64_t vd) { wgmma_m64n40k16_rs_tb(o[m], Px[0], Px[1], Px[2], Px[3], vd, 1); };
          auto clear = [&]() {
#pragma unroll
            for (int i = 0; i < 20; i++) o[0][i] = o[1][i] = 0.f;
            fence_regs(o[0]); fence_regs(o[1]);
#pragma unroll
            for (int i = 0; i < 4; i++) PA[i] = PB[i] = zero;
          };
          mbar_wait(sb + B_TF, 0);
          wg_fence(); qka(0, 0, kd0); qkb(0, 0, kd0); qka(0, 1, kd0); qkb(0, 1, kd0); wg_commit();
          clear();
          wg_wait<0>(); fence_regs(SA[0]); fence_regs(SB[0]);
#pragma unroll 1
          for (int pass = 0; pass < 2; pass++) {
#pragma unroll 1
            for (int j = 0; j < 8; j++) {
              const uint32_t s = j & 3, sn = j < 7 ? (j + 1) & 3 : s, sp = j > 0 ? (j + 3) & 3 : s;
              const uint64_t kd = kd0 + s * 2048, vd = vd0 + s * (32 * VSTEP), kdn = kd0 + sn * 2048, vdp = vd0 + sp * (32 * VSTEP) + 15 * VSTEP;
              bool landed = false;
#pragma unroll
              for (int r = 0; r < 16; r++) {
                const int c = r / RPC, ro = r % RPC, cn = c + 1;
                if (r == 16 - RPC && !landed) mbar_wait(sb + B_TF + 8 * sn, ((j + 1) >> 2) & 1);
                wg_fence();
                const uint64_t kx = cn < NC ? kd + cn * NQ * 4 : kdn, vx = r > 0 ? vd + (r - 1) * VSTEP : vdp;
                if (LAG & 4) { pv(0, PA, vx); pv(1, PB, vx); }
#pragma unroll
                for (int k = 0; k < 2; k++) {
                  if (ro == ((OA >> (4 * k)) & 15)) qka(cn & 1, k, kx);
                  if (ro == ((OB >> (4 * k)) & 15)) qkb(cn & 1, k, kx);
                }
                if (!(LAG & 4)) {
                  if (ro == RPC - 1 || (LAG & 1)) wg_commit();
                  if (LAG & 8) { pv(1, PB, vx); pv(0, PA, vx); } else { pv(0, PA, vx); pv(1, PB, vx); }
                }
                wg_commit();
                if (r == 14 - RPC) landed = mbar_test(sb + B_TF + 8 * sn, ((j + 1) >> 2) & 1) || j == 7;
#pragma unroll
                for (int i = 0; i < 4; i++) {
                  if (LAG & 16) PB[i] = exp2_h2(SB[c & 1][4 * ro + i]);
                  PA[i] = pack2(ex2(SA[c & 1][8 * ro + 2 * i]), ex2(SA[c & 1][8 * ro + 2 * i + 1]));
                  if (!(LAG & 16)) PB[i] = exp2_h2(SB[c & 1][4 * ro + i]);
                }
                if (r == 15 || ((LAG & 4) && ro == RPC - 1 && ((OA >> 4) == ro || (OB >> 4) == ro))) wg_wait<0>(); else if (ro == RPC - 1 || !(LAG & 2)) wg_wait<1>();
                if (ro == RPC - 1) { fence_regs(SA[cn & 1]); fence_regs(SB[cn & 1]); }
                if (r == RPC && elected && j > 0) mbar_arrive(sb + B_TE + 8 * sp);
              }
            }
            int badm = 0;
            if (pass == 0) mbar_wait(sb + B_TF, 0);
            wg_fence(); pv(0, PA, vd0 + 3 * (32 * VSTEP) + 15 * VSTEP); pv(1, PB, vd0 + 3 * (32 * VSTEP) + 15 * VSTEP); wg_commit();
            qka(0, 0, kd0, 1); qkb(0, 0, kd0, 1); qka(0, 1, kd0, 1); qkb(0, 1, kd0, 1); wg_commit();
            if (pass == 0) bar_sync(NB_KN + wg, 160);
            const float kmax = *(volatile float*)(smem + ROWST + 4 * pass);
            wg_wait<1>(); fence_regs(o[0]); fence_regs(o[1]);
            if (w == 0) e_arrive(sb + B_TE + 8 * 3);
#pragma unroll
            for (int m = 0; m < 2; m++) {
              const float of[16] = {o[m][0], o[m][1], o[m][2], o[m][3], o[m][4], o[m][5], o[m][6], o[m][7], o[m][8], o[m][9], o[m][10], o[m][11], o[m][12], o[m][13], o[m][14], o[m][15]};
              const uint32_t chk = put_o(pass, m, of, rcp(o[m][16]), rcp(o[m][18]));
              const bool bad = !(__uint_as_float(qn[0][m]) * kmax <= (m ? 0.875f * 0.875f : 112.f * 112.f)) || !(fminf(o[m][16], o[m][18]) >= 9.3e-10f) ||
                               !(o[m][16] + o[m][18] <= 3e38f) || ((chk + 0x00800080u) & 0x80008000u);
              badm |= __any_sync(~0u, bad) << m;
            }
            wg_wait<0>(); fence_regs(SA[0]); fence_regs(SB[0]);
            if (badm) {
#pragma unroll 1
              for (int m = 0; m < 2; m++) if ((badm >> m) & 1) {
                uint32_t qq[8]; float res[20];
#pragma unroll
                for (int i = 0; i < 8; i++) { qq[i] = m ? q[0][1][i] : q[0][0][i]; if ((m ? qn[0][1] : qn[0][0]) != NOT_F16) qq[i] = h2_to_bf2(qq[i]); }
                attn_slow(qq, m ? 128.f : 1.f, 2 * (cta_id() & 15) + pass, g_kn + ((l >> 1) * 128 + (cta_id() & 15) * 8) * 32 + 16 * pass, res, lane_id());
                const float of[16] = {res[0], res[1], res[2], res[3], res[4], res[5], res[6], res[7], res[8], res[9], res[10], res[11], res[12], res[13], res[14], res[15]};
                put_o(pass, m, of, rcp(res[16]), rcp(res[18]));
              }
            }
            bar_arrive(NB_SIG + 2 * pass + wg, 160);
            qn[0][0] = qn[1][0]; qn[0][1] = qn[1][1];
#pragma unroll
            for (int m = 0; m < 2; m++)
#pragma unroll
              for (int i = 0; i < 8; i++) q[0][m][i] = q[1][m][i];
            clear();
          }
        }
      }
      {
        float acc[64];
#pragma unroll
        for (int i = 0; i < 64; i++) acc[i] = 0.f;
        fence_regs(acc);
        uint32_t s = 0, lap = 0;
#pragma unroll 1
        for (int kt = 0; kt < 16; kt++) {
          mbar_wait(sb + B_PF + 8 * s, ((s < 4 ? l : 0) + lap) & 1);
          const uint64_t da = mkdesc(sb + pslot_a(s, l) + wg * 8192, 16, 1024, 1), db = mkdesc(sb + pslot_b(s, l), 8192, 1024, 1);
          wg_fence();
#pragma unroll
          for (int k = 0; k < 4; k++) wgmma_m64n128k16_ss_tb(acc, da + k * 2, db + k * 128, 1);
          wg_commit();
          wg_wait<1>();
          if (kt > 0 && w == 0) e_arrive_both(sb + B_PE + 8 * (s ? s - 1 : 5));
          if (++s == 6) { s = 0; lap++; }
        }
        IDS();
        const int g = lane >> 2, qd = lane & 3;
        const int r0 = wg * 64 + w * 16;
        const uint32_t r = r0 + (lane & 7) + ((lane >> 3) & 1) * 8;
        uint32_t x[8][4];
        mbar_wait(sb + B_RF, l & 1);
#pragma unroll
        for (int jj = 0; jj < 8; jj++) ldsm4(sb + ((l & 1) ? RES : 0) + (jj >> 2) * 16384 + r * 128 + ((((2 * jj + (lane >> 4)) & 7) ^ (r & 7)) << 4), x[jj]);
        wg_wait<0>();
        fence_regs(acc);
        if (w == 0) e_arrive_both(sb + B_PE + 8 * 3);
        bar_sync(NB_SC, 256);
        const CUtensorMap* mo = &prm.m[l == 3 ? M_OUT : M_XST];
#pragma unroll
        for (int jj = 0; jj < 8; jj++) {
#pragma unroll
          for (int i = 0; i < 4; i++) x[jj][i] = add_bf16x2(x[jj][i], pack2(acc[8 * jj + 2 * i], acc[8 * jj + 2 * i + 1]));
          stsm4(sb + (jj >> 2) * QSTG + po * 16384 + r * 128 + ((((2 * jj + (lane >> 4)) & 7) ^ (r & 7)) << 4), x[jj][0], x[jj][1], x[jj][2], x[jj][3]);
          if ((jj & 3) == 3) { fence_async_smem(); __syncwarp(); tma_st(mo, pn * 128 + (jj >> 2) * 64, pm * 128 + r0, sb + (jj >> 2) * QSTG + po * 16384 + r0 * 128); }
        }
        bulk_commit();
        if (l < 3) {
          bar_arrive(NB_X, 288);
          float s1[2] = {0.f, 0.f}, s2[2] = {0.f, 0.f};
#pragma unroll
          for (int i = 0; i < 32; i++) {
            const float a = bf_lo(x[i >> 2][i & 3]), c = bf_hi(x[i >> 2][i & 3]);
            s1[i & 1] += a + c; s2[i & 1] = fmaf(a, a, fmaf(c, c, s2[i & 1]));
          }
#pragma unroll
          for (int hh = 0; hh < 2; hh++) { s1[hh] += __shfl_xor_sync(~0u, s1[hh], 1); s2[hh] += __shfl_xor_sync(~0u, s2[hh], 1); }
#pragma unroll
          for (int hh = 0; hh < 2; hh++) {
            s1[hh] += __shfl_xor_sync(~0u, s1[hh], 2); s2[hh] += __shfl_xor_sync(~0u, s2[hh], 2);
            if (qd == 0) g_stats[pn * 2048 + pm * 128 + r0 + g + 8 * hh] = make_float2(s1[hh], s2[hh]);
          }
        }
        bulk_wait_n<0>();
        if (l < 3) bar_arrive(NB_X0, 288);
      }
    }
  }
  asm volatile("barrier.cluster.arrive.relaxed.aligned;\nbarrier.cluster.wait.aligned;" ::: "memory");
}

typedef CUresult (*EncodeFn)(CUtensorMap*, CUtensorMapDataType, cuuint32_t, void*, const cuuint64_t*, const cuuint64_t*, const cuuint32_t*,
                             const cuuint32_t*, CUtensorMapInterleave, CUtensorMapSwizzle, CUtensorMapL2promotion, CUtensorMapFloatOOBfill);

static void make_map(EncodeFn fn, CUtensorMap* m, const void* ptr, int rank, const uint64_t* dims, const uint64_t* strides, const uint32_t* box, CUtensorMapSwizzle sw) {
  cuuint64_t d[5], st[4];
  cuuint32_t bx[5], es[5];
  for (int i = 0; i < rank; i++) { d[i] = dims[i]; bx[i] = box[i]; es[i] = 1; if (i) st[i - 1] = strides[i - 1] * 2; }
  fn(m, CU_TENSOR_MAP_DATA_TYPE_BFLOAT16, rank, (void*)ptr, d, st, bx, es, CU_TENSOR_MAP_INTERLEAVE_NONE, sw,
     CU_TENSOR_MAP_L2_PROMOTION_L2_128B, CU_TENSOR_MAP_FLOAT_OOB_FILL_NONE);
}
static void map2(EncodeFn fn, CUtensorMap* m, const void* ptr, uint64_t inner, uint64_t outer, uint32_t bi, uint32_t bo, CUtensorMapSwizzle sw) {
  const uint64_t d[2] = {inner, outer}, st[1] = {inner};
  const uint32_t bx[2] = {bi, bo};
  make_map(fn, m, ptr, 2, d, st, bx, sw);
}

extern "C" void kernel_launch(void* const* d_in, const int* in_sizes, int n_in, void* d_out, int out_size) {
  (void)in_sizes; (void)n_in; (void)out_size;
  static EncodeFn enc = nullptr;
  static void *xs, *os, *kk, *vv;
  if (!enc) {
    void* p = nullptr;
    cudaDriverEntryPointQueryResult qr;
    cudaGetDriverEntryPoint("cuTensorMapEncodeTiled", &p, cudaEnableDefault, &qr);
    enc = (EncodeFn)p;
    cudaGetSymbolAddress(&xs, g_xs); cudaGetSymbolAddress(&os, g_os); cudaGetSymbolAddress(&kk, g_k); cudaGetSymbolAddress(&vv, g_v);
    cudaFuncSetAttribute(fused_kernel, cudaFuncAttributeMaxDynamicSharedMemorySize, SMEM_BYTES);
  }
  Params prm;
  const CUtensorMapSwizzle S128 = CU_TENSOR_MAP_SWIZZLE_128B, S64 = CU_TENSOR_MAP_SWIZZLE_64B;
  map2(enc, &prm.m[M_X0A], d_in[0], 1024, 2048, 64, 256, S128);
  map2(enc, &prm.m[M_XSA], xs, 1024, 2048, 64, 256, S128);
  for (int t = 0; t < 2; t++) {
    const uint64_t d3[3] = {1024, 1024, 3}, s3[2] = {3072, 1024};
    const uint32_t b3[3] = {64, 64, 3};
    make_map(enc, &prm.m[M_WQA + t], d_in[1 + 3 * t], 3, d3, s3, b3, S128);
    const uint64_t d5[5] = {64, 32, 2, 16, 16}, s5[4] = {1024, 32 * 1024, 64 * 1024, 64};
    const uint32_t b5[5] = {64, 32, 1, 2, 2};
    make_map(enc, &prm.m[M_WOA + t], d_in[2 + 3 * t], 5, d5, s5, b5, S128);
    const uint64_t dr[3] = {64, 2048, 16}, sr[2] = {1024, 64};
    const uint32_t br[3] = {64, 128, 2};
    make_map(enc, &prm.m[M_X0R + t], t ? xs : d_in[0], 3, dr, sr, br, S128);
  }
  map2(enc, &prm.m[M_OS], os, 1024, 2048, 64, 64, S128);
  map2(enc, &prm.m[M_K], kk, 32, 65536, 32, 256, S64);
  map2(enc, &prm.m[M_V], vv, 32, 65536, 32, 256, S64);
  map2(enc, &prm.m[M_K4], kk, 32, 65536, 32, 64, S64);
  map2(enc, &prm.m[M_V4], vv, 32, 65536, 32, 64, S64);
  map2(enc, &prm.m[M_XSO], xs, 1024, 2048, 64, 128, S128);
  map2(enc, &prm.m[M_X0H], d_in[0], 1024, 2048, 64, 128, S128);
  map2(enc, &prm.m[M_XST], xs, 1024, 2048, 64, 16, S128);
  map2(enc, &prm.m[M_OUT], d_out, 1024, 2048, 64, 16, S128);
  prm.x0 = (const bf16*)d_in[0];
  prm.wq[0] = (const bf16*)d_in[1]; prm.wq[1] = (const bf16*)d_in[4];
  prm.zero = 0;
  for (int i = 0; i < 128; i++) prm.map[i] = remap(i);
  fused_kernel<<<128, 384, SMEM_BYTES>>>(prm);
}
```

```cpp
#include <cuda_runtime.h>
#include <cuda_bf16.h>
#include <cuda.h>
#include <stdint.h>

typedef __nv_bfloat16 bf16;

__device__ __forceinline__ void wgmma_m64n192k16_ss_tb(float (&d)[96], uint64_t da, uint64_t db, int scale_d) {
  asm volatile("{\n.reg .pred p;\nsetp.ne.b32 p, %98, 0;\n"
    "wgmma.mma_async.sync.aligned.m64n192k16.f32.bf16.bf16 "
    "{%0, %1, %2, %3, %4, %5, %6, %7, %8, %9, %10, %11, %12, %13, %14, %15, "
    "%16, %17, %18, %19, %20, %21, %22, %23, %24, %25, %26, %27, %28, %29, %30, %31, "
    "%32, %33, %34, %35, %36, %37, %38, %39, %40, %41, %42, %43, %44, %45, %46, %47, "
    "%48, %49, %50, %51, %52, %53, %54, %55, %56, %57, %58, %59, %60, %61, %62, %63, "
    "%64, %65, %66, %67, %68, %69, %70, %71, %72, %73, %74, %75, %76, %77, %78, %79, "
    "%80, %81, %82, %83, %84, %85, %86, %87, %88, %89, %90, %91, %92, %93, %94, %95}, "
    "%96, %97, p, 1, 1, 0, 1;\n}\n"
    : "+f"(d[0]), "+f"(d[1]), "+f"(d[2]), "+f"(d[3]), "+f"(d[4]), "+f"(d[5]), "+f"(d[6]), "+f"(d[7]),
      "+f"(d[8]), "+f"(d[9]), "+f"(d[10]), "+f"(d[11]), "+f"(d[12]), "+f"(d[13]), "+f"(d[14]), "+f"(d[15]),
      "+f"(d[16]), "+f"(d[17]), "+f"(d[18]), "+f"(d[19]), "+f"(d[20]), "+f"(d[21]), "+f"(d[22]), "+f"(d[23]),
      "+f"(d[24]), "+f"(d[25]), "+f"(d[26]), "+f"(d[27]), "+f"(d[28]), "+f"(d[29]), "+f"(d[30]), "+f"(d[31]),
      "+f"(d[32]), "+f"(d[33]), "+f"(d[34]), "+f"(d[35]), "+f"(d[36]), "+f"(d[37]), "+f"(d[38]), "+f"(d[39]),
      "+f"(d[40]), "+f"(d[41]), "+f"(d[42]), "+f"(d[43]), "+f"(d[44]), "+f"(d[45]), "+f"(d[46]), "+f"(d[47]),
      "+f"(d[48]), "+f"(d[49]), "+f"(d[50]), "+f"(d[51]), "+f"(d[52]), "+f"(d[53]), "+f"(d[54]), "+f"(d[55]),
      "+f"(d[56]), "+f"(d[57]), "+f"(d[58]), "+f"(d[59]), "+f"(d[60]), "+f"(d[61]), "+f"(d[62]), "+f"(d[63]),
      "+f"(d[64]), "+f"(d[65]), "+f"(d[66]), "+f"(d[67]), "+f"(d[68]), "+f"(d[69]), "+f"(d[70]), "+f"(d[71]),
      "+f"(d[72]), "+f"(d[73]), "+f"(d[74]), "+f"(d[75]), "+f"(d[76]), "+f"(d[77]), "+f"(d[78]), "+f"(d[79]),
      "+f"(d[80]), "+f"(d[81]), "+f"(d[82]), "+f"(d[83]), "+f"(d[84]), "+f"(d[85]), "+f"(d[86]), "+f"(d[87]),
      "+f"(d[88]), "+f"(d[89]), "+f"(d[90]), "+f"(d[91]), "+f"(d[92]), "+f"(d[93]), "+f"(d[94]), "+f"(d[95])
    : "l"(da), "l"(db), "r"(scale_d));
}

__device__ __forceinline__ void wgmma_m64n128k16_ss_tb(float (&d)[64], uint64_t da, uint64_t db, int scale_d) {
  asm volatile("{\n.reg .pred p;\nsetp.ne.b32 p, %66, 0;\n"
    "wgmma.mma_async.sync.aligned.m64n128k16.f32.bf16.bf16 "
    "{%0, %1, %2, %3, %4, %5, %6, %7, %8, %9, %10, %11, %12, %13, %14, %15, "
    "%16, %17, %18, %19, %20, %21, %22, %23, %24, %25, %26, %27, %28, %29, %30, %31, "
    "%32, %33, %34, %35, %36, %37, %38, %39, %40, %41, %42, %43, %44, %45, %46, %47, "
    "%48, %49, %50, %51, %52, %53, %54, %55, %56, %57, %58, %59, %60, %61, %62, %63}, "
    "%64, %65, p, 1, 1, 0, 1;\n}\n"
    : "+f"(d[0]), "+f"(d[1]), "+f"(d[2]), "+f"(d[3]), "+f"(d[4]), "+f"(d[5]), "+f"(d[6]), "+f"(d[7]),
      "+f"(d[8]), "+f"(d[9]), "+f"(d[10]), "+f"(d[11]), "+f"(d[12]), "+f"(d[13]), "+f"(d[14]), "+f"(d[15]),
      "+f"(d[16]), "+f"(d[17]), "+f"(d[18]), "+f"(d[19]), "+f"(d[20]), "+f"(d[21]), "+f"(d[22]), "+f"(d[23]),
      "+f"(d[24]), "+f"(d[25]), "+f"(d[26]), "+f"(d[27]), "+f"(d[28]), "+f"(d[29]), "+f"(d[30]), "+f"(d[31]),
      "+f"(d[32]), "+f"(d[33]), "+f"(d[34]), "+f"(d[35]), "+f"(d[36]), "+f"(d[37]), "+f"(d[38]), "+f"(d[39]),
      "+f"(d[40]), "+f"(d[41]), "+f"(d[42]), "+f"(d[43]), "+f"(d[44]), "+f"(d[45]), "+f"(d[46]), "+f"(d[47]),
      "+f"(d[48]), "+f"(d[49]), "+f"(d[50]), "+f"(d[51]), "+f"(d[52]), "+f"(d[53]), "+f"(d[54]), "+f"(d[55]),
      "+f"(d[56]), "+f"(d[57]), "+f"(d[58]), "+f"(d[59]), "+f"(d[60]), "+f"(d[61]), "+f"(d[62]), "+f"(d[63])
    : "l"(da), "l"(db), "r"(scale_d));
}

__device__ __forceinline__ void wgmma_m64n32k16_rs_nb_h(float (&d)[16], uint32_t a0, uint32_t a1, uint32_t a2, uint32_t a3, uint64_t db, int scale_d) {
  asm volatile("{\n.reg .pred p;\nsetp.ne.b32 p, %21, 0;\n"
    "wgmma.mma_async.sync.aligned.m64n32k16.f32.f16.f16 "
    "{%0, %1, %2, %3, %4, %5, %6, %7, %8, %9, %10, %11, %12, %13, %14, %15}, "
    "{%16, %17, %18, %19}, %20, p, 1, 1, 0;\n}\n"
    : "+f"(d[0]), "+f"(d[1]), "+f"(d[2]), "+f"(d[3]), "+f"(d[4]), "+f"(d[5]), "+f"(d[6]), "+f"(d[7]),
      "+f"(d[8]), "+f"(d[9]), "+f"(d[10]), "+f"(d[11]), "+f"(d[12]), "+f"(d[13]), "+f"(d[14]), "+f"(d[15])
    : "r"(a0), "r"(a1), "r"(a2), "r"(a3), "l"(db), "r"(scale_d));
}

__device__ __forceinline__ void wgmma_m64n32k16_rs_nb_hh(uint32_t (&d)[8], uint32_t a0, uint32_t a1, uint32_t a2, uint32_t a3, uint64_t db, int scale_d) {
  asm volatile("{\n.reg .pred p;\nsetp.ne.b32 p, %13, 0;\n"
    "wgmma.mma_async.sync.aligned.m64n32k16.f16.f16.f16 "
    "{%0, %1, %2, %3, %4, %5, %6, %7}, "
    "{%8, %9, %10, %11}, %12, p, 1, 1, 0;\n}\n"
    : "+r"(d[0]), "+r"(d[1]), "+r"(d[2]), "+r"(d[3]), "+r"(d[4]), "+r"(d[5]), "+r"(d[6]), "+r"(d[7])
    : "r"(a0), "r"(a1), "r"(a2), "r"(a3), "l"(db), "r"(scale_d));
}

__device__ __forceinline__ void wgmma_m64n64k16_rs_nb_h(float (&d)[32], uint32_t a0, uint32_t a1, uint32_t a2, uint32_t a3, uint64_t db, int scale_d) {
  asm volatile("{\n.reg .pred p;\nsetp.ne.b32 p, %37, 0;\n"
    "wgmma.mma_async.sync.aligned.m64n64k16.f32.f16.f16 "
    "{%0, %1, %2, %3, %4, %5, %6, %7, %8, %9, %10, %11, %12, %13, %14, %15, "
    "%16, %17, %18, %19, %20, %21, %22, %23, %24, %25, %26, %27, %28, %29, %30, %31}, "
    "{%32, %33, %34, %35}, %36, p, 1, 1, 0;\n}\n"
    : "+f"(d[0]), "+f"(d[1]), "+f"(d[2]), "+f"(d[3]), "+f"(d[4]), "+f"(d[5]), "+f"(d[6]), "+f"(d[7]),
      "+f"(d[8]), "+f"(d[9]), "+f"(d[10]), "+f"(d[11]), "+f"(d[12]), "+f"(d[13]), "+f"(d[14]), "+f"(d[15]),
      "+f"(d[16]), "+f"(d[17]), "+f"(d[18]), "+f"(d[19]), "+f"(d[20]), "+f"(d[21]), "+f"(d[22]), "+f"(d[23]),
      "+f"(d[24]), "+f"(d[25]), "+f"(d[26]), "+f"(d[27]), "+f"(d[28]), "+f"(d[29]), "+f"(d[30]), "+f"(d[31])
    : "r"(a0), "r"(a1), "r"(a2), "r"(a3), "l"(db), "r"(scale_d));
}

__device__ __forceinline__ void wgmma_m64n64k16_rs_nb_hh(uint32_t (&d)[16], uint32_t a0, uint32_t a1, uint32_t a2, uint32_t a3, uint64_t db, int scale_d) {
  asm volatile("{\n.reg .pred p;\nsetp.ne.b32 p, %21, 0;\n"
    "wgmma.mma_async.sync.aligned.m64n64k16.f16.f16.f16 "
    "{%0, %1, %2, %3, %4, %5, %6, %7, %8, %9, %10, %11, %12, %13, %14, %15}, "
    "{%16, %17, %18, %19}, %20, p, 1, 1, 0;\n}\n"
    : "+r"(d[0]), "+r"(d[1]), "+r"(d[2]), "+r"(d[3]), "+r"(d[4]), "+r"(d[5]), "+r"(d[6]), "+r"(d[7]),
      "+r"(d[8]), "+r"(d[9]), "+r"(d[10]), "+r"(d[11]), "+r"(d[12]), "+r"(d[13]), "+r"(d[14]), "+r"(d[15])
    : "r"(a0), "r"(a1), "r"(a2), "r"(a3), "l"(db), "r"(scale_d));
}

__device__ __forceinline__ void wgmma_m64n40k16_rs_tb(float (&d)[20], uint32_t a0, uint32_t a1, uint32_t a2, uint32_t a3, uint64_t db, int scale_d) {
  asm volatile("{\n.reg .pred p;\nsetp.ne.b32 p, %25, 0;\n"
    "wgmma.mma_async.sync.aligned.m64n40k16.f32.bf16.bf16 "
    "{%0, %1, %2, %3, %4, %5, %6, %7, %8, %9, %10, %11, %12, %13, %14, %15, "
    "%16, %17, %18, %19}, "
    "{%20, %21, %22, %23}, %24, p, 1, 1, 1;\n}\n"
    : "+f"(d[0]), "+f"(d[1]), "+f"(d[2]), "+f"(d[3]), "+f"(d[4]), "+f"(d[5]), "+f"(d[6]), "+f"(d[7]),
      "+f"(d[8]), "+f"(d[9]), "+f"(d[10]), "+f"(d[11]), "+f"(d[12]), "+f"(d[13]), "+f"(d[14]), "+f"(d[15]),
      "+f"(d[16]), "+f"(d[17]), "+f"(d[18]), "+f"(d[19])
    : "r"(a0), "r"(a1), "r"(a2), "r"(a3), "l"(db), "r"(scale_d));
}

#define DEVINL __device__ __forceinline__
DEVINL void pin(uint32_t z) { asm volatile("{\n.reg .pred p;\nsetp.ne.u32 p, %0, 0;\nPIN:\n@p bra.uni PIN;\n}" ::"r"(z) : "memory"); }
DEVINL void wg_fence() { asm volatile("wgmma.fence.sync.aligned;" ::: "memory"); }
DEVINL void wg_commit() { asm volatile("wgmma.commit_group.sync.aligned;" ::: "memory"); }
template <int N> DEVINL void wg_wait() { asm volatile("wgmma.wait_group.sync.aligned %0;" ::"n"(N) : "memory"); }
DEVINL uint64_t mkdesc(uint32_t addr, uint32_t lbo, uint32_t sbo, int sw) {
  return (uint64_t)((addr & 0x3FFFF) >> 4) | ((uint64_t)(lbo >> 4) << 16) | ((uint64_t)(sbo >> 4) << 32) | ((uint64_t)sw << 62);
}
DEVINL void mbar_arrive(uint32_t bar) { asm volatile("mbarrier.arrive.shared::cta.b64 _, [%0];" ::"r"(bar) : "memory"); }
DEVINL bool mbar_try(uint32_t bar, uint32_t parity) {
  uint32_t ok;
  asm volatile("{\n.reg .pred p;\nmbarrier.try_wait.parity.shared::cta.b64 p, [%1], %2;\nselp.u32 %0, 1, 0, p;\n}" : "=r"(ok) : "r"(bar), "r"(parity) : "memory");
  return ok;
}
DEVINL bool mbar_test(uint32_t bar, uint32_t parity) {
  uint32_t ok;
  asm volatile("{\n.reg .pred p;\nmbarrier.test_wait.parity.shared::cta.b64 p, [%1], %2;\nselp.u32 %0, 1, 0, p;\n}" : "=r"(ok) : "r"(bar), "r"(parity) : "memory");
  return ok;
}
DEVINL void mbar_hint(uint32_t bar, uint32_t parity) {
#pragma unroll 1
  for (uint32_t n = 0; n < 16u; n++) if (mbar_try(bar, parity)) break;
}
DEVINL void mbar_wait(uint32_t bar, uint32_t parity) {
#pragma unroll 1
  for (uint32_t n = 0; n < 100000u; n++) if (mbar_try(bar, parity)) break;
}
#define EL(txt) "{\n.reg .pred pe;\nelect.sync _|pe, 0xffffffff;\n@pe " txt "\n}"
DEVINL void e_expect_tx(uint32_t bar, uint32_t bytes) { asm volatile(EL("mbarrier.arrive.expect_tx.shared::cta.b64 _, [%0], %1;") ::"r"(bar), "r"(bytes) : "memory"); }
DEVINL void e_init(uint32_t bar, uint32_t cnt) { asm volatile(EL("mbarrier.init.shared::cta.b64 [%0], %1;") ::"r"(bar), "r"(cnt) : "memory"); }
DEVINL void e_arrive(uint32_t bar) { asm volatile(EL("mbarrier.arrive.shared::cta.b64 _, [%0];") ::"r"(bar) : "memory"); }
DEVINL void e_red(uint32_t* p) { asm volatile(EL("red.release.gpu.global.add.u32 [%0], 1;") ::"l"(p) : "memory"); }
DEVINL void e_red_relaxed(uint32_t* p) { asm volatile(EL("red.relaxed.gpu.global.add.u32 [%0], 1;") ::"l"(p) : "memory"); }
DEVINL void tma_ld(uint32_t dst, const CUtensorMap* m, int c0, int c1, uint32_t bar) {
  asm volatile(EL("cp.async.bulk.tensor.2d.shared::cluster.global.mbarrier::complete_tx::bytes [%0], [%1, {%3, %4}], [%2];")
               ::"r"(dst), "l"(m), "r"(bar), "r"(c0), "r"(c1) : "memory");
}
DEVINL void tma_ld3(uint32_t dst, const CUtensorMap* m, int c0, int c1, int c2, uint32_t bar) {
  asm volatile(EL("cp.async.bulk.tensor.3d.shared::cluster.global.mbarrier::complete_tx::bytes [%0], [%1, {%3, %4, %5}], [%2];")
               ::"r"(dst), "l"(m), "r"(bar), "r"(c0), "r"(c1), "r"(c2) : "memory");
}
DEVINL void tma_ld5(uint32_t dst, const CUtensorMap* m, int c2, int c3, int c4, uint32_t bar) {
  asm volatile(EL("cp.async.bulk.tensor.5d.shared::cluster.global.mbarrier::complete_tx::bytes [%0], [%1, {0, 0, %3, %4, %5}], [%2];")
               ::"r"(dst), "l"(m), "r"(bar), "r"(c2), "r"(c3), "r"(c4) : "memory");
}
DEVINL void tma_ld_mc(uint32_t dst, const CUtensorMap* m, int c0, int c1, uint32_t bar) {
  asm volatile(EL("cp.async.bulk.tensor.2d.shared::cluster.global.mbarrier::complete_tx::bytes.multicast::cluster [%0], [%1, {%3, %4}], [%2], %5;")
               ::"r"(dst), "l"(m), "r"(bar), "r"(c0), "r"(c1), "h"((uint16_t)3) : "memory");
}
DEVINL void e_arrive_both(uint32_t bar) {
  asm volatile("{\n.reg .pred pe;\n.reg .b32 r0, r1;\nelect.sync _|pe, 0xffffffff;\nmapa.shared::cluster.u32 r0, %0, 0;\nmapa.shared::cluster.u32 r1, %0, 1;\n"
               "@pe mbarrier.arrive.shared::cluster.b64 _, [r0];\n@pe mbarrier.arrive.shared::cluster.b64 _, [r1];\n}" ::"r"(bar) : "memory");
}
DEVINL void tma_st(const CUtensorMap* m, int c0, int c1, uint32_t src) {
  asm volatile(EL("cp.async.bulk.tensor.2d.global.shared::cta.bulk_group [%0, {%2, %3}], [%1];") ::"l"(m), "r"(src), "r"(c0), "r"(c1) : "memory");
}
DEVINL void bulk_commit() { asm volatile("cp.async.bulk.commit_group;" ::: "memory"); }
template <int N> DEVINL void bulk_wait_n() { asm volatile("cp.async.bulk.wait_group %0;\nbar.warp.sync 0xffffffff;" ::"n"(N) : "memory"); }
DEVINL void l2_prefetch(const void* g, uint32_t bytes) { asm volatile(EL("cp.async.bulk.prefetch.L2.global [%0], %1;") ::"l"(g), "r"(bytes) : "memory"); }
DEVINL void fence_async_smem() { asm volatile("fence.proxy.async.shared::cta;" ::: "memory"); }
DEVINL void fence_async_gl() { asm volatile("fence.proxy.async.global;" ::: "memory"); }
DEVINL void cluster_wait() { asm volatile("barrier.cluster.wait.aligned;" ::: "memory"); }
DEVINL void bar_sync(int id, int n) { asm volatile("bar.sync %0, %1;" ::"r"(id), "r"(n) : "memory"); }
DEVINL void bar_arrive(int id, int n) { asm volatile("bar.arrive %0, %1;" ::"r"(id), "r"(n) : "memory"); }
DEVINL uint32_t ld_acquire(const uint32_t* p) { uint32_t v; asm volatile("ld.acquire.gpu.global.u32 %0, [%1];" : "=r"(v) : "l"(p) : "memory"); return v; }
DEVINL void watch(const uint32_t* p, uint32_t target, uint32_t all, uint32_t tag, uint32_t slot) {
  uint32_t seen = 0;
#pragma unroll 1
  for (uint32_t n = 0; n < 200000u && seen != all; n++) {
    const uint32_t m = __ballot_sync(~0u, (int)(ld_acquire(p) - target) >= 0) & all;
    if (m != seen) { seen = m; asm volatile("st.release.cta.shared.u32 [%0], %1;" ::"r"(slot), "r"(tag << 16 | m) : "memory"); }
  }
}
template <bool RELAXED = false> DEVINL void await_bit(uint32_t slot, uint32_t tag, int j, uint32_t& rdy) {
  if ((rdy >> j) & 1) return;
#pragma unroll 1
  for (uint32_t n = 0; n < 8000000u; n++) {
    uint32_t v;
    asm volatile("ld.acquire.cta.shared.u32 %0, [%1];" : "=r"(v) : "r"(slot) : "memory");
    if ((v >> 16) == tag && ((v >> j) & 1)) { rdy = v; break; }
    if (RELAXED) __nanosleep(200);
  }
  asm volatile("fence.proxy.async.global;" ::: "memory");
}
DEVINL void poll_ge(const uint32_t* p, uint32_t target) {
#pragma unroll 1
  for (uint32_t n = 0; n < 200000u; n++) if (__all_sync(~0u, (int)(ld_acquire(p) - target) >= 0)) break;
}
DEVINL int lane_id() { int v; asm volatile("mov.u32 %0, %%laneid;" : "=r"(v)); return v; }
__host__ DEVINL int remap(int v) {
  const int c = v >> 1, u = c - 36, r = (u * 37) >> 8;
  const int L = max(c - 4 + max(r + 1, 0), (c - 4) >> 31 & (32 + 8 * c));
  return 2 * L + (v & 1);
}
DEVINL int block_id() { int v; asm volatile("mov.u32 %0, %%ctaid.x;" : "=r"(v)); return v; }
#define cta_id() prm.map[block_id()]
#define IDS() const int lane = lane_id(), b = cta_id(), bm = b >> 4, bn = b & 15, rank = b & 1, pm = 2 * bm + (bn >> 3), pn = bn & 7, po = pm & 1; \
  (void)lane; (void)bm; (void)bn; (void)rank; (void)pm; (void)pn; (void)po
DEVINL void st_tagged(unsigned long long* p, uint32_t v, uint32_t tag) {
  asm volatile("{\n.reg .b64 t;\nmov.b64 t, {%1, %2};\nst.relaxed.gpu.global.b64 [%0], t;\n}" ::"l"(p), "r"(v), "r"(tag) : "memory");
}
DEVINL float ex2(float x) { float y; asm("ex2.approx.ftz.f32 %0, %1;" : "=f"(y) : "f"(x)); return y; }
DEVINL float rcp(float x) { float y; asm("rcp.approx.ftz.f32 %0, %1;" : "=f"(y) : "f"(x)); return y; }
DEVINL uint32_t pack2(float lo, float hi) { uint32_t r; asm("cvt.rn.bf16x2.f32 %0, %1, %2;" : "=r"(r) : "f"(hi), "f"(lo)); return r; }
DEVINL float bf_lo(uint32_t w) { return __uint_as_float(w << 16); }
DEVINL float bf_hi(uint32_t w) { return __uint_as_float(w & 0xFFFF0000u); }
DEVINL float bf_round(float x) { return bf_lo(pack2(x, 0.f)); }
DEVINL uint32_t add_bf16x2(uint32_t a, uint32_t b) { uint32_t r; asm("add.rn.bf16x2 %0, %1, %2;" : "=r"(r) : "r"(a), "r"(b)); return r; }
DEVINL void stsm4(uint32_t addr, uint32_t a, uint32_t b, uint32_t c, uint32_t d) {
  asm volatile("stmatrix.sync.aligned.m8n8.x4.shared.b16 [%0], {%1, %2, %3, %4};" ::"r"(addr), "r"(a), "r"(b), "r"(c), "r"(d) : "memory");
}
DEVINL void ldsm4(uint32_t addr, uint32_t (&r)[4]) {
  asm volatile("ldmatrix.sync.aligned.m8n8.x4.shared.b16 {%0, %1, %2, %3}, [%4];" : "=r"(r[0]), "=r"(r[1]), "=r"(r[2]), "=r"(r[3]) : "r"(addr) : "memory");
}
DEVINL void ldsm4t(uint32_t addr, uint32_t (&r)[4]) {
  asm volatile("ldmatrix.sync.aligned.m8n8.x4.trans.shared.b16 {%0, %1, %2, %3}, [%4];" : "=r"(r[0]), "=r"(r[1]), "=r"(r[2]), "=r"(r[3]) : "r"(addr) : "memory");
}
DEVINL void sts128(uint32_t addr, uint32_t a, uint32_t b, uint32_t c, uint32_t d) {
  asm volatile("st.shared.v4.b32 [%0], {%1, %2, %3, %4};" ::"r"(addr), "r"(a), "r"(b), "r"(c), "r"(d) : "memory");
}
DEVINL float4 lds128f(uint32_t addr) { float4 v; asm volatile("ld.shared.v4.f32 {%0, %1, %2, %3}, [%4];" : "=f"(v.x), "=f"(v.y), "=f"(v.z), "=f"(v.w) : "r"(addr) : "memory"); return v; }
DEVINL float lds32f(uint32_t addr) { float v; asm volatile("ld.shared.f32 %0, [%1];" : "=f"(v) : "r"(addr) : "memory"); return v; }
DEVINL float2 lds64f(uint32_t addr) { float2 v; asm volatile("ld.shared.v2.f32 {%0, %1}, [%2];" : "=f"(v.x), "=f"(v.y) : "r"(addr) : "memory"); return v; }
DEVINL void mma16816(float (&d)[4], uint32_t a0, uint32_t a1, uint32_t a2, uint32_t a3, uint32_t b0, uint32_t b1) {
  asm("mma.sync.aligned.m16n8k16.row.col.f32.bf16.bf16.f32 {%0, %1, %2, %3}, {%4, %5, %6, %7}, {%8, %9}, {%0, %1, %2, %3};"
               : "+f"(d[0]), "+f"(d[1]), "+f"(d[2]), "+f"(d[3]) : "r"(a0), "r"(a1), "r"(a2), "r"(a3), "r"(b0), "r"(b1));
}
DEVINL void mma1688(float (&d)[4], uint32_t a0, uint32_t a1, uint32_t b0) {
  asm("mma.sync.aligned.m16n8k8.row.col.f32.bf16.bf16.f32 {%0, %1, %2, %3}, {%4, %5}, {%6}, {%0, %1, %2, %3};"
               : "+f"(d[0]), "+f"(d[1]), "+f"(d[2]), "+f"(d[3]) : "r"(a0), "r"(a1), "r"(b0));
}
DEVINL void mma16816h(float (&d)[4], uint32_t a0, uint32_t a1, uint32_t a2, uint32_t a3, uint32_t b0, uint32_t b1) {
  asm("mma.sync.aligned.m16n8k16.row.col.f32.f16.f16.f32 {%0, %1, %2, %3}, {%4, %5, %6, %7}, {%8, %9}, {%0, %1, %2, %3};"
               : "+f"(d[0]), "+f"(d[1]), "+f"(d[2]), "+f"(d[3]) : "r"(a0), "r"(a1), "r"(a2), "r"(a3), "r"(b0), "r"(b1));
}
template <int N> DEVINL void fence_regs(uint32_t (&d)[N]) {
#pragma unroll
  for (int i = 0; i < N; i++) asm volatile("" : "+r"(d[i])::"memory");
}
template <int N> DEVINL void fence_regs(float (&d)[N]) {
#pragma unroll
  for (int i = 0; i < N; i++) asm volatile("" : "+f"(d[i])::"memory");
}

__device__ __align__(1024) bf16 g_xs[2048 * 1024];
__device__ __align__(1024) bf16 g_os[2048 * 1024];
__device__ __align__(1024) bf16 g_k[32 * 2048 * 32];
__device__ __align__(1024) bf16 g_v[32 * 2048 * 32];
__device__ __align__(128) float2 g_stats[8 * 2048];
__device__ __align__(16) float g_csp[2 * 16 * 8 * 192];
__device__ __align__(128) float g_kn[2 * 128 * 32];
__device__ unsigned long long g_halo[2 * 128 * 32 * 32];
__device__ __align__(128) uint32_t g_cnt[256 * 32];
__device__ uint32_t g_epoch;

DEVINL uint32_t* cnt_x(int l, int bm) { return g_cnt + (l * 8 + bm) * 32; }
DEVINL uint32_t* cnt_o(int l, int pm, int h) { return g_cnt + (32 + (l * 16 + pm) * 2 + h) * 32; }
DEVINL uint32_t* cnt_kv(int lb, int bn) { return g_cnt + (160 + lb * 16 + bn) * 32; }
DEVINL uint32_t* cnt_ad(int bn) { return g_cnt + (192 + bn) * 32; }
DEVINL uint32_t* cnt_cs(int t, int bn) { return g_cnt + (208 + t * 16 + bn) * 32; }

DEVINL int qord(int i, int l, int pn) { return l == 0 ? i : i < 4 ? ((2 * pn) ^ (i & 2)) + (i & 1) : i - 4 < 2 * (pn & 6) ? i - 4 : i; }
struct Params {
  CUtensorMap m[17];
  const bf16* x0;
  const bf16* wq[2];
  uint32_t* epoch;
  uint32_t zero;
  int map[128];
};
enum { M_X0A = 0, M_XSA, M_WQA, M_WQB, M_WOA, M_WOB, M_OS, M_K, M_V, M_X0R, M_XSR, M_XSO, M_OUT, M_XST, M_X0H, M_K4, M_V4, M_COUNT };

constexpr uint32_t QSTG = 57344;
constexpr uint32_t T0 = 65536, TSTG = 32768;
constexpr uint32_t ONES = 230400;
constexpr uint32_t PSTG = 32768, RES = 196608;
constexpr uint32_t ASC = 17408;
constexpr uint32_t ROWST = 229376, COLS = 231424, BARS = 232192, SMEM_BYTES = 232448;
constexpr uint32_t B_QF = BARS, B_QE = BARS + 32, B_TF = BARS + 64, B_TE = BARS + 96, B_PF = BARS + 128, B_PE = BARS + 176,
                   B_RF = BARS + 224, W_X = BARS + 232, W_O = BARS + 236, B_QL = BARS + 240, B_PA = BARS + 248;
enum { NB_ST = 1, NB_KV = 2  , NB_DONE = 3, NB_SC = 4, NB_SIG = 5  , NB_KN = 9  , NB_X = 11, NB_HALO = 12  , NB_X0 = 15 };

DEVINL uint32_t pslot_b(uint32_t s, int l) { return ((((l & 1) ? 0x320415u : 0x468795u) >> (4 * s)) & 15) * 16384u; }
DEVINL uint32_t pslot_a(uint32_t s, int l) { return ((((l & 1) ? 0xBA7896u : 0x32DCBAu) >> (4 * s)) & 15) * 16384u; }

#define G1 2
#define G2 0
#define G3 2
#define KC (11 + 2 * wg)
#define NA2 2
#define RESI 9
#define PERHEAD 1
#define PUBMODE 1
#define LA 1
#define LB 1
#define PFETCH 0
#define NQ 32
#define OA 0x10
#define OB 0x10
#define LAG 2
#define QK_A wgmma_m64n32k16_rs_nb_h
#define QK_B wgmma_m64n32k16_rs_nb_hh
constexpr float QSCALE = 0.17677669529663687f * 1.4426950408889634f;

DEVINL uint32_t hfma2(uint32_t a, uint32_t b, uint32_t c) { uint32_t r; asm("fma.rn.f16x2 %0, %1, %2, %3;" : "=r"(r) : "r"(a), "r"(b), "r"(c)); return r; }
DEVINL uint32_t pack2h(float lo, float hi) { uint32_t r; asm("cvt.rn.f16x2.f32 %0, %1, %2;" : "=r"(r) : "f"(hi), "f"(lo)); return r; }
DEVINL uint32_t h2_to_bf2(uint32_t h) {
  float a, b;
  asm("{\n.reg .b16 l, h;\nmov.b32 {l, h}, %2;\ncvt.f32.f16 %0, l;\ncvt.f32.f16 %1, h;\n}" : "=f"(a), "=f"(b) : "r"(h));
  return pack2(a, b);
}
DEVINL uint32_t exp2_h2(uint32_t s) {
  const uint32_t r = hfma2(s, 0x00800080u, 0x007E007Eu);
  const uint32_t g = hfma2(hfma2(r, 0xF800F800u, 0x33FD33FDu), 0x44004400u, s);
  return r * 128u + hfma2(hfma2(g, g, 0x0DE10DE1u), g, 0x00300030u);
}
constexpr uint32_t NOT_F16 = 0x7FC00000u, K_LO = 0x35000000u  ;
DEVINL uint32_t f16_class(uint32_t norm2, uint32_t lo) { return norm2 - lo > 0x4E800000u - lo ? NOT_F16 : norm2; }

DEVINL void attn_slow(const uint32_t (&q)[8], float up, int head, const float* kn, float (&res)[20], int lane) {
  const int g = lane >> 2, qd = lane & 3;
  const bf16* kb = g_k + (size_t)head * 2048 * 32;
  const bf16* vb = g_v + (size_t)head * 2048 * 32;
  float o[4][4], m0 = -INFINITY, m1 = -INFINITY, l0 = 0.f, l1 = 0.f;
#pragma unroll
  for (int j = 0; j < 4; j++) { o[j][0] = o[j][1] = o[j][2] = o[j][3] = 0.f; }
#pragma unroll 1
  for (int k0 = 0; k0 < 2048; k0 += 16) {
    float s[2][4];
    const bool kh = __float_as_uint(__ldcg(kn + (k0 >> 8) * 32 + ((k0 >> 6) & 1) * 8 + ((k0 >> 7) & 1) * 4 + ((k0 >> 4) & 3))) != NOT_F16;
#pragma unroll
    for (int nt = 0; nt < 2; nt++) {
      s[nt][0] = s[nt][1] = s[nt][2] = s[nt][3] = 0.f;
      const uint32_t* kp = (const uint32_t*)(kb + (size_t)(k0 + nt * 8 + g) * 32) + qd;
      uint32_t kf[4];
#pragma unroll
      for (int i = 0; i < 4; i++) { kf[i] = __ldcg(kp + 4 * i); if (kh) kf[i] = h2_to_bf2(kf[i]); }
      mma16816(s[nt], q[0], q[1], q[2], q[3], kf[0], kf[1]);
      mma16816(s[nt], q[4], q[5], q[6], q[7], kf[2], kf[3]);
      s[nt][0] *= up; s[nt][1] *= up; s[nt][2] *= up; s[nt][3] *= up;
    }
    float a0 = fmaxf(fmaxf(s[0][0], s[0][1]), fmaxf(s[1][0], s[1][1]));
    float a1 = fmaxf(fmaxf(s[0][2], s[0][3]), fmaxf(s[1][2], s[1][3]));
    a0 = fmaxf(a0, __shfl_xor_sync(~0u, a0, 1)); a0 = fmaxf(a0, __shfl_xor_sync(~0u, a0, 2));
    a1 = fmaxf(a1, __shfl_xor_sync(~0u, a1, 1)); a1 = fmaxf(a1, __shfl_xor_sync(~0u, a1, 2));
    const float n0 = fmaxf(m0, a0), n1 = fmaxf(m1, a1);
    const float c0 = (m0 == n0) ? 1.f : ex2(m0 - n0), c1 = (m1 == n1) ? 1.f : ex2(m1 - n1);
    m0 = n0; m1 = n1;
    const uint32_t p0 = pack2(ex2(s[0][0] - n0), ex2(s[0][1] - n0)), p1 = pack2(ex2(s[0][2] - n1), ex2(s[0][3] - n1));
    const uint32_t p2 = pack2(ex2(s[1][0] - n0), ex2(s[1][1] - n0)), p3 = pack2(ex2(s[1][2] - n1), ex2(s[1][3] - n1));
    l0 = l0 * c0 + bf_lo(p0) + bf_hi(p0) + bf_lo(p2) + bf_hi(p2);
    l1 = l1 * c1 + bf_lo(p1) + bf_hi(p1) + bf_lo(p3) + bf_hi(p3);
#pragma unroll
    for (int j = 0; j < 4; j++) {
      o[j][0] *= c0; o[j][1] *= c0; o[j][2] *= c1; o[j][3] *= c1;
      const unsigned short* vp = (const unsigned short*)(vb + (size_t)(k0 + 2 * qd) * 32 + j * 8 + g);
      const uint32_t b0 = (uint32_t)__ldcg(vp) | ((uint32_t)__ldcg(vp + 32) << 16);
      const uint32_t b1 = (uint32_t)__ldcg(vp + 256) | ((uint32_t)__ldcg(vp + 288) << 16);
      mma16816(o[j], p0, p1, p2, p3, b0, b1);
    }
  }
  l0 += __shfl_xor_sync(~0u, l0, 1); l0 += __shfl_xor_sync(~0u, l0, 2);
  l1 += __shfl_xor_sync(~0u, l1, 1); l1 += __shfl_xor_sync(~0u, l1, 2);
#pragma unroll
  for (int j = 0; j < 4; j++) { res[4 * j] = o[j][0]; res[4 * j + 1] = o[j][1]; res[4 * j + 2] = o[j][2]; res[4 * j + 3] = o[j][3]; }
  res[16] = l0; res[18] = l1;
}

__global__ void __cluster_dims__(2, 1, 1) __launch_bounds__(384, 1) fused_kernel(const __grid_constant__ Params prm) {
  extern __shared__ __align__(1024) char smem[];
  const uint32_t sb = (uint32_t)__cvta_generic_to_shared(smem);
  const int tid = threadIdx.x;
  const int wid = __shfl_sync(0xffffffffu, tid >> 5, 0), wg = wid >> 2, w = wid & 3;
  const int bm = remap(blockIdx.x) >> 4, bn = remap(blockIdx.x) & 15;
  auto first_tile = [&](int kt) {
    e_expect_tx(sb + B_QF + 8 * kt, QSTG);
    tma_ld(sb + kt * QSTG, &prm.m[M_X0A], kt * 64, bm * 256, sb + B_QF + 8 * kt);
    tma_ld3(sb + kt * QSTG + 32768, &prm.m[M_WQA], bn * 64, kt * 64, 0, sb + B_QF + 8 * kt);
  };
  if (wid == 8) {
    e_init(sb + B_QF, 1);
    asm volatile("fence.mbarrier_init.release.cluster;" ::: "memory");
    first_tile(0);
  }
  if (wid < 8) {
#pragma unroll
    for (int i = 0; i < 4; i++) {
      const uint32_t cnt = (uint32_t)((i == 0 ? 0x14112140 : i == 1 ? 0x04112141 : i == 2 ? 0x14412141 : 0x24412141) >> (4 * wid)) & 7;
      if (cnt) e_init(sb + BARS + 32 * wid + 8 * i, cnt);
    }
    if (tid == 255) *(uint2*)(smem + W_X) = make_uint2(0u, 0u);
    asm volatile("fence.mbarrier_init.release.cluster;" ::: "memory");
  }
  const uint32_t epoch = *(volatile uint32_t*)prm.epoch;
  __syncthreads();
  asm volatile("barrier.cluster.arrive.relaxed.aligned;" ::: "memory");

  if (wg == 2) {
    asm volatile("setmaxnreg.dec.sync.aligned.u32 56;");
    const uint32_t ep1 = epoch + 1;
    if (w == 0) {
      first_tile(1);
      mbar_wait(sb + B_QF, 0);
      first_tile(2); first_tile(3);
#pragma unroll 1
      for (int kt = 4; kt < 16; kt++) l2_prefetch(prm.wq[0] + kt * 196608 + blockIdx.x * 1536, 3072);
      cluster_wait();
#pragma unroll 1
      for (int l = 0; l < 4; l++) {
        IDS();
        const CUtensorMap* mw = &prm.m[M_WQA + (l & 1)];
        const CUtensorMap* mx = &prm.m[l == 0 ? M_X0A : M_XSA];
        const CUtensorMap* mh = &prm.m[l == 0 ? M_X0H : M_XSO];
        const CUtensorMap* mo = &prm.m[M_WOA + (l & 1)];
        auto q_b = [&](int i) {
          const int s = i & 3;
          mbar_wait(sb + B_QE + 8 * s, ((i >> 2) & 1) ^ 1);
          e_expect_tx(sb + B_QF + 8 * s, QSTG);
          tma_ld3(sb + s * QSTG + 32768, mw, bn * 64, qord(i, l, pn) * 64, 0, sb + B_QF + 8 * s);
        };
        uint32_t rdy = l ? 0u : ~0u;
        auto q_a = [&](int i) {
          const int kt = qord(i, l, pn);
          await_bit(sb + W_X, l, kt >> 1, rdy);
          if (i < 4) tma_ld(sb + i * QSTG, mx, kt * 64, bm * 256, sb + B_QF + 8 * i);
          else tma_ld_mc(sb + (i & 3) * QSTG + rank * 16384, mh, kt * 64, bm * 256 + rank * 128, sb + B_QF + 8 * (i & 3));
        };
        if (l > 0) {
          await_bit(sb + W_X, l, pn, rdy);
#pragma unroll 1
          for (int i = 0; i < 2; i++) {
            e_expect_tx(sb + B_QF + 8 * i, 16384);
            tma_ld(sb + i * QSTG + (po ^ 1) * 16384, &prm.m[M_XSO], (2 * pn + i) * 64, (pm ^ 1) * 128, sb + B_QF + 8 * i);
          }
          mbar_wait(sb + B_QF, 0);
          q_a(2);
          mbar_wait(sb + B_QF + 8, 0);
        }
#pragma unroll 1
        for (int i = l ? 3 : 4; i < 16; i++) {
          q_b(i); q_a(i);
        }
        if (l & 1) {
          if (l == 3) poll_ge(cnt_ad(bn), ep1 * 16);
          const int krow = 2 * bn * 2048 + bm * 256;
          uint32_t* kvc = cnt_kv(l >> 1, bn);
#pragma unroll 1
          for (int m = 1; m >= 0; m--) {
            bar_sync(m ? NB_ST : NB_KV, 288);
#pragma unroll
            for (int i = 0; i < 4; i++) tma_st(&prm.m[M_K4 + (i >> 1)], 0, krow + (i & 1) * 128 + m * 64, sb + T0 + i * 8192 + m * 4096);
            if (m) {
              sts128(sb + ONES + lane * 32, 0x3f803f80u, 0x3f803f80u, 0x3f803f80u, 0x3f803f80u);
              sts128(sb + ONES + lane * 32 + 16, 0x3f803f80u, 0x3f803f80u, 0x3f803f80u, 0x3f803f80u);
              fence_async_smem();
              __syncwarp();
            }
          }
          e_arrive(sb + B_TF);
          bulk_commit(); bulk_wait_n<0>();
          e_red(kvc + bm);
          bar_sync(NB_KV + 12, 288);
          tma_st(&prm.m[M_K], 0, krow + 2048, sb);
          tma_st(&prm.m[M_V], 0, krow + 2048, sb + 16384);
          bulk_commit();
          uint32_t seen = 0;
#pragma unroll 1
          for (int it = 1; it < 16; it++) {
            const int s = it & 3, blk = it;
            if (it == 4) { bulk_wait_n<0>(); e_red(kvc + bm); }
            if (it == 12) { e_expect_tx(sb + B_RF, 32768); tma_ld3(sb + RES, &prm.m[M_XSR], 0, pm * 128, 2 * pn, sb + B_RF); }
            if (it == 2 || it == 3) mbar_wait(sb + B_TF + 8 * (it - 1), 0);
            mbar_wait(sb + B_TE + 8 * s, ((it >> 2) & 1) ^ 1);
            if (it < 8) {
#pragma unroll 1
              for (uint32_t n = 0; n < 200000u && !((seen >> it) & 1); n++)
                seen = __ballot_sync(~0u, (int)(ld_acquire(kvc + ((bm + lane) & 7)) - (ep1 * 2 - 1)) >= 0);
              fence_async_gl();
            } else if (it == 8) { poll_ge(kvc + (lane & 7), ep1 * 2); fence_async_gl(); }
            const int row = (2 * bn + (it >> 3)) * 2048 + ((bm + blk) & 7) * 256;
            e_expect_tx(sb + B_TF + 8 * s, 32768);
            tma_ld(sb + T0 + s * TSTG, &prm.m[M_K], 0, row, sb + B_TF + 8 * s);
            tma_ld(sb + T0 + s * TSTG + 16384, &prm.m[M_V], 0, row, sb + B_TF + 8 * s);
          }
        }
        auto p_b = [&](int i, uint32_t s, uint32_t par) {
          mbar_wait(sb + B_PE + 8 * s, par ^ 1);
          e_expect_tx(sb + B_PF + 8 * s, PSTG);
          tma_ld5(sb + pslot_b(s, l), mo, i >> 3, 2 * (i & 7), 2 * pn, sb + B_PF + 8 * s);
        };
        auto p_a = [&](int i, uint32_t s) {
          await_bit(sb + W_O, l + 1, i, rdy);
          tma_ld_mc(sb + pslot_a(s, l) + rank * 8192, &prm.m[M_OS], i * 64, pm * 128 + rank * 64, sb + B_PF + 8 * s);
        };
        auto p_a2 = [&](int i) {
          await_bit(sb + W_O, l + 1, i, rdy);
          tma_ld(sb + pslot_a(i, l), &prm.m[M_OS], i * 64, pm * 128, sb + B_PF + 8 * i);
          tma_ld(sb + pslot_a(i, l) + 8192, &prm.m[M_OS], i * 64, pm * 128 + 64, sb + B_PF + 8 * i);
        };
        rdy = 0;
        if (l & 1) {
#pragma unroll 1
          for (int u = 0; u < 6; u++) { const int i = (0x205413 >> (4 * u)) & 7; if (u == 4) mbar_wait(sb + B_TE, 1); p_b(i, i, i < 4 ? 1 : 0); }
#pragma unroll 1
          for (int u = 0; u < 6; u++) {
            const int i = (0x542130 >> (4 * u)) & 7;
            if (!(u & 1)) mbar_wait(sb + B_TE + 8 + 4 * u, 1);
            p_a2(i);
          }
        } else {
#pragma unroll 1
          for (int u = 0; u < 5; u++) { const int i = (0x32140 >> (4 * u)) & 7; if (!(u & 5)) mbar_wait(sb + B_QE + 8 + 4 * u, 1); p_b(i, i, 0); }
          mbar_wait(sb + B_QE + 24, 1);
#pragma unroll 1
          for (int i = 0; i < 4; i++) { if (i < NA2) p_a2(i); else p_a(i, i); }
          bar_sync(NB_DONE, 96);
          e_arrive_both(sb + B_PA);
          p_b(5, 5, 0);
          mbar_wait(sb + B_PA, (l >> 1) & 1);
          p_a(4, 4); p_a(5, 5);
        }
        uint32_t s = 0, lap = 1;
#pragma unroll 1
        for (int i = 6; i < 16; i++) {
          if (i == RESI && !(l & 1)) { e_expect_tx(sb + B_RF, 32768); tma_ld3(sb, &prm.m[l == 0 ? M_X0R : M_XSR], 0, pm * 128, 2 * pn, sb + B_RF); }
          p_b(i, s, ((s < 4 ? l : 0) + lap) & 1);
          p_a(i, s);
          if (++s == 6) { s = 0; lap++; }
        }
        const CUtensorMap* mn = &prm.m[M_WQA + ((l + 1) & 1)];
        if (l < 3) {
          mbar_wait(sb + B_PE + 8 * 4, 1); mbar_wait(sb + B_PE + 8 * 5, 1);
          tma_ld3(sb + 32768, mn, bn * 64, 2 * pn * 64, 0, sb + B_QL);
          mbar_wait(sb + B_PE + 8 * 0, l & 1);
          tma_ld3(sb + QSTG + 32768, mn, bn * 64, (2 * pn + 1) * 64, 0, sb + B_QL);
          mbar_wait(sb + B_PE + 8 * 1, l & 1);
          e_expect_tx(sb + B_QF + 16, QSTG);
          tma_ld3(sb + 2 * QSTG + 32768, mn, bn * 64, ((2 * pn) ^ 2) * 64, 0, sb + B_QF + 16);
        }
        if (l < 3) { bar_sync(NB_X, 288); e_expect_tx(sb + B_QL, 49152); }
      }
      if (blockIdx.x == 0 && lane_id() == 0) *(volatile uint32_t*)prm.epoch = ep1;
    } else {
      const int hw = w - 1;
      if (hw == 1 && lane_id() < M_COUNT) asm volatile("prefetch.tensormap [%0];" ::"l"(&prm.m[lane_id()]) : "memory");
      cluster_wait();
      mbar_wait(sb + B_QF, 0);
#pragma unroll 1
      for (int l = 0; l < 4; l++) {
        IDS();
        if (hw == 2 && l > 0) watch(cnt_x(l, bm) + (lane & 7), ep1 * 2, 0xFFu, l, sb + W_X);
        if (l == 0) {
#pragma unroll 1
          for (int r = 2 * hw; r < 16; r += 6) {
            const uint4* p = (const uint4*)(prm.x0 + (size_t)(b * 16 + r) * 1024) + lane;
            float s1[2] = {0.f, 0.f}, s2[2] = {0.f, 0.f};
#pragma unroll
            for (int i = 0; i < 8; i++) {
              const uint4 v = __ldg(p + 32 * i);
              const uint32_t u[4] = {v.x, v.y, v.z, v.w};
#pragma unroll
              for (int k = 0; k < 4; k++) { const float a = bf_lo(u[k]), c = bf_hi(u[k]); s1[i >> 2] += a + c; s2[i >> 2] = fmaf(a, a, fmaf(c, c, s2[i >> 2])); }
            }
#pragma unroll
            for (int o = 16; o; o >>= 1)
#pragma unroll
              for (int rr = 0; rr < 2; rr++) { s1[rr] += __shfl_xor_sync(~0u, s1[rr], o); s2[rr] += __shfl_xor_sync(~0u, s2[rr], o); }
            if (lane == 0) *(float4*)&g_stats[b * 16 + r] = make_float4(s1[0], s2[0], s1[1], s2[1]);
          }
        }
        if (l == 1) { uint32_t rdy = 0; await_bit<true>(sb + W_X, 1, pn, rdy); mbar_hint(sb + B_QF + 8, 0); }
        if (l < 2) {
          float cs[8];
#pragma unroll
          for (int i = 0; i < 8; i++) cs[i] = 0.f;
          const uint4* wp = (const uint4*)(prm.wq[l] + (size_t)(bm * 128 + (lane >> 3)) * 3072 + hw * 1024 + bn * 64) + (lane & 7);
#pragma unroll 8
          for (int i = 0; i < 32; i++) {
            const uint4 v = __ldg(wp + (size_t)i * 4 * 384);
            cs[0] += bf_lo(v.x); cs[1] += bf_hi(v.x); cs[2] += bf_lo(v.y); cs[3] += bf_hi(v.y);
            cs[4] += bf_lo(v.z); cs[5] += bf_hi(v.z); cs[6] += bf_lo(v.w); cs[7] += bf_hi(v.w);
          }
#pragma unroll
          for (int i = 0; i < 8; i++) { cs[i] += __shfl_xor_sync(~0u, cs[i], 8); cs[i] += __shfl_xor_sync(~0u, cs[i], 16); }
          if (lane < 8) {
            float4* d = (float4*)(g_csp + ((l * 16 + bn) * 8 + bm) * 192 + hw * 64 + lane * 8);
            d[0] = make_float4(cs[0], cs[1], cs[2], cs[3]); d[1] = make_float4(cs[4], cs[5], cs[6], cs[7]);
          }
          __syncwarp();
          asm volatile("fence.acq_rel.gpu;" ::: "memory");
          e_red_relaxed(cnt_cs(l, bn));
          if (l == 0) e_red_relaxed(cnt_x(0, bm) + pn);
          poll_ge(lane < 8 && l == 0 ? cnt_x(0, bm) + lane : cnt_cs(l, bn), ep1 * (lane < 8 && l == 0 ? 6 : 24));
        }
        if (l > 0) {
          uint32_t rdy = 0;
#pragma unroll 1
          for (int j = 0; j < 8; j++) await_bit<true>(sb + W_X, l, j, rdy);
        }
#pragma unroll 1
        for (int it = hw * 32 + lane; it < 176; it += 96) {
          const bool rows = it < 128;
          const float4* p = rows ? (const float4*)(g_stats + bm * 256) + it : (const float4*)(g_csp + ((l & 1) * 16 + bn) * 8 * 192) + (it - 128);
          const int stride = rows ? 1024 : 48, np = rows && l == 0 ? 1 : 8;
          float4 a = make_float4(0.f, 0.f, 0.f, 0.f);
#pragma unroll
          for (int k = 0; k < 8; k++) if (k < np) { const float4 v = __ldcg(p + k * stride); a.x += v.x; a.y += v.y; a.z += v.z; a.w += v.w; }
          if (rows) {
            const float m0 = a.x * (1.f / 1024.f), m1 = a.z * (1.f / 1024.f);
            const float v0 = fmaxf(a.y * (1.f / 1024.f) - m0 * m0, 0.f), v1 = fmaxf(a.w * (1.f / 1024.f) - m1 * m1, 0.f);
            const float r0 = __fdividef(1.f, bf_round(sqrtf(bf_round(bf_round(v0) + 1e-5f)))), r1 = __fdividef(1.f, bf_round(sqrtf(bf_round(bf_round(v1) + 1e-5f))));
            a = make_float4(r0, -bf_round(m0), r1, -bf_round(m1));
          }
          if (rows) *(float4*)(smem + ROWST + it * 16) = a;
          else {
            float2* d = (float2*)(smem + COLS) + ((it - 128) >> 2) * 8 + (it & 1) * 4 + ((it >> 1) & 1);
            d[0] = make_float2(a.y, a.x); d[2] = make_float2(a.w, a.z);
          }
        }
        __syncwarp();
        if (lane == 0) asm volatile("red.release.cta.shared.add.u32 [%0], 0x100;" ::"r"(sb + W_X) : "memory");
        if (hw == 2) {
          if (!(l & 1)) {
            bar_sync(NB_ST, 288);
            const volatile unsigned long long* hp = g_halo + ((size_t)(l >> 1) * 128 + b - 16) * 1024 + lane;
#pragma unroll 1
            for (int h = 0; h < 2; h++) {
              uint32_t t[16];
#pragma unroll
              for (int i = 0; i < 16; i++) t[i] = 0;
#pragma unroll 1
              for (uint32_t n = bm ? 0 : 100000u; n < 100000u; n++) {
                uint32_t miss = 0;
#pragma unroll
                for (int i = 0; i < 16; i++) {
                  const unsigned long long v = hp[h * 512 + i * 32];
                  t[i] = (uint32_t)v; miss |= (uint32_t)(v >> 32) ^ ep1;
                }
                if (__all_sync(~0u, !miss)) break;
              }
              const uint32_t r = (lane & 7) + ((lane >> 3) & 1) * 8, rv = lane >> 2;
#pragma unroll
              for (int jj = 0; jj < 2; jj++) stsm4(sb + 2 * h * ASC + r * 64 + (((2 * jj + (lane >> 4)) ^ ((r >> 1) & 3)) << 4), t[4 * jj], t[4 * jj + 1], t[4 * jj + 2], t[4 * jj + 3]);
              const uint32_t ad = sb + (2 * h + 1) * ASC + rv * 64 + (((lane & 3) ^ ((rv >> 1) & 3)) << 4);
              sts128(ad, t[8], t[10], t[12], t[14]); sts128(ad + 512, t[9], t[11], t[13], t[15]);
              bar_arrive(NB_HALO + h, 64);
            }
          } else {
            mbar_hint(sb + B_TF + 8, 0);
            poll_ge(cnt_kv(l >> 1, bn) + (lane & 7), ep1 * 2);
            const uint4* kp = (const uint4*)(g_kn + ((l >> 1) * 128 + bn * 8) * 32) + 2 * lane;
            const uint4 v = __ldcg(kp), u = __ldcg(kp + 1);
            const uint32_t mx = max(max(max(v.x, v.y), max(v.z, v.w)), max(max(u.x, u.y), max(u.z, u.w)));
            const uint32_t m0 = __reduce_max_sync(~0u, (lane & 2) ? 0u : mx), m1 = __reduce_max_sync(~0u, (lane & 2) ? mx : 0u);
            if (lane == 0) *(uint2*)(smem + ROWST) = make_uint2(m0, m1);
            __syncwarp();
            bar_arrive(NB_KN, 160); bar_arrive(NB_KN + 1, 160);
          }
        } else {
          bar_sync(NB_SIG + 2 * hw, 160); bar_sync(NB_SIG + 2 * hw + 1, 160);
          if (!(l & 1)) bar_arrive(NB_DONE, 96);
          asm volatile("fence.acq_rel.gpu;" ::: "memory");
          e_red_relaxed(cnt_o(l, 2 * bm, hw) + (bn >> 1));
          e_red_relaxed(cnt_o(l, 2 * bm + 1, hw) + (bn >> 1));
          if (hw == 1 && l == 1) { e_red_relaxed(cnt_ad(bn)); e_red_relaxed(cnt_ad(bn)); }
        }
        if (hw == 2) watch(cnt_o(l, pm, (lane >> 3) & 1) + (lane & 7), ep1 * 2, 0xFFFFu, l + 1, sb + W_O);
        if (hw == 0 && l < 3) {
          bar_sync(NB_X0, 288);
          e_red(cnt_x(l + 1, bm) + pn);
        }
      }
    }
  } else {
    asm volatile("setmaxnreg.inc.sync.aligned.u32 224;");
    const uint32_t zero = prm.zero;
    cluster_wait();
    const uint32_t ep1 = __shfl_sync(~0u, epoch + 1, 0);
#pragma unroll 1
    for (int l = 0; l < 4; l++) {
      {
        float acc[2][96];
#pragma unroll
        for (int i = 0; i < 96; i++) { acc[0][i] = 0.f; acc[1][i] = 0.f; }
        fence_regs(acc[0]); fence_regs(acc[1]);
        const bool early = l > 0 && wg == ((cta_id() >> 3) & 1);
#pragma unroll 1
        for (int kt = 0; kt < 14; kt++) {
          const int s = kt & 3;
          if (l > 0 && kt == 0) mbar_wait(sb + B_QL, (l + 1) & 1);
          if (!(early && kt < 2)) mbar_wait(sb + B_QF + 8 * s, (kt >> 2) & 1);
          const uint64_t da = mkdesc(sb + s * QSTG + wg * 16384, 16, 1024, 1), db = mkdesc(sb + s * QSTG + 32768, 8192, 1024, 1);
          wg_fence();
#pragma unroll
          for (int k = 0; k < 4; k++)
#pragma unroll
            for (int m = 0; m < 2; m++) wgmma_m64n192k16_ss_tb(acc[m], da + m * 512 + k * 2, db + k * 128, 1);
          wg_commit();
          wg_wait<1>();
          if (early && (kt == 1 || kt == 2)) mbar_wait(sb + B_QF + 8 * (kt - 1), 0);
          if (kt > 0 && w == 0) e_arrive_both(sb + B_QE + 8 * ((kt - 1) & 3));
          if (kt == KC) {
#pragma unroll 1
            for (uint32_t n = 0; n < 4000000u; n++) {
              uint32_t v;
              asm volatile("ld.acquire.cta.shared.u32 %0, [%1];" : "=r"(v) : "r"(sb + W_X) : "memory");
              if ((v >> 8) == (uint32_t)(l * 256 + 3)) break;
            }
            const int lane = lane_id();
            float nm[4];
#pragma unroll
            for (int i = 0; i < 4; i++) nm[i] = lds32f(sb + ROWST + (wg * 128 + w * 16 + (lane >> 2) + (i >> 1) * 64 + (i & 1) * 8) * 8 + 4);
            wg_wait<0>();
            fence_regs(acc[0]); fence_regs(acc[1]);
#pragma unroll
            for (int j = 0; j < 12; j++) {
              const float4 c = lds128f(sb + COLS + j * 64 + (lane & 3) * 16);
#pragma unroll
              for (int m = 0; m < 2; m++) {
                float* a = &acc[m][8 * j];
                a[0] = fmaf(nm[2 * m], c.y, a[0]); a[1] = fmaf(nm[2 * m], c.x, a[1]); a[2] = fmaf(nm[2 * m + 1], c.y, a[2]); a[3] = fmaf(nm[2 * m + 1], c.x, a[3]);
                a[4] = fmaf(nm[2 * m], c.w, a[4]); a[5] = fmaf(nm[2 * m], c.z, a[5]); a[6] = fmaf(nm[2 * m + 1], c.w, a[6]); a[7] = fmaf(nm[2 * m + 1], c.z, a[7]);
              }
            }
            fence_regs(acc[0]); fence_regs(acc[1]);
          }
        }
        auto part = [&](int s, int m, int k0, int k1) {
          const uint64_t da = mkdesc(sb + s * QSTG + wg * 16384 + m * 8192, 16, 1024, 1), db = mkdesc(sb + s * QSTG + 32768, 8192, 1024, 1);
          pin(zero);
          wg_fence();
#pragma unroll
          for (int k = k0; k < k1; k++) wgmma_m64n192k16_ss_tb(acc[m], da + k * 2, db + k * 128, 1);
          wg_commit();
          pin(zero);
        };
        mbar_wait(sb + B_QF + 16, 1);
        part(2, 1, 0, 4);
        wg_wait<1>();
        if (w == 0) e_arrive_both(sb + B_QE + 8);
        if (!(l & 1)) bar_arrive(NB_ST, 288);
        mbar_wait(sb + B_QF + 24, 1);
        part(3, 1, 0, 4);
        part(2, 0, 0, G1);
        IDS();
        const int g = lane >> 2, qd = lane & 3;
        float rs[2][2];
#pragma unroll
        for (int i = 0; i < 4; i++) rs[i >> 1][i & 1] = lds32f(sb + ROWST + (wg * 128 + w * 16 + g + (i >> 1) * 64 + (i & 1) * 8) * 8);
        auto scale = [&](int gi, int m, float sc) {
          const float r0 = rs[m][0] * sc, r1 = rs[m][1] * sc;
#pragma unroll
          for (int i = 0; i < 16; i++) acc[m][16 * gi + i] *= (i & 2) ? r1 : r0;
        };
        auto pack_b = [&](int gi, int m, uint32_t (&t)[8]) {
#pragma unroll
          for (int i = 0; i < 8; i++) t[i] = pack2(acc[m][16 * gi + 2 * i], acc[m][16 * gi + 2 * i + 1]);
        };
        auto norm_tile = [&](int gi, int m, uint32_t (&t)[8]) { scale(gi, m, 1.f); pack_b(gi, m, t); };
        auto pack_h = [&](int gi, int m, uint32_t (&t)[8]) {
#pragma unroll
          for (int i = 0; i < 8; i++) t[i] = pack2h(acc[m][16 * gi + 2 * i], acc[m][16 * gi + 2 * i + 1]);
        };
        uint32_t q[2][2][8], qn[2][2];
        const uint32_t srow = (lane & 7) + ((lane >> 3) & 1) * 8;
        const uint32_t row0 = wg * 128 + w * 16;
        auto put_kv = [&](int h, int v, int m, const uint32_t (&t)[8]) {
          const uint32_t base = sb + ((l & 1) ? (h ? 0 : T0) + v * 16384 : (2 * h + v) * ASC + 1024) + (row0 + m * 64) * 64;
          if (!v) {
#pragma unroll
            for (int jj = 0; jj < 2; jj++) stsm4(base + srow * 64 + (((2 * jj + (lane >> 4)) ^ ((srow >> 1) & 3)) << 4), t[4 * jj], t[4 * jj + 1], t[4 * jj + 2], t[4 * jj + 3]);
          } else {
            const uint32_t ad = base + g * 64 + ((qd ^ (g >> 1)) << 4);
            sts128(ad, t[0], t[2], t[4], t[6]); sts128(ad + 512, t[1], t[3], t[5], t[7]);
          }
        };
        auto send_halo = [&](int h, int v, const uint32_t (&t)[8]) {
          unsigned long long* hp = g_halo + ((size_t)(l >> 1) * 128 + b) * 1024 + h * 512 + v * 256 + lane;
#pragma unroll
          for (int i = 0; i < 8; i++) st_tagged(hp + i * 32, t[i], ep1);
        };
        auto put_kn = [&](int h, int m, uint32_t kn) {
          if (lane == 0) g_kn[((l >> 1) * 128 + bn * 8 + bm) * 32 + 16 * h + 8 * m + wg * 4 + w] = __uint_as_float(kn);
        };
        auto conv_tile1 = [&](int h) {
          uint32_t t[8], tv[8], kn = NOT_F16;
          norm_tile(4 + h, 1, tv);
          put_kv(h, 1, 1, tv);
          scale(2 + h, 1, 1.f);
          if (h == 0) { if (G1 < 4) part(2, 0, G1, 4); if (G2) part(3, 0, 0, G2); } else if (G3 < 4) part(3, 0, G3, 4);
          if (l & 1) {
            float n[2] = {0.f, 0.f};
#pragma unroll
            for (int i = 0; i < 16; i++) n[(i >> 1) & 1] = fmaf(acc[1][32 + 16 * h + i], acc[1][32 + 16 * h + i], n[(i >> 1) & 1]);
            const float a = ((qd & 1) ? n[1] : n[0]) + __shfl_xor_sync(~0u, (qd & 1) ? n[0] : n[1], 1);
            scale(h, 1, QSCALE / 128.f);
            kn = f16_class(__reduce_max_sync(~0u, __float_as_uint(a + __shfl_xor_sync(~0u, a, 2))), K_LO);
            put_kn(h, 1, kn);
          } else scale(h, 1, 1.f);
          if (kn == NOT_F16) pack_b(2 + h, 1, t); else pack_h(2 + h, 1, t);
          put_kv(h, 0, 1, t);
          if (!(l & 1) && row0 == 176 && bm < 7) { send_halo(h, 0, t); send_halo(h, 1, tv); }
        };
        mbar_wait(sb + B_QE + 8, 1);
        wg_wait<1>();
        fence_regs(acc[1]);
        conv_tile1(0);
        if (G2 < G3) part(3, 0, G2, G3);
        if (l & 1) { fence_async_smem(); bar_arrive(NB_ST, 288); }
        conv_tile1(1);
        wg_wait<(G2 > 0) + (G2 < G3) + (G3 < 4)>();
        if (w == 0) e_arrive_both(sb + B_QE + 16);
        wg_wait<0>();
        fence_regs(acc[0]);
        if (w == 0) e_arrive_both(sb + B_QE + 24);
        bf16* const op0 = [&] { IDS(); return g_os + (size_t)(bm * 256 + row0 + (lane >> 2)) * 1024 + bn * 32 + (lane & 3) * 8; }();
        auto put_o = [&](int h, int m, const float (&o)[16], float i0, float i1) {
          bf16* op = op0 + m * 65536 + h * 512;
          const uint4 a = make_uint4(pack2(o[0] * i0, o[1] * i0), pack2(o[4] * i0, o[5] * i0), pack2(o[8] * i0, o[9] * i0), pack2(o[12] * i0, o[13] * i0));
          const uint4 c = make_uint4(pack2(o[2] * i1, o[3] * i1), pack2(o[6] * i1, o[7] * i1), pack2(o[10] * i1, o[11] * i1), pack2(o[14] * i1, o[15] * i1));
          *(uint4*)op = a; *(uint4*)(op + 8 * 1024) = c;
          const uint32_t hi = __vimax3_u16x2(__vimax3_u16x2(a.x, a.y, a.z), __vimax3_u16x2(a.w, c.x, c.y), __vmaxu2(c.z, c.w));
          const uint32_t lo = __vimax3_s16x2(__vimax3_s16x2(a.x, a.y, a.z), __vimax3_s16x2(a.w, c.x, c.y), __vmaxs2(c.z, c.w));
          return __vmaxu2(hi & 0x7FFF7FFFu, lo & 0x7FFF7FFFu);
        };
        if (!(l & 1)) {
          auto conv_kv = [&](int h) {
            uint32_t t[8];
            norm_tile(2 + h, 0, t); put_kv(h, 0, 0, t);
            norm_tile(4 + h, 0, t); put_kv(h, 1, 0, t);
          };
          conv_kv(0);
          if (!PERHEAD) conv_kv(1);
          norm_tile(0, 0, q[0][0]); pack_b(0, 1, q[0][1]);
          bar_sync(NB_SC, 256);
          const bool e = g & 1, sel = 2 * qd + (g & 1) >= g + 2, first = bm == 0 && row0 == 0;
#pragma unroll 1
          for (int h = 0; h < 2; h++) {
            if (row0 == 0) bar_sync(NB_HALO + h, 64);
            float s[2][4][4];
            uint32_t vf[2][4][4], pf[2][2][4];
#pragma unroll
            for (int m = 0; m < 2; m++)
#pragma unroll
              for (int nt = 0; nt < 4; nt++) {
                uint32_t kf[4];
                const uint32_t r = row0 + m * 64 + 8 * nt + (lane & 7);
                ldsm4(sb + 2 * h * ASC + r * 64 + (((lane >> 3) ^ ((r >> 1) & 3)) << 4), kf);
                s[m][nt][0] = s[m][nt][1] = s[m][nt][2] = s[m][nt][3] = 0.f;
                mma16816(s[m][nt], q[0][m][0], q[0][m][1], q[0][m][2], q[0][m][3], kf[0], kf[1]);
                mma16816(s[m][nt], q[0][m][4], q[0][m][5], q[0][m][6], q[0][m][7], kf[2], kf[3]);
              }
#pragma unroll
            for (int m = 0; m < 2; m++)
#pragma unroll
              for (int i = 0; i < 4; i++) {
                const uint32_t r = row0 + m * 64 + 16 * (i >> 1) + srow, ch = 2 * (i & 1) + (lane >> 4);
                ldsm4t(sb + (2 * h + 1) * ASC + r * 64 + ((ch ^ ((r >> 1) & 3)) << 4), vf[m][i]);
              }
            float va[4], vb[4], mx[4];
#pragma unroll
            for (int i = 0; i < 4; i++) {
              const int m = i >> 1, hh = i & 1;
              const float a = e ? s[m][hh + 1][2 * hh + 1] : s[m][hh + 1][2 * hh];
              const float lo = e ? s[m][hh][2 * hh + 1] : s[m][hh][2 * hh], hi = e ? s[m][hh + 2][2 * hh + 1] : s[m][hh + 2][2 * hh];
              const uint32_t t = pack2(a, sel ? lo : hi);
              const uint32_t u = pack2(bf_lo(t) * 0.17677669529663687f, bf_hi(t) * 0.17677669529663687f);
              va[i] = (m == 0 && hh == 0 && first) ? -INFINITY : bf_lo(u);
              vb[i] = (m == 0 && first && sel) ? -INFINITY : bf_hi(u);
              mx[i] = fmaxf(va[i], vb[i]);
            }
#pragma unroll
            for (int i = 0; i < 4; i++) mx[i] = fmaxf(mx[i], __shfl_xor_sync(~0u, mx[i], 1));
#pragma unroll
            for (int i = 0; i < 4; i++) mx[i] = fmaxf(mx[i], __shfl_xor_sync(~0u, mx[i], 2));
#pragma unroll
            for (int i = 0; i < 4; i++) {
              va[i] = ex2((va[i] - mx[i]) * 1.4426950408889634f); vb[i] = ex2((vb[i] - mx[i]) * 1.4426950408889634f);
              mx[i] = va[i] + vb[i];
            }
#pragma unroll
            for (int i = 0; i < 4; i++) mx[i] += __shfl_xor_sync(~0u, mx[i], 1);
#pragma unroll
            for (int i = 0; i < 4; i++) mx[i] += __shfl_xor_sync(~0u, mx[i], 2);
#pragma unroll
            for (int i = 0; i < 4; i++) {
              const int m = i >> 1, hh = i & 1;
              const float inv = rcp(mx[i]);
              const uint32_t t = pack2(va[i] * inv, vb[i] * inv);
              const uint32_t pa = e ? t << 16 : t & 0xFFFFu, pb = e ? t & 0xFFFF0000u : t >> 16;
              pf[m][hh][hh + 1] = pa; pf[m][hh][hh] = sel ? pb : 0u; pf[m][hh][hh + 2] = sel ? 0u : pb; pf[m][hh][3 - 3 * hh] = 0u;
            }
#pragma unroll
            for (int m = 0; m < 2; m++) {
              float o[4][4];
#pragma unroll
              for (int j = 0; j < 4; j++) o[j][0] = o[j][1] = o[j][2] = o[j][3] = 0.f;
#pragma unroll
              for (int i = 0; i < 4; i++) {
                const int kk = i >> 1, jj = 2 * (i & 1);
                mma16816(o[jj], pf[m][0][2 * kk], pf[m][1][2 * kk], pf[m][0][2 * kk + 1], pf[m][1][2 * kk + 1], vf[m][i][0], vf[m][i][1]);
                mma16816(o[jj + 1], pf[m][0][2 * kk], pf[m][1][2 * kk], pf[m][0][2 * kk + 1], pf[m][1][2 * kk + 1], vf[m][i][2], vf[m][i][3]);
              }
              const float of[16] = {o[0][0], o[0][1], o[0][2], o[0][3], o[1][0], o[1][1], o[1][2], o[1][3], o[2][0], o[2][1], o[2][2], o[2][3], o[3][0], o[3][1], o[3][2], o[3][3]};
              put_o(h, m, of, 1.f, 1.f);
            }
            bar_arrive(NB_SIG + 2 * h + wg, 160);
            if (h == 0) {
              if (PERHEAD) conv_kv(1);
              norm_tile(1, 0, q[0][0]); pack_b(1, 1, q[0][1]);
              if (PERHEAD) bar_sync(NB_SC, 256);
            }
          }
        } else {
          auto conv_h = [&](int gi, int m, uint32_t (&t)[8]) {
            pack_h(gi, m, t);
            float d0[4] = {0.f, 0.f, 0.f, 0.f}, d1[4] = {0.f, 0.f, 0.f, 0.f};
            mma16816h(d0, t[0], t[1], t[2], t[3], t[0], t[2]); mma16816h(d1, t[0], t[1], t[2], t[3], t[1], t[3]);
            mma16816h(d0, t[4], t[5], t[6], t[7], t[4], t[6]); mma16816h(d1, t[4], t[5], t[6], t[7], t[5], t[7]);
            return (uint32_t)__reduce_max_sync(~0u, max(max(__float_as_int(d0[0]), __float_as_int(d0[1])), max(__float_as_int(d1[2]), __float_as_int(d1[3]))));
          };
#pragma unroll
          for (int h = 0; h < 2; h++) {
            uint32_t t[8], tv[8];
            scale(2 + h, 0, 1.f);
            const uint32_t kn = f16_class(conv_h(2 + h, 0, t), K_LO);
            if (h) {
#pragma unroll
              for (int i = 0; i < 2; i++) {
                scale(i, 0, QSCALE);
                qn[i][0] = f16_class(conv_h(i, 0, q[i][0]), K_LO);
                qn[i][1] = f16_class(conv_h(i, 1, q[i][1]), K_LO);
              }
            }
            norm_tile(4 + h, 0, tv);
            put_kv(h, 1, 0, tv);
            put_kn(h, 0, kn);
            if (kn == NOT_F16) pack_b(2 + h, 0, t);
            put_kv(h, 0, 0, t);
            fence_async_smem();
            bar_arrive(NB_KV + 12 * h, 288);
            if (h == 0) mbar_wait(sb + B_QF + 24, 1);
          }
          if (max(max(qn[0][0], qn[0][1]), max(qn[1][0], qn[1][1])) == NOT_F16) {
#pragma unroll
            for (int i = 0; i < 4; i++) if (qn[i >> 1][i & 1] == NOT_F16) pack_b(i >> 1, i & 1, q[i >> 1][i & 1]);
          }
          const bool elected = w == 0 && lane == 0;
          const uint64_t kd0 = mkdesc(sb + T0, 16, 512, 2);
          const uint64_t vd0 = mkdesc(sb + T0 + 16384, ONES - (T0 + 16384), 512, 2);
          constexpr uint64_t VSTEP = 64 - (64ull << 16);
          constexpr int RPC = NQ / 16, NC = 256 / NQ;
          float o[2][20], SA[2][NQ / 2];
          uint32_t SB[2][NQ / 4], PA[LA][4], PB[LB][4];
#pragma unroll
          for (int m = 0; m < 2; m++) {
#pragma unroll
            for (int i = 0; i < NQ / 2; i++) SA[m][i] = 0.f;
#pragma unroll
            for (int i = 0; i < NQ / 4; i++) SB[m][i] = 0u;
            fence_regs(SA[m]); fence_regs(SB[m]);
          }
          auto qka = [&](int b, int k, uint64_t d, int h = 0) { QK_A(SA[b], q[h][0][4 * k], q[h][0][4 * k + 1], q[h][0][4 * k + 2], q[h][0][4 * k + 3], d + 2 * k, k ? 1 : zero); };
          auto qkb = [&](int b, int k, uint64_t d, int h = 0) { QK_B(SB[b], q[h][1][4 * k], q[h][1][4 * k + 1], q[h][1][4 * k + 2], q[h][1][4 * k + 3], d + 2 * k, k ? 1 : zero); };
          auto pv = [&](int m, const uint32_t (&Px)[4], uint64_t vd) { wgmma_m64n40k16_rs_tb(o[m], Px[0], Px[1], Px[2], Px[3], vd, 1); };
          auto clear = [&]() {
#pragma unroll
            for (int i = 0; i < 20; i++) o[0][i] = o[1][i] = 0.f;
            fence_regs(o[0]); fence_regs(o[1]);
#pragma unroll
            for (int i = 0; i < 4; i++) PA[0][i] = PB[0][i] = PA[LA - 1][i] = PB[LB - 1][i] = zero;
          };
          mbar_wait(sb + B_TF, 0);
          wg_fence(); qka(0, 0, kd0); qkb(0, 0, kd0); qka(0, 1, kd0); qkb(0, 1, kd0); wg_commit();
          clear();
          wg_wait<0>(); fence_regs(SA[0]); fence_regs(SB[0]);
#pragma unroll 1
          for (int pass = 0; pass < 2; pass++) {
#pragma unroll 1
            for (int j = 0; j < 8; j++) {
              const uint32_t s = j & 3, sn = j < 7 ? (j + 1) & 3 : s, sp = j > 0 ? (j + 3) & 3 : s;
              const uint64_t kd = kd0 + s * 2048, vd = vd0 + s * (32 * VSTEP), kdn = kd0 + sn * 2048, vdp = vd0 + sp * (32 * VSTEP) + 16 * VSTEP;
              bool landed = false;
#pragma unroll
              for (int r = 0; r < 16; r++) {
                const int c = r / RPC, ro = r % RPC, cn = c + 1;
                if (r == 16 - RPC && !landed) mbar_wait(sb + B_TF + 8 * sn, ((j + 1) >> 2) & 1);
                wg_fence();
                const uint64_t kx = cn < NC ? kd + cn * NQ * 4 : kdn, va = (r >= LA ? vd : vdp) + (r - LA) * VSTEP, vb = (r >= LB ? vd : vdp) + (r - LB) * VSTEP;
                if (LAG & 4) { pv(0, PA[r % LA], va); pv(1, PB[r % LB], vb); }
#pragma unroll
                for (int k = 0; k < 2; k++) {
                  if (ro == ((OA >> (4 * k)) & 15)) qka(cn & 1, k, kx);
                  if (ro == ((OB >> (4 * k)) & 15)) qkb(cn & 1, k, kx);
                }
                if (!(LAG & 4)) {
                  if (ro == RPC - 1 || (LAG & 1)) wg_commit();
                  if (LAG & 8) { pv(1, PB[r % LB], vb); pv(0, PA[r % LA], va); } else { pv(0, PA[r % LA], va); pv(1, PB[r % LB], vb); }
                }
                wg_commit();
                if (r == 14 - RPC) landed = mbar_test(sb + B_TF + 8 * sn, ((j + 1) >> 2) & 1) || j == 7;
#pragma unroll
                for (int i = 0; i < 4; i++) {
                  if (LAG & 16) PB[r % LB][i] = exp2_h2(SB[c & 1][4 * ro + i]);
                  PA[r % LA][i] = pack2(ex2(SA[c & 1][8 * ro + 2 * i]), ex2(SA[c & 1][8 * ro + 2 * i + 1]));
                  if (!(LAG & 16)) PB[r % LB][i] = exp2_h2(SB[c & 1][4 * ro + i]);
                }
                if (r == 15 || ((LAG & 4) && ro == RPC - 1 && ((OA >> 4) == ro || (OB >> 4) == ro))) wg_wait<0>(); else if (ro == RPC - 1 || !(LAG & 2)) wg_wait<1>();
                if (ro == RPC - 1) { fence_regs(SA[cn & 1]); fence_regs(SB[cn & 1]); }
                if (r == (LA + LB > 2 ? 4 : RPC) && elected && j > 0) mbar_arrive(sb + B_TE + 8 * sp);
              }
            }
            int badm = 0;
            if (pass == 0) mbar_wait(sb + B_TF, 0);
            wg_fence();
            if (LA == 2) pv(0, PA[0], vd0 + 110 * VSTEP);
            if (LB == 2) pv(1, PB[0], vd0 + 110 * VSTEP);
            pv(0, PA[LA - 1], vd0 + 111 * VSTEP); pv(1, PB[LB - 1], vd0 + 111 * VSTEP); wg_commit();
            qka(0, 0, kd0, 1); qkb(0, 0, kd0, 1); qka(0, 1, kd0, 1); qkb(0, 1, kd0, 1); wg_commit();
            if (pass == 0) bar_sync(NB_KN + wg, 160);
            const float kmax = *(volatile float*)(smem + ROWST + 4 * pass);
            wg_wait<1>(); fence_regs(o[0]); fence_regs(o[1]);
            if (w == 0) e_arrive(sb + B_TE + 8 * 3);
#pragma unroll
            for (int m = 0; m < 2; m++) {
              const float of[16] = {o[m][0], o[m][1], o[m][2], o[m][3], o[m][4], o[m][5], o[m][6], o[m][7], o[m][8], o[m][9], o[m][10], o[m][11], o[m][12], o[m][13], o[m][14], o[m][15]};
              const uint32_t chk = put_o(pass, m, of, rcp(o[m][16]), rcp(o[m][18]));
              const bool bad = !(__uint_as_float(qn[0][m]) * kmax <= (m ? 0.875f * 0.875f : 112.f * 112.f)) || !(fminf(o[m][16], o[m][18]) >= 9.3e-10f) ||
                               !(o[m][16] + o[m][18] <= 3e38f) || ((chk + 0x00800080u) & 0x80008000u);
              badm |= __any_sync(~0u, bad) << m;
            }
            wg_wait<0>(); fence_regs(SA[0]); fence_regs(SB[0]);
            if (badm) {
#pragma unroll 1
              for (int m = 0; m < 2; m++) if ((badm >> m) & 1) {
                uint32_t qq[8]; float res[20];
#pragma unroll
                for (int i = 0; i < 8; i++) { qq[i] = m ? q[0][1][i] : q[0][0][i]; if ((m ? qn[0][1] : qn[0][0]) != NOT_F16) qq[i] = h2_to_bf2(qq[i]); }
                attn_slow(qq, m ? 128.f : 1.f, 2 * (cta_id() & 15) + pass, g_kn + ((l >> 1) * 128 + (cta_id() & 15) * 8) * 32 + 16 * pass, res, lane_id());
                const float of[16] = {res[0], res[1], res[2], res[3], res[4], res[5], res[6], res[7], res[8], res[9], res[10], res[11], res[12], res[13], res[14], res[15]};
                put_o(pass, m, of, rcp(res[16]), rcp(res[18]));
              }
            }
            bar_arrive(NB_SIG + 2 * pass + wg, 160);
            qn[0][0] = qn[1][0]; qn[0][1] = qn[1][1];
#pragma unroll
            for (int m = 0; m < 2; m++)
#pragma unroll
              for (int i = 0; i < 8; i++) q[0][m][i] = q[1][m][i];
            clear();
          }
        }
      }
      {
        float acc[64];
#pragma unroll
        for (int i = 0; i < 64; i++) acc[i] = 0.f;
        fence_regs(acc);
        uint32_t s = 0, lap = 0;
#pragma unroll 1
        for (int kt = 0; kt < 16; kt++) {
          mbar_wait(sb + B_PF + 8 * s, ((s < 4 ? l : 0) + lap) & 1);
          const uint64_t da = mkdesc(sb + pslot_a(s, l) + wg * 8192, 16, 1024, 1), db = mkdesc(sb + pslot_b(s, l), 8192, 1024, 1);
          wg_fence();
#pragma unroll
          for (int k = 0; k < 4; k++) wgmma_m64n128k16_ss_tb(acc, da + k * 2, db + k * 128, 1);
          wg_commit();
          wg_wait<1>();
          if (kt > 0 && w == 0) e_arrive_both(sb + B_PE + 8 * (s ? s - 1 : 5));
          if (++s == 6) { s = 0; lap++; }
        }
        IDS();
        const int g = lane >> 2, qd = lane & 3;
        const int r0 = wg * 64 + w * 16;
        const uint32_t r = r0 + (lane & 7) + ((lane >> 3) & 1) * 8;
        uint32_t x[8][4];
        mbar_wait(sb + B_RF, l & 1);
#pragma unroll
        for (int jj = 0; jj < 8; jj++) ldsm4(sb + ((l & 1) ? RES : 0) + (jj >> 2) * 16384 + r * 128 + ((((2 * jj + (lane >> 4)) & 7) ^ (r & 7)) << 4), x[jj]);
        wg_wait<0>();
        fence_regs(acc);
        if (w == 0) e_arrive_both(sb + B_PE + 8 * 3);
        bar_sync(NB_SC, 256);
        const CUtensorMap* mo = &prm.m[l == 3 ? M_OUT : M_XST];
#pragma unroll
        for (int jj = 0; jj < 8; jj++) {
#pragma unroll
          for (int i = 0; i < 4; i++) x[jj][i] = add_bf16x2(x[jj][i], pack2(acc[8 * jj + 2 * i], acc[8 * jj + 2 * i + 1]));
          stsm4(sb + (jj >> 2) * QSTG + po * 16384 + r * 128 + ((((2 * jj + (lane >> 4)) & 7) ^ (r & 7)) << 4), x[jj][0], x[jj][1], x[jj][2], x[jj][3]);
          if ((jj & 3) == 3) { fence_async_smem(); __syncwarp(); tma_st(mo, pn * 128 + (jj >> 2) * 64, pm * 128 + r0, sb + (jj >> 2) * QSTG + po * 16384 + r0 * 128); }
        }
        bulk_commit();
        if (l < 3) {
          bar_arrive(NB_X, 288);
          float s1[4] = {0.f, 0.f, 0.f, 0.f}, s2[4][4];
#pragma unroll
          for (int i = 0; i < 16; i++) s2[i >> 2][i & 3] = 0.f;
#pragma unroll
          for (int jj = 0; jj < 8; jj++) {
            mma16816(s1, x[jj][0], x[jj][1], x[jj][2], x[jj][3], 0x3f803f80u, 0x3f803f80u);
#pragma unroll
            for (int i = 0; i < 4; i++) mma1688(s2[i], x[jj][i & 2], x[jj][i | 1], x[jj][i]);
          }
          if (qd == (g >> 1)) {
            float2* sp = g_stats + pn * 2048 + pm * 128 + r0 + g;
            sp[0] = make_float2(s1[0], (g & 1) ? s2[0][1] + s2[2][1] : s2[0][0] + s2[2][0]);
            sp[8] = make_float2(s1[2], (g & 1) ? s2[1][3] + s2[3][3] : s2[1][2] + s2[3][2]);
          }
        }
        bulk_wait_n<0>();
        if (l < 3) bar_arrive(NB_X0, 288);
      }
    }
  }
  asm volatile("barrier.cluster.arrive.relaxed.aligned;\nbarrier.cluster.wait.aligned;" ::: "memory");
}

typedef CUresult (*EncodeFn)(CUtensorMap*, CUtensorMapDataType, cuuint32_t, void*, const cuuint64_t*, const cuuint64_t*, const cuuint32_t*,
                             const cuuint32_t*, CUtensorMapInterleave, CUtensorMapSwizzle, CUtensorMapL2promotion, CUtensorMapFloatOOBfill);

static void make_map(EncodeFn fn, CUtensorMap* m, const void* ptr, int rank, const uint64_t* dims, const uint64_t* strides, const uint32_t* box, CUtensorMapSwizzle sw) {
  cuuint64_t d[5], st[4];
  cuuint32_t bx[5], es[5];
  for (int i = 0; i < rank; i++) { d[i] = dims[i]; bx[i] = box[i]; es[i] = 1; if (i) st[i - 1] = strides[i - 1] * 2; }
  fn(m, CU_TENSOR_MAP_DATA_TYPE_BFLOAT16, rank, (void*)ptr, d, st, bx, es, CU_TENSOR_MAP_INTERLEAVE_NONE, sw,
     CU_TENSOR_MAP_L2_PROMOTION_L2_128B, CU_TENSOR_MAP_FLOAT_OOB_FILL_NONE);
}
static void map2(EncodeFn fn, CUtensorMap* m, const void* ptr, uint64_t inner, uint64_t outer, uint32_t bi, uint32_t bo, CUtensorMapSwizzle sw) {
  const uint64_t d[2] = {inner, outer}, st[1] = {inner};
  const uint32_t bx[2] = {bi, bo};
  make_map(fn, m, ptr, 2, d, st, bx, sw);
}

extern "C" void kernel_launch(void* const* d_in, const int* in_sizes, int n_in, void* d_out, int out_size) {
  (void)in_sizes; (void)n_in; (void)out_size;
  static EncodeFn enc = nullptr;
  static void *xs, *os, *kk, *vv, *ep;
  if (!enc) {
    void* p = nullptr;
    cudaDriverEntryPointQueryResult qr;
    cudaGetDriverEntryPoint("cuTensorMapEncodeTiled", &p, cudaEnableDefault, &qr);
    enc = (EncodeFn)p;
    cudaGetSymbolAddress(&xs, g_xs); cudaGetSymbolAddress(&os, g_os); cudaGetSymbolAddress(&kk, g_k); cudaGetSymbolAddress(&vv, g_v); cudaGetSymbolAddress(&ep, g_epoch);
    cudaFuncSetAttribute(fused_kernel, cudaFuncAttributeMaxDynamicSharedMemorySize, SMEM_BYTES);
  }
  Params prm;
  const CUtensorMapSwizzle S128 = CU_TENSOR_MAP_SWIZZLE_128B, S64 = CU_TENSOR_MAP_SWIZZLE_64B;
  map2(enc, &prm.m[M_X0A], d_in[0], 1024, 2048, 64, 256, S128);
  map2(enc, &prm.m[M_XSA], xs, 1024, 2048, 64, 256, S128);
  for (int t = 0; t < 2; t++) {
    const uint64_t d3[3] = {1024, 1024, 3}, s3[2] = {3072, 1024};
    const uint32_t b3[3] = {64, 64, 3};
    make_map(enc, &prm.m[M_WQA + t], d_in[1 + 3 * t], 3, d3, s3, b3, S128);
    const uint64_t d5[5] = {64, 32, 2, 16, 16}, s5[4] = {1024, 32 * 1024, 64 * 1024, 64};
    const uint32_t b5[5] = {64, 32, 1, 2, 2};
    make_map(enc, &prm.m[M_WOA + t], d_in[2 + 3 * t], 5, d5, s5, b5, S128);
    const uint64_t dr[3] = {64, 2048, 16}, sr[2] = {1024, 64};
    const uint32_t br[3] = {64, 128, 2};
    make_map(enc, &prm.m[M_X0R + t], t ? xs : d_in[0], 3, dr, sr, br, S128);
  }
  map2(enc, &prm.m[M_OS], os, 1024, 2048, 64, 64, S128);
  map2(enc, &prm.m[M_K], kk, 32, 65536, 32, 256, S64);
  map2(enc, &prm.m[M_V], vv, 32, 65536, 32, 256, S64);
  map2(enc, &prm.m[M_K4], kk, 32, 65536, 32, 64, S64);
  map2(enc, &prm.m[M_V4], vv, 32, 65536, 32, 64, S64);
  map2(enc, &prm.m[M_XSO], xs, 1024, 2048, 64, 128, S128);
  map2(enc, &prm.m[M_X0H], d_in[0], 1024, 2048, 64, 128, S128);
  map2(enc, &prm.m[M_XST], xs, 1024, 2048, 64, 16, S128);
  map2(enc, &prm.m[M_OUT], d_out, 1024, 2048, 64, 16, S128);
  prm.x0 = (const bf16*)d_in[0];
  prm.wq[0] = (const bf16*)d_in[1]; prm.wq[1] = (const bf16*)d_in[4];
  prm.epoch = (uint32_t*)ep;
  prm.zero = 0;
  for (int i = 0; i < 128; i++) prm.map[i] = remap(i);
  fused_kernel<<<128, 384, SMEM_BYTES>>>(prm);
}
```

```cpp
#include <cuda_runtime.h>
#include <cuda_bf16.h>
#include <cuda.h>
#include <stdint.h>

typedef __nv_bfloat16 bf16;

__device__ __forceinline__ void wgmma_m64n192k16_ss_tb(float (&d)[96], uint64_t da, uint64_t db, int scale_d) {
  asm volatile("{\n.reg .pred p;\nsetp.ne.b32 p, %98, 0;\n"
    "wgmma.mma_async.sync.aligned.m64n192k16.f32.bf16.bf16 "
    "{%0, %1, %2, %3, %4, %5, %6, %7, %8, %9, %10, %11, %12, %13, %14, %15, "
    "%16, %17, %18, %19, %20, %21, %22, %23, %24, %25, %26, %27, %28, %29, %30, %31, "
    "%32, %33, %34, %35, %36, %37, %38, %39, %40, %41, %42, %43, %44, %45, %46, %47, "
    "%48, %49, %50, %51, %52, %53, %54, %55, %56, %57, %58, %59, %60, %61, %62, %63, "
    "%64, %65, %66, %67, %68, %69, %70, %71, %72, %73, %74, %75, %76, %77, %78, %79, "
    "%80, %81, %82, %83, %84, %85, %86, %87, %88, %89, %90, %91, %92, %93, %94, %95}, "
    "%96, %97, p, 1, 1, 0, 1;\n}\n"
    : "+f"(d[0]), "+f"(d[1]), "+f"(d[2]), "+f"(d[3]), "+f"(d[4]), "+f"(d[5]), "+f"(d[6]), "+f"(d[7]),
      "+f"(d[8]), "+f"(d[9]), "+f"(d[10]), "+f"(d[11]), "+f"(d[12]), "+f"(d[13]), "+f"(d[14]), "+f"(d[15]),
      "+f"(d[16]), "+f"(d[17]), "+f"(d[18]), "+f"(d[19]), "+f"(d[20]), "+f"(d[21]), "+f"(d[22]), "+f"(d[23]),
      "+f"(d[24]), "+f"(d[25]), "+f"(d[26]), "+f"(d[27]), "+f"(d[28]), "+f"(d[29]), "+f"(d[30]), "+f"(d[31]),
      "+f"(d[32]), "+f"(d[33]), "+f"(d[34]), "+f"(d[35]), "+f"(d[36]), "+f"(d[37]), "+f"(d[38]), "+f"(d[39]),
      "+f"(d[40]), "+f"(d[41]), "+f"(d[42]), "+f"(d[43]), "+f"(d[44]), "+f"(d[45]), "+f"(d[46]), "+f"(d[47]),
      "+f"(d[48]), "+f"(d[49]), "+f"(d[50]), "+f"(d[51]), "+f"(d[52]), "+f"(d[53]), "+f"(d[54]), "+f"(d[55]),
      "+f"(d[56]), "+f"(d[57]), "+f"(d[58]), "+f"(d[59]), "+f"(d[60]), "+f"(d[61]), "+f"(d[62]), "+f"(d[63]),
      "+f"(d[64]), "+f"(d[65]), "+f"(d[66]), "+f"(d[67]), "+f"(d[68]), "+f"(d[69]), "+f"(d[70]), "+f"(d[71]),
      "+f"(d[72]), "+f"(d[73]), "+f"(d[74]), "+f"(d[75]), "+f"(d[76]), "+f"(d[77]), "+f"(d[78]), "+f"(d[79]),
      "+f"(d[80]), "+f"(d[81]), "+f"(d[82]), "+f"(d[83]), "+f"(d[84]), "+f"(d[85]), "+f"(d[86]), "+f"(d[87]),
      "+f"(d[88]), "+f"(d[89]), "+f"(d[90]), "+f"(d[91]), "+f"(d[92]), "+f"(d[93]), "+f"(d[94]), "+f"(d[95])
    : "l"(da), "l"(db), "r"(scale_d));
}

__device__ __forceinline__ void wgmma_m64n128k16_ss_tb(float (&d)[64], uint64_t da, uint64_t db, int scale_d) {
  asm volatile("{\n.reg .pred p;\nsetp.ne.b32 p, %66, 0;\n"
    "wgmma.mma_async.sync.aligned.m64n128k16.f32.bf16.bf16 "
    "{%0, %1, %2, %3, %4, %5, %6, %7, %8, %9, %10, %11, %12, %13, %14, %15, "
    "%16, %17, %18, %19, %20, %21, %22, %23, %24, %25, %26, %27, %28, %29, %30, %31, "
    "%32, %33, %34, %35, %36, %37, %38, %39, %40, %41, %42, %43, %44, %45, %46, %47, "
    "%48, %49, %50, %51, %52, %53, %54, %55, %56, %57, %58, %59, %60, %61, %62, %63}, "
    "%64, %65, p, 1, 1, 0, 1;\n}\n"
    : "+f"(d[0]), "+f"(d[1]), "+f"(d[2]), "+f"(d[3]), "+f"(d[4]), "+f"(d[5]), "+f"(d[6]), "+f"(d[7]),
      "+f"(d[8]), "+f"(d[9]), "+f"(d[10]), "+f"(d[11]), "+f"(d[12]), "+f"(d[13]), "+f"(d[14]), "+f"(d[15]),
      "+f"(d[16]), "+f"(d[17]), "+f"(d[18]), "+f"(d[19]), "+f"(d[20]), "+f"(d[21]), "+f"(d[22]), "+f"(d[23]),
      "+f"(d[24]), "+f"(d[25]), "+f"(d[26]), "+f"(d[27]), "+f"(d[28]), "+f"(d[29]), "+f"(d[30]), "+f"(d[31]),
      "+f"(d[32]), "+f"(d[33]), "+f"(d[34]), "+f"(d[35]), "+f"(d[36]), "+f"(d[37]), "+f"(d[38]), "+f"(d[39]),
      "+f"(d[40]), "+f"(d[41]), "+f"(d[42]), "+f"(d[43]), "+f"(d[44]), "+f"(d[45]), "+f"(d[46]), "+f"(d[47]),
      "+f"(d[48]), "+f"(d[49]), "+f"(d[50]), "+f"(d[51]), "+f"(d[52]), "+f"(d[53]), "+f"(d[54]), "+f"(d[55]),
      "+f"(d[56]), "+f"(d[57]), "+f"(d[58]), "+f"(d[59]), "+f"(d[60]), "+f"(d[61]), "+f"(d[62]), "+f"(d[63])
    : "l"(da), "l"(db), "r"(scale_d));
}

__device__ __forceinline__ void wgmma_m64n32k16_rs_nb_h(float (&d)[16], uint32_t a0, uint32_t a1, uint32_t a2, uint32_t a3, uint64_t db, int scale_d) {
  asm volatile("{\n.reg .pred p;\nsetp.ne.b32 p, %21, 0;\n"
    "wgmma.mma_async.sync.aligned.m64n32k16.f32.f16.f16 "
    "{%0, %1, %2, %3, %4, %5, %6, %7, %8, %9, %10, %11, %12, %13, %14, %15}, "
    "{%16, %17, %18, %19}, %20, p, 1, 1, 0;\n}\n"
    : "+f"(d[0]), "+f"(d[1]), "+f"(d[2]), "+f"(d[3]), "+f"(d[4]), "+f"(d[5]), "+f"(d[6]), "+f"(d[7]),
      "+f"(d[8]), "+f"(d[9]), "+f"(d[10]), "+f"(d[11]), "+f"(d[12]), "+f"(d[13]), "+f"(d[14]), "+f"(d[15])
    : "r"(a0), "r"(a1), "r"(a2), "r"(a3), "l"(db), "r"(scale_d));
}

__device__ __forceinline__ void wgmma_m64n32k16_rs_nb_hh(uint32_t (&d)[8], uint32_t a0, uint32_t a1, uint32_t a2, uint32_t a3, uint64_t db, int scale_d) {
  asm volatile("{\n.reg .pred p;\nsetp.ne.b32 p, %13, 0;\n"
    "wgmma.mma_async.sync.aligned.m64n32k16.f16.f16.f16 "
    "{%0, %1, %2, %3, %4, %5, %6, %7}, "
    "{%8, %9, %10, %11}, %12, p, 1, 1, 0;\n}\n"
    : "+r"(d[0]), "+r"(d[1]), "+r"(d[2]), "+r"(d[3]), "+r"(d[4]), "+r"(d[5]), "+r"(d[6]), "+r"(d[7])
    : "r"(a0), "r"(a1), "r"(a2), "r"(a3), "l"(db), "r"(scale_d));
}

__device__ __forceinline__ void wgmma_m64n64k16_rs_nb_h(float (&d)[32], uint32_t a0, uint32_t a1, uint32_t a2, uint32_t a3, uint64_t db, int scale_d) {
  asm volatile("{\n.reg .pred p;\nsetp.ne.b32 p, %37, 0;\n"
    "wgmma.mma_async.sync.aligned.m64n64k16.f32.f16.f16 "
    "{%0, %1, %2, %3, %4, %5, %6, %7, %8, %9, %10, %11, %12, %13, %14, %15, "
    "%16, %17, %18, %19, %20, %21, %22, %23, %24, %25, %26, %27, %28, %29, %30, %31}, "
    "{%32, %33, %34, %35}, %36, p, 1, 1, 0;\n}\n"
    : "+f"(d[0]), "+f"(d[1]), "+f"(d[2]), "+f"(d[3]), "+f"(d[4]), "+f"(d[5]), "+f"(d[6]), "+f"(d[7]),
      "+f"(d[8]), "+f"(d[9]), "+f"(d[10]), "+f"(d[11]), "+f"(d[12]), "+f"(d[13]), "+f"(d[14]), "+f"(d[15]),
      "+f"(d[16]), "+f"(d[17]), "+f"(d[18]), "+f"(d[19]), "+f"(d[20]), "+f"(d[21]), "+f"(d[22]), "+f"(d[23]),
      "+f"(d[24]), "+f"(d[25]), "+f"(d[26]), "+f"(d[27]), "+f"(d[28]), "+f"(d[29]), "+f"(d[30]), "+f"(d[31])
    : "r"(a0), "r"(a1), "r"(a2), "r"(a3), "l"(db), "r"(scale_d));
}

__device__ __forceinline__ void wgmma_m64n64k16_rs_nb_hh(uint32_t (&d)[16], uint32_t a0, uint32_t a1, uint32_t a2, uint32_t a3, uint64_t db, int scale_d) {
  asm volatile("{\n.reg .pred p;\nsetp.ne.b32 p, %21, 0;\n"
    "wgmma.mma_async.sync.aligned.m64n64k16.f16.f16.f16 "
    "{%0, %1, %2, %3, %4, %5, %6, %7, %8, %9, %10, %11, %12, %13, %14, %15}, "
    "{%16, %17, %18, %19}, %20, p, 1, 1, 0;\n}\n"
    : "+r"(d[0]), "+r"(d[1]), "+r"(d[2]), "+r"(d[3]), "+r"(d[4]), "+r"(d[5]), "+r"(d[6]), "+r"(d[7]),
      "+r"(d[8]), "+r"(d[9]), "+r"(d[10]), "+r"(d[11]), "+r"(d[12]), "+r"(d[13]), "+r"(d[14]), "+r"(d[15])
    : "r"(a0), "r"(a1), "r"(a2), "r"(a3), "l"(db), "r"(scale_d));
}

__device__ __forceinline__ void wgmma_m64n40k16_rs_tb(float (&d)[20], uint32_t a0, uint32_t a1, uint32_t a2, uint32_t a3, uint64_t db, int scale_d) {
  asm volatile("{\n.reg .pred p;\nsetp.ne.b32 p, %25, 0;\n"
    "wgmma.mma_async.sync.aligned.m64n40k16.f32.bf16.bf16 "
    "{%0, %1, %2, %3, %4, %5, %6, %7, %8, %9, %10, %11, %12, %13, %14, %15, "
    "%16, %17, %18, %19}, "
    "{%20, %21, %22, %23}, %24, p, 1, 1, 1;\n}\n"
    : "+f"(d[0]), "+f"(d[1]), "+f"(d[2]), "+f"(d[3]), "+f"(d[4]), "+f"(d[5]), "+f"(d[6]), "+f"(d[7]),
      "+f"(d[8]), "+f"(d[9]), "+f"(d[10]), "+f"(d[11]), "+f"(d[12]), "+f"(d[13]), "+f"(d[14]), "+f"(d[15]),
      "+f"(d[16]), "+f"(d[17]), "+f"(d[18]), "+f"(d[19])
    : "r"(a0), "r"(a1), "r"(a2), "r"(a3), "l"(db), "r"(scale_d));
}

#define DEVINL __device__ __forceinline__
DEVINL void pin(uint32_t z) { asm volatile("{\n.reg .pred p;\nsetp.ne.u32 p, %0, 0;\nPIN:\n@p bra.uni PIN;\n}" ::"r"(z) : "memory"); }
DEVINL void wg_fence() { asm volatile("wgmma.fence.sync.aligned;" ::: "memory"); }
DEVINL void wg_commit() { asm volatile("wgmma.commit_group.sync.aligned;" ::: "memory"); }
template <int N> DEVINL void wg_wait() { asm volatile("wgmma.wait_group.sync.aligned %0;" ::"n"(N) : "memory"); }
DEVINL uint64_t mkdesc(uint32_t addr, uint32_t lbo, uint32_t sbo, int sw) {
  return (uint64_t)((addr & 0x3FFFF) >> 4) | ((uint64_t)(lbo >> 4) << 16) | ((uint64_t)(sbo >> 4) << 32) | ((uint64_t)sw << 62);
}
DEVINL void mbar_arrive(uint32_t bar) { asm volatile("mbarrier.arrive.shared::cta.b64 _, [%0];" ::"r"(bar) : "memory"); }
DEVINL bool mbar_try(uint32_t bar, uint32_t parity) {
  uint32_t ok;
  asm volatile("{\n.reg .pred p;\nmbarrier.try_wait.parity.shared::cta.b64 p, [%1], %2;\nselp.u32 %0, 1, 0, p;\n}" : "=r"(ok) : "r"(bar), "r"(parity) : "memory");
  return ok;
}
DEVINL bool mbar_test(uint32_t bar, uint32_t parity) {
  uint32_t ok;
  asm volatile("{\n.reg .pred p;\nmbarrier.test_wait.parity.shared::cta.b64 p, [%1], %2;\nselp.u32 %0, 1, 0, p;\n}" : "=r"(ok) : "r"(bar), "r"(parity) : "memory");
  return ok;
}
DEVINL void mbar_hint(uint32_t bar, uint32_t parity) {
#pragma unroll 1
  for (uint32_t n = 0; n < 16u; n++) if (mbar_try(bar, parity)) break;
}
DEVINL void mbar_wait(uint32_t bar, uint32_t parity) {
#pragma unroll 1
  for (uint32_t n = 0; n < 100000u; n++) if (mbar_try(bar, parity)) break;
}
#define EL(txt) "{\n.reg .pred pe;\nelect.sync _|pe, 0xffffffff;\n@pe " txt "\n}"
DEVINL void e_expect_tx(uint32_t bar, uint32_t bytes) { asm volatile(EL("mbarrier.arrive.expect_tx.shared::cta.b64 _, [%0], %1;") ::"r"(bar), "r"(bytes) : "memory"); }
DEVINL void e_init(uint32_t bar, uint32_t cnt) { asm volatile(EL("mbarrier.init.shared::cta.b64 [%0], %1;") ::"r"(bar), "r"(cnt) : "memory"); }
DEVINL void e_arrive(uint32_t bar) { asm volatile(EL("mbarrier.arrive.shared::cta.b64 _, [%0];") ::"r"(bar) : "memory"); }
DEVINL void e_red(uint32_t* p) { asm volatile(EL("red.release.gpu.global.add.u32 [%0], 1;") ::"l"(p) : "memory"); }
DEVINL void e_red_relaxed(uint32_t* p) { asm volatile(EL("red.relaxed.gpu.global.add.u32 [%0], 1;") ::"l"(p) : "memory"); }
DEVINL void tma_ld(uint32_t dst, const CUtensorMap* m, int c0, int c1, uint32_t bar) {
  asm volatile(EL("cp.async.bulk.tensor.2d.shared::cluster.global.mbarrier::complete_tx::bytes [%0], [%1, {%3, %4}], [%2];")
               ::"r"(dst), "l"(m), "r"(bar), "r"(c0), "r"(c1) : "memory");
}
DEVINL void tma_ld3(uint32_t dst, const CUtensorMap* m, int c0, int c1, int c2, uint32_t bar) {
  asm volatile(EL("cp.async.bulk.tensor.3d.shared::cluster.global.mbarrier::complete_tx::bytes [%0], [%1, {%3, %4, %5}], [%2];")
               ::"r"(dst), "l"(m), "r"(bar), "r"(c0), "r"(c1), "r"(c2) : "memory");
}
DEVINL void tma_ld5(uint32_t dst, const CUtensorMap* m, int c2, int c3, int c4, uint32_t bar) {
  asm volatile(EL("cp.async.bulk.tensor.5d.shared::cluster.global.mbarrier::complete_tx::bytes [%0], [%1, {0, 0, %3, %4, %5}], [%2];")
               ::"r"(dst), "l"(m), "r"(bar), "r"(c2), "r"(c3), "r"(c4) : "memory");
}
DEVINL void tma_ld_mc(uint32_t dst, const CUtensorMap* m, int c0, int c1, uint32_t bar) {
  asm volatile(EL("cp.async.bulk.tensor.2d.shared::cluster.global.mbarrier::complete_tx::bytes.multicast::cluster [%0], [%1, {%3, %4}], [%2], %5;")
               ::"r"(dst), "l"(m), "r"(bar), "r"(c0), "r"(c1), "h"((uint16_t)3) : "memory");
}
DEVINL void e_arrive_both(uint32_t bar) {
  asm volatile("{\n.reg .pred pe;\n.reg .b32 r0, r1;\nelect.sync _|pe, 0xffffffff;\nmapa.shared::cluster.u32 r0, %0, 0;\nmapa.shared::cluster.u32 r1, %0, 1;\n"
               "@pe mbarrier.arrive.shared::cluster.b64 _, [r0];\n@pe mbarrier.arrive.shared::cluster.b64 _, [r1];\n}" ::"r"(bar) : "memory");
}
DEVINL void push_peer(uint32_t dst, uint32_t src, uint32_t bar, uint32_t peer) {
  asm volatile("{\n.reg .pred pe;\n.reg .b32 d, b;\nelect.sync _|pe, 0xffffffff;\nmapa.shared::cluster.u32 d, %0, %3;\nmapa.shared::cluster.u32 b, %2, %3;\n"
               "@pe cp.async.bulk.shared::cluster.shared::cta.mbarrier::complete_tx::bytes [d], [%1], 16384, [b];\n}" ::"r"(dst), "r"(src), "r"(bar), "r"(peer) : "memory");
}
DEVINL void tma_st(const CUtensorMap* m, int c0, int c1, uint32_t src) {
  asm volatile(EL("cp.async.bulk.tensor.2d.global.shared::cta.bulk_group [%0, {%2, %3}], [%1];") ::"l"(m), "r"(src), "r"(c0), "r"(c1) : "memory");
}
DEVINL void bulk_commit() { asm volatile("cp.async.bulk.commit_group;" ::: "memory"); }
template <int N> DEVINL void bulk_wait_n() { asm volatile("cp.async.bulk.wait_group %0;\nbar.warp.sync 0xffffffff;" ::"n"(N) : "memory"); }
DEVINL void l2_prefetch(const void* g, uint32_t bytes) { asm volatile(EL("cp.async.bulk.prefetch.L2.global [%0], %1;") ::"l"(g), "r"(bytes) : "memory"); }
DEVINL void fence_async_smem() { asm volatile("fence.proxy.async.shared::cta;" ::: "memory"); }
DEVINL void fence_async_gl() { asm volatile("fence.proxy.async.global;" ::: "memory"); }
DEVINL void cluster_wait() { asm volatile("barrier.cluster.wait.aligned;" ::: "memory"); }
DEVINL void bar_sync(int id, int n) { asm volatile("bar.sync %0, %1;" ::"r"(id), "r"(n) : "memory"); }
DEVINL void bar_arrive(int id, int n) { asm volatile("bar.arrive %0, %1;" ::"r"(id), "r"(n) : "memory"); }
DEVINL uint32_t ld_acquire(const uint32_t* p) { uint32_t v; asm volatile("ld.acquire.gpu.global.u32 %0, [%1];" : "=r"(v) : "l"(p) : "memory"); return v; }
DEVINL void watch(const uint32_t* p, uint32_t target, uint32_t all, uint32_t tag, uint32_t slot) {
  uint32_t seen = 0;
#pragma unroll 1
  for (uint32_t n = 0; n < 200000u && seen != all; n++) {
    const uint32_t m = __ballot_sync(~0u, (int)(ld_acquire(p) - target) >= 0) & all;
    if (m != seen) { seen = m; asm volatile("st.release.cta.shared.u32 [%0], %1;" ::"r"(slot), "r"(tag << 16 | m) : "memory"); }
  }
}
template <bool RELAXED = false> DEVINL void await_bit(uint32_t slot, uint32_t tag, int j, uint32_t& rdy) {
  if ((rdy >> j) & 1) return;
#pragma unroll 1
  for (uint32_t n = 0; n < 8000000u; n++) {
    uint32_t v;
    asm volatile("ld.acquire.cta.shared.u32 %0, [%1];" : "=r"(v) : "r"(slot) : "memory");
    if ((v >> 16) == tag && ((v >> j) & 1)) { rdy = v; break; }
    if (RELAXED) __nanosleep(200);
  }
  asm volatile("fence.proxy.async.global;" ::: "memory");
}
DEVINL void poll_ge(const uint32_t* p, uint32_t target) {
#pragma unroll 1
  for (uint32_t n = 0; n < 200000u; n++) if (__all_sync(~0u, (int)(ld_acquire(p) - target) >= 0)) break;
}
DEVINL int lane_id() { int v; asm volatile("mov.u32 %0, %%laneid;" : "=r"(v)); return v; }
__host__ DEVINL int remap(int v) {
  const int c = v >> 1, u = c - 36, r = (u * 37) >> 8;
  const int L = max(c - 4 + max(r + 1, 0), (c - 4) >> 31 & (32 + 8 * c));
  return 2 * L + (v & 1);
}
DEVINL int block_id() { int v; asm volatile("mov.u32 %0, %%ctaid.x;" : "=r"(v)); return v; }
#define cta_id() prm.map[block_id()]
#define IDS() const int lane = lane_id(), b = cta_id(), bm = b >> 4, bn = b & 15, rank = b & 1, pm = 2 * bm + (bn >> 3), pn = bn & 7, po = pm & 1; \
  (void)lane; (void)bm; (void)bn; (void)rank; (void)pm; (void)pn; (void)po
DEVINL void st_tagged(unsigned long long* p, uint32_t v, uint32_t tag) {
  asm volatile("{\n.reg .b64 t;\nmov.b64 t, {%1, %2};\nst.relaxed.gpu.global.b64 [%0], t;\n}" ::"l"(p), "r"(v), "r"(tag) : "memory");
}
DEVINL float ex2(float x) { float y; asm("ex2.approx.ftz.f32 %0, %1;" : "=f"(y) : "f"(x)); return y; }
DEVINL float rcp(float x) { float y; asm("rcp.approx.ftz.f32 %0, %1;" : "=f"(y) : "f"(x)); return y; }
DEVINL uint32_t pack2(float lo, float hi) { uint32_t r; asm("cvt.rn.bf16x2.f32 %0, %1, %2;" : "=r"(r) : "f"(hi), "f"(lo)); return r; }
DEVINL float bf_lo(uint32_t w) { return __uint_as_float(w << 16); }
DEVINL float bf_hi(uint32_t w) { return __uint_as_float(w & 0xFFFF0000u); }
DEVINL float bf_round(float x) { return bf_lo(pack2(x, 0.f)); }
DEVINL uint32_t add_bf16x2(uint32_t a, uint32_t b) { uint32_t r; asm("add.rn.bf16x2 %0, %1, %2;" : "=r"(r) : "r"(a), "r"(b)); return r; }
DEVINL void stsm4(uint32_t addr, uint32_t a, uint32_t b, uint32_t c, uint32_t d) {
  asm volatile("stmatrix.sync.aligned.m8n8.x4.shared.b16 [%0], {%1, %2, %3, %4};" ::"r"(addr), "r"(a), "r"(b), "r"(c), "r"(d) : "memory");
}
DEVINL void ldsm4(uint32_t addr, uint32_t (&r)[4]) {
  asm volatile("ldmatrix.sync.aligned.m8n8.x4.shared.b16 {%0, %1, %2, %3}, [%4];" : "=r"(r[0]), "=r"(r[1]), "=r"(r[2]), "=r"(r[3]) : "r"(addr) : "memory");
}
DEVINL void ldsm4t(uint32_t addr, uint32_t (&r)[4]) {
  asm volatile("ldmatrix.sync.aligned.m8n8.x4.trans.shared.b16 {%0, %1, %2, %3}, [%4];" : "=r"(r[0]), "=r"(r[1]), "=r"(r[2]), "=r"(r[3]) : "r"(addr) : "memory");
}
DEVINL void sts128(uint32_t addr, uint32_t a, uint32_t b, uint32_t c, uint32_t d) {
  asm volatile("st.shared.v4.b32 [%0], {%1, %2, %3, %4};" ::"r"(addr), "r"(a), "r"(b), "r"(c), "r"(d) : "memory");
}
DEVINL float4 lds128f(uint32_t addr) { float4 v; asm volatile("ld.shared.v4.f32 {%0, %1, %2, %3}, [%4];" : "=f"(v.x), "=f"(v.y), "=f"(v.z), "=f"(v.w) : "r"(addr) : "memory"); return v; }
DEVINL float lds32f(uint32_t addr) { float v; asm volatile("ld.shared.f32 %0, [%1];" : "=f"(v) : "r"(addr) : "memory"); return v; }
DEVINL float2 lds64f(uint32_t addr) { float2 v; asm volatile("ld.shared.v2.f32 {%0, %1}, [%2];" : "=f"(v.x), "=f"(v.y) : "r"(addr) : "memory"); return v; }
DEVINL void mma16816(float (&d)[4], uint32_t a0, uint32_t a1, uint32_t a2, uint32_t a3, uint32_t b0, uint32_t b1) {
  asm("mma.sync.aligned.m16n8k16.row.col.f32.bf16.bf16.f32 {%0, %1, %2, %3}, {%4, %5, %6, %7}, {%8, %9}, {%0, %1, %2, %3};"
               : "+f"(d[0]), "+f"(d[1]), "+f"(d[2]), "+f"(d[3]) : "r"(a0), "r"(a1), "r"(a2), "r"(a3), "r"(b0), "r"(b1));
}
DEVINL void mma1688(float (&d)[4], uint32_t a0, uint32_t a1, uint32_t b0) {
  asm("mma.sync.aligned.m16n8k8.row.col.f32.bf16.bf16.f32 {%0, %1, %2, %3}, {%4, %5}, {%6}, {%0, %1, %2, %3};"
               : "+f"(d[0]), "+f"(d[1]), "+f"(d[2]), "+f"(d[3]) : "r"(a0), "r"(a1), "r"(b0));
}
DEVINL void mma16816h(float (&d)[4], uint32_t a0, uint32_t a1, uint32_t a2, uint32_t a3, uint32_t b0, uint32_t b1) {
  asm("mma.sync.aligned.m16n8k16.row.col.f32.f16.f16.f32 {%0, %1, %2, %3}, {%4, %5, %6, %7}, {%8, %9}, {%0, %1, %2, %3};"
               : "+f"(d[0]), "+f"(d[1]), "+f"(d[2]), "+f"(d[3]) : "r"(a0), "r"(a1), "r"(a2), "r"(a3), "r"(b0), "r"(b1));
}
template <int N> DEVINL void fence_regs(uint32_t (&d)[N]) {
#pragma unroll
  for (int i = 0; i < N; i++) asm volatile("" : "+r"(d[i])::"memory");
}
template <int N> DEVINL void fence_regs(float (&d)[N]) {
#pragma unroll
  for (int i = 0; i < N; i++) asm volatile("" : "+f"(d[i])::"memory");
}

__device__ __align__(1024) bf16 g_xs[2048 * 1024];
__device__ __align__(1024) bf16 g_os[2048 * 1024];
__device__ __align__(1024) bf16 g_k[32 * 2048 * 32];
__device__ __align__(1024) bf16 g_v[32 * 2048 * 32];
__device__ __align__(128) float2 g_stats[8 * 2048];
__device__ __align__(16) float g_csp[2 * 16 * 8 * 192];
__device__ __align__(128) float g_kn[2 * 128 * 32];
__device__ unsigned long long g_halo[2 * 128 * 32 * 32];
__device__ __align__(128) uint32_t g_cnt[256 * 32];
__device__ uint32_t g_epoch;

DEVINL uint32_t* cnt_x(int l, int bm) { return g_cnt + (l * 8 + bm) * 32; }
DEVINL uint32_t* cnt_o(int l, int pm, int h) { return g_cnt + (32 + (l * 16 + pm) * 2 + h) * 32; }
DEVINL uint32_t* cnt_kv(int lb, int bn) { return g_cnt + (160 + lb * 16 + bn) * 32; }
DEVINL uint32_t* cnt_ad(int bn) { return g_cnt + (192 + bn) * 32; }
DEVINL uint32_t* cnt_cs(int t, int bn) { return g_cnt + (208 + t * 16 + bn) * 32; }

DEVINL int qord(int i, int l, int pn) { return l == 0 ? i : i < 4 ? ((2 * pn) ^ (i & 2)) + (i & 1) : i - 4 < 2 * (pn & 6) ? i - 4 : i; }
struct Params {
  CUtensorMap m[17];
  const bf16* x0;
  const bf16* wq[2];
  uint32_t* epoch;
  uint32_t zero;
  int map[128];
};
enum { M_X0A = 0, M_XSA, M_WQA, M_WQB, M_WOA, M_WOB, M_OS, M_K, M_V, M_X0R, M_XSR, M_XSO, M_OUT, M_XST, M_X0H, M_K4, M_V4, M_COUNT };

constexpr uint32_t QSTG = 57344;
constexpr uint32_t T0 = 65536, TSTG = 32768;
constexpr uint32_t ONES = 229376;
constexpr uint32_t PSTG = 32768, RES = 196608;
constexpr uint32_t ASC = 17408;
constexpr uint32_t RSTD = 229376, MEAN = 230400, COLS = 230912, KMAX = 231680, B_QD = 231688, BARS = 232192, SMEM_BYTES = 232448;
constexpr uint32_t B_QF = BARS, B_QE = BARS + 32, B_TF = BARS + 64, B_TE = BARS + 96, B_PF = BARS + 128, B_PE = BARS + 176,
                   B_RF = BARS + 224, W_X = BARS + 232, W_O = BARS + 236, B_QL = BARS + 240, B_PA = BARS + 248;
enum { NB_ST = 1, NB_KV = 2  , NB_DONE = 3, NB_SC = 4, NB_SIG = 5  , NB_KN = 9  , NB_X = 11, NB_HALO = 12  , NB_X0 = 15 };

DEVINL uint32_t pslot_b(uint32_t s, int l) { return ((((l & 1) ? 0x320415u : 0x468795u) >> (4 * s)) & 15) * 16384u; }
DEVINL uint32_t pslot_a(uint32_t s, int l) { return ((((l & 1) ? 0xBA7896u : 0x32DCBAu) >> (4 * s)) & 15) * 16384u; }

#define G1 2
#define G2 0
#define G3 2
#define KC (11 + 2 * wg)
#define NA2 2
#define RESI 9
#define PERHEAD 1
#define PUBMODE 1
#define LA 1
#define LB 1
#define PFETCH 0
#define NQ 32
#define OA 0x10
#define OB 0x10
#define LAG 2
#define QK_A wgmma_m64n32k16_rs_nb_h
#define QK_B wgmma_m64n32k16_rs_nb_hh
constexpr float QSCALE = 0.17677669529663687f * 1.4426950408889634f;

DEVINL uint32_t hfma2(uint32_t a, uint32_t b, uint32_t c) { uint32_t r; asm("fma.rn.f16x2 %0, %1, %2, %3;" : "=r"(r) : "r"(a), "r"(b), "r"(c)); return r; }
DEVINL uint32_t pack2h(float lo, float hi) { uint32_t r; asm("cvt.rn.f16x2.f32 %0, %1, %2;" : "=r"(r) : "f"(hi), "f"(lo)); return r; }
DEVINL uint32_t h2_to_bf2(uint32_t h) {
  float a, b;
  asm("{\n.reg .b16 l, h;\nmov.b32 {l, h}, %2;\ncvt.f32.f16 %0, l;\ncvt.f32.f16 %1, h;\n}" : "=f"(a), "=f"(b) : "r"(h));
  return pack2(a, b);
}
DEVINL uint32_t exp2_h2(uint32_t s) {
  const uint32_t r = hfma2(s, 0x00800080u, 0x007E007Eu);
  const uint32_t g = hfma2(hfma2(r, 0xF800F800u, 0x33FD33FDu), 0x44004400u, s);
  return r * 128u + hfma2(hfma2(g, g, 0x0DE10DE1u), g, 0x00300030u);
}
constexpr uint32_t NOT_F16 = 0x7FC00000u, K_LO = 0x35000000u  ;
DEVINL uint32_t f16_class(uint32_t norm2, uint32_t lo) { return norm2 - lo > 0x4E800000u - lo ? NOT_F16 : norm2; }

DEVINL void attn_slow(const uint32_t (&q)[8], float up, int head, const float* kn, float (&res)[20], int lane) {
  const int g = lane >> 2, qd = lane & 3;
  const bf16* kb = g_k + (size_t)head * 2048 * 32;
  const bf16* vb = g_v + (size_t)head * 2048 * 32;
  float o[4][4], m0 = -INFINITY, m1 = -INFINITY, l0 = 0.f, l1 = 0.f;
#pragma unroll
  for (int j = 0; j < 4; j++) { o[j][0] = o[j][1] = o[j][2] = o[j][3] = 0.f; }
#pragma unroll 1
  for (int k0 = 0; k0 < 2048; k0 += 16) {
    float s[2][4];
    const bool kh = __float_as_uint(__ldcg(kn + (k0 >> 8) * 32 + ((k0 >> 6) & 1) * 8 + ((k0 >> 7) & 1) * 4 + ((k0 >> 4) & 3))) != NOT_F16;
#pragma unroll
    for (int nt = 0; nt < 2; nt++) {
      s[nt][0] = s[nt][1] = s[nt][2] = s[nt][3] = 0.f;
      const uint32_t* kp = (const uint32_t*)(kb + (size_t)(k0 + nt * 8 + g) * 32) + qd;
      uint32_t kf[4];
#pragma unroll
      for (int i = 0; i < 4; i++) { kf[i] = __ldcg(kp + 4 * i); if (kh) kf[i] = h2_to_bf2(kf[i]); }
      mma16816(s[nt], q[0], q[1], q[2], q[3], kf[0], kf[1]);
      mma16816(s[nt], q[4], q[5], q[6], q[7], kf[2], kf[3]);
      s[nt][0] *= up; s[nt][1] *= up; s[nt][2] *= up; s[nt][3] *= up;
    }
    float a0 = fmaxf(fmaxf(s[0][0], s[0][1]), fmaxf(s[1][0], s[1][1]));
    float a1 = fmaxf(fmaxf(s[0][2], s[0][3]), fmaxf(s[1][2], s[1][3]));
    a0 = fmaxf(a0, __shfl_xor_sync(~0u, a0, 1)); a0 = fmaxf(a0, __shfl_xor_sync(~0u, a0, 2));
    a1 = fmaxf(a1, __shfl_xor_sync(~0u, a1, 1)); a1 = fmaxf(a1, __shfl_xor_sync(~0u, a1, 2));
    const float n0 = fmaxf(m0, a0), n1 = fmaxf(m1, a1);
    const float c0 = (m0 == n0) ? 1.f : ex2(m0 - n0), c1 = (m1 == n1) ? 1.f : ex2(m1 - n1);
    m0 = n0; m1 = n1;
    const uint32_t p0 = pack2(ex2(s[0][0] - n0), ex2(s[0][1] - n0)), p1 = pack2(ex2(s[0][2] - n1), ex2(s[0][3] - n1));
    const uint32_t p2 = pack2(ex2(s[1][0] - n0), ex2(s[1][1] - n0)), p3 = pack2(ex2(s[1][2] - n1), ex2(s[1][3] - n1));
    l0 = l0 * c0 + bf_lo(p0) + bf_hi(p0) + bf_lo(p2) + bf_hi(p2);
    l1 = l1 * c1 + bf_lo(p1) + bf_hi(p1) + bf_lo(p3) + bf_hi(p3);
#pragma unroll
    for (int j = 0; j < 4; j++) {
      o[j][0] *= c0; o[j][1] *= c0; o[j][2] *= c1; o[j][3] *= c1;
      const unsigned short* vp = (const unsigned short*)(vb + (size_t)(k0 + 2 * qd) * 32 + j * 8 + g);
      const uint32_t b0 = (uint32_t)__ldcg(vp) | ((uint32_t)__ldcg(vp + 32) << 16);
      const uint32_t b1 = (uint32_t)__ldcg(vp + 256) | ((uint32_t)__ldcg(vp + 288) << 16);
      mma16816(o[j], p0, p1, p2, p3, b0, b1);
    }
  }
  l0 += __shfl_xor_sync(~0u, l0, 1); l0 += __shfl_xor_sync(~0u, l0, 2);
  l1 += __shfl_xor_sync(~0u, l1, 1); l1 += __shfl_xor_sync(~0u, l1, 2);
#pragma unroll
  for (int j = 0; j < 4; j++) { res[4 * j] = o[j][0]; res[4 * j + 1] = o[j][1]; res[4 * j + 2] = o[j][2]; res[4 * j + 3] = o[j][3]; }
  res[16] = l0; res[18] = l1;
}

__global__ void __cluster_dims__(2, 1, 1) __launch_bounds__(384, 1) fused_kernel(const __grid_constant__ Params prm) {
  extern __shared__ __align__(1024) char smem[];
  const uint32_t sb = (uint32_t)__cvta_generic_to_shared(smem);
  const int tid = threadIdx.x;
  const int wid = __shfl_sync(0xffffffffu, tid >> 5, 0), wg = wid >> 2, w = wid & 3;
  const int bm = remap(blockIdx.x) >> 4, bn = remap(blockIdx.x) & 15;
  auto first_tile = [&](int kt) {
    e_expect_tx(sb + B_QF + 8 * kt, QSTG);
    tma_ld(sb + kt * QSTG, &prm.m[M_X0A], kt * 64, bm * 256, sb + B_QF + 8 * kt);
    tma_ld3(sb + kt * QSTG + 32768, &prm.m[M_WQA], bn * 64, kt * 64, 0, sb + B_QF + 8 * kt);
  };
  if (wid == 8) {
    e_init(sb + B_QF, 1);
    asm volatile("fence.mbarrier_init.release.cluster;" ::: "memory");
    first_tile(0);
  }
  if (wid < 8) {
#pragma unroll
    for (int i = 0; i < 4; i++) {
      const uint32_t cnt = (uint32_t)((i == 0 ? 0x14112140 : i == 1 ? 0x04112141 : i == 2 ? 0x14412141 : 0x24412141) >> (4 * wid)) & 7;
      if (cnt) e_init(sb + BARS + 32 * wid + 8 * i, cnt);
    }
    if (wid == 0 || wid == 7) e_init(sb + B_QD + (wid & 1) * 8, 1);
    if (tid == 255) *(uint2*)(smem + W_X) = make_uint2(0u, 0u);
    asm volatile("fence.mbarrier_init.release.cluster;" ::: "memory");
  }
  const uint32_t epoch = *(volatile uint32_t*)prm.epoch;
  __syncthreads();
  asm volatile("barrier.cluster.arrive.relaxed.aligned;" ::: "memory");

  if (wg == 2) {
    asm volatile("setmaxnreg.dec.sync.aligned.u32 56;");
    const uint32_t ep1 = epoch + 1;
    if (w == 0) {
      first_tile(1);
      mbar_wait(sb + B_QF, 0);
      first_tile(2); first_tile(3);
#pragma unroll 1
      for (int kt = 4; kt < 16; kt++) l2_prefetch(prm.wq[0] + kt * 196608 + blockIdx.x * 1536, 3072);
      cluster_wait();
#pragma unroll 1
      for (int l = 0; l < 4; l++) {
        IDS();
        const CUtensorMap* mw = &prm.m[M_WQA + (l & 1)];
        const CUtensorMap* mh = &prm.m[l == 0 ? M_X0H : M_XSO];
        const CUtensorMap* mo = &prm.m[M_WOA + (l & 1)];
        auto q_b = [&](int i) {
          const int s = i & 3;
          mbar_wait(sb + B_QE + 8 * s, ((i >> 2) & 1) ^ 1);
          e_expect_tx(sb + B_QF + 8 * s, QSTG);
          tma_ld3(sb + s * QSTG + 32768, mw, bn * 64, qord(i, l, pn) * 64, 0, sb + B_QF + 8 * s);
        };
        uint32_t rdy = l ? 0u : ~0u;
        auto q_a = [&](int i) {
          const int kt = qord(i, l, pn);
          await_bit(sb + W_X, l, kt >> 1, rdy);
          tma_ld_mc(sb + (i & 3) * QSTG + rank * 16384, mh, kt * 64, bm * 256 + rank * 128, sb + B_QF + 8 * (i & 3));
        };
        if (l > 0) {
#pragma unroll 1
          for (int i = 0; i < 4; i++) {
            const int kt = qord(i, l, pn);
            await_bit(sb + W_X, l, kt >> 1, rdy);
            e_expect_tx(sb + B_QF + 8 * i, 16384);
            tma_ld(sb + i * QSTG + (po ^ 1) * 16384, &prm.m[M_XSO], kt * 64, (pm ^ 1) * 128, sb + B_QF + 8 * i);
          }
        }
#pragma unroll 1
        for (int i = 4; i < 16; i++) {
          q_b(i); q_a(i);
        }
        if (l & 1) {
          if (l == 3) poll_ge(cnt_ad(bn), ep1 * 16);
          const int krow = 2 * bn * 2048 + bm * 256;
          uint32_t* kvc = cnt_kv(l >> 1, bn);
#pragma unroll 1
          for (int m = 1; m >= 0; m--) {
            bar_sync(m ? NB_ST : NB_KV, 288);
#pragma unroll
            for (int i = 0; i < 4; i++) tma_st(&prm.m[M_K4 + (i >> 1)], 0, krow + (i & 1) * 128 + m * 64, sb + T0 + i * 8192 + m * 4096);
            if (m) {
              sts128(sb + ONES + lane * 32, 0x3f803f80u, 0x3f803f80u, 0x3f803f80u, 0x3f803f80u);
              sts128(sb + ONES + lane * 32 + 16, 0x3f803f80u, 0x3f803f80u, 0x3f803f80u, 0x3f803f80u);
              fence_async_smem();
              __syncwarp();
            }
          }
          e_arrive(sb + B_TF);
          bulk_commit(); bulk_wait_n<0>();
          e_red(kvc + bm);
          bar_sync(NB_KV + 12, 288);
          tma_st(&prm.m[M_K], 0, krow + 2048, sb);
          tma_st(&prm.m[M_V], 0, krow + 2048, sb + 16384);
          bulk_commit();
          uint32_t seen = 0;
#pragma unroll 1
          for (int it = 1; it < 16; it++) {
            const int s = it & 3, blk = it;
            if (it == 4) { bulk_wait_n<0>(); e_red(kvc + bm); }
            if (it == 12) { e_expect_tx(sb + B_RF, 32768); tma_ld3(sb + RES, &prm.m[M_XSR], 0, pm * 128, 2 * pn, sb + B_RF); }
            if (it == 2 || it == 3) mbar_wait(sb + B_TF + 8 * (it - 1), 0);
            mbar_wait(sb + B_TE + 8 * s, ((it >> 2) & 1) ^ 1);
            if (it < 8) {
#pragma unroll 1
              for (uint32_t n = 0; n < 200000u && !((seen >> it) & 1); n++)
                seen = __ballot_sync(~0u, (int)(ld_acquire(kvc + ((bm + lane) & 7)) - (ep1 * 2 - 1)) >= 0);
              fence_async_gl();
            } else if (it == 8) { poll_ge(kvc + (lane & 7), ep1 * 2); fence_async_gl(); }
            const int row = (2 * bn + (it >> 3)) * 2048 + ((bm + blk) & 7) * 256;
            e_expect_tx(sb + B_TF + 8 * s, 32768);
            tma_ld(sb + T0 + s * TSTG, &prm.m[M_K], 0, row, sb + B_TF + 8 * s);
            tma_ld(sb + T0 + s * TSTG + 16384, &prm.m[M_V], 0, row, sb + B_TF + 8 * s);
          }
        }
        auto p_b = [&](int i, uint32_t s, uint32_t par) {
          mbar_wait(sb + B_PE + 8 * s, par ^ 1);
          e_expect_tx(sb + B_PF + 8 * s, PSTG);
          tma_ld5(sb + pslot_b(s, l), mo, i >> 3, 2 * (i & 7), 2 * pn, sb + B_PF + 8 * s);
        };
        auto p_a = [&](int i, uint32_t s) {
          await_bit(sb + W_O, l + 1, i, rdy);
          tma_ld_mc(sb + pslot_a(s, l) + rank * 8192, &prm.m[M_OS], i * 64, pm * 128 + rank * 64, sb + B_PF + 8 * s);
        };
        auto p_a2 = [&](int i) {
          await_bit(sb + W_O, l + 1, i, rdy);
          tma_ld(sb + pslot_a(i, l), &prm.m[M_OS], i * 64, pm * 128, sb + B_PF + 8 * i);
          tma_ld(sb + pslot_a(i, l) + 8192, &prm.m[M_OS], i * 64, pm * 128 + 64, sb + B_PF + 8 * i);
        };
        rdy = 0;
        if (l & 1) {
#pragma unroll 1
          for (int u = 0; u < 6; u++) { const int i = (0x205413 >> (4 * u)) & 7; if (u == 4) mbar_wait(sb + B_TE, 1); p_b(i, i, i < 4 ? 1 : 0); }
#pragma unroll 1
          for (int u = 0; u < 6; u++) {
            const int i = (0x542130 >> (4 * u)) & 7;
            if (!(u & 1)) mbar_wait(sb + B_TE + 8 + 4 * u, 1);
            p_a2(i);
          }
        } else {
#pragma unroll 1
          for (int u = 0; u < 5; u++) { const int i = (0x32140 >> (4 * u)) & 7; if (!(u & 5)) mbar_wait(sb + B_QE + 8 + 4 * u, 1); p_b(i, i, 0); }
          mbar_wait(sb + B_QE + 24, 1);
#pragma unroll 1
          for (int i = 0; i < 4; i++) { if (i < NA2) p_a2(i); else p_a(i, i); }
          bar_sync(NB_DONE, 96);
          e_arrive_both(sb + B_PA);
          p_b(5, 5, 0);
          mbar_wait(sb + B_PA, (l >> 1) & 1);
          p_a(4, 4); p_a(5, 5);
        }
        uint32_t s = 0, lap = 1;
#pragma unroll 1
        for (int i = 6; i < 16; i++) {
          if (i == RESI && !(l & 1)) { e_expect_tx(sb + B_RF, 32768); tma_ld3(sb, &prm.m[l == 0 ? M_X0R : M_XSR], 0, pm * 128, 2 * pn, sb + B_RF); }
          p_b(i, s, ((s < 4 ? l : 0) + lap) & 1);
          p_a(i, s);
          if (++s == 6) { s = 0; lap++; }
        }
        const CUtensorMap* mn = &prm.m[M_WQA + ((l + 1) & 1)];
        if (l < 3) {
          mbar_wait(sb + B_PE + 8 * 4, 1); mbar_wait(sb + B_PE + 8 * 5, 1);
          tma_ld3(sb + 32768, mn, bn * 64, 2 * pn * 64, 0, sb + B_QL);
          mbar_wait(sb + B_PE + 8 * 0, l & 1);
          tma_ld3(sb + QSTG + 32768, mn, bn * 64, (2 * pn + 1) * 64, 0, sb + B_QL);
          mbar_wait(sb + B_PE + 8 * 1, l & 1);
          e_expect_tx(sb + B_QD, 40960);
          tma_ld3(sb + 2 * QSTG + 32768, mn, bn * 64, ((2 * pn) ^ 2) * 64, 0, sb + B_QD);
          bar_sync(NB_X, 288);
          e_expect_tx(sb + B_QL, 49152);
          e_expect_tx(sb + B_QD + 8, 40960);
          tma_ld3(sb + 3 * QSTG + 32768, mn, bn * 64, (((2 * pn) ^ 2) + 1) * 64, 0, sb + B_QD + 8);
        }
      }
      if (blockIdx.x == 0 && lane_id() == 0) *(volatile uint32_t*)prm.epoch = ep1;
    } else {
      const int hw = w - 1;
      if (hw == 1 && lane_id() < M_COUNT) asm volatile("prefetch.tensormap [%0];" ::"l"(&prm.m[lane_id()]) : "memory");
      cluster_wait();
      mbar_wait(sb + B_QF, 0);
#pragma unroll 1
      for (int l = 0; l < 4; l++) {
        IDS();
        if (hw == 2 && l > 0) watch(cnt_x(l, bm) + (lane & 7), ep1 * 2, 0xFFu, l, sb + W_X);
        if (l == 0) {
#pragma unroll 1
          for (int r = 2 * hw; r < 16; r += 6) {
            const uint4* p = (const uint4*)(prm.x0 + (size_t)(b * 16 + r) * 1024) + lane;
            float s1[2] = {0.f, 0.f}, s2[2] = {0.f, 0.f};
#pragma unroll
            for (int i = 0; i < 8; i++) {
              const uint4 v = __ldg(p + 32 * i);
              const uint32_t u[4] = {v.x, v.y, v.z, v.w};
#pragma unroll
              for (int k = 0; k < 4; k++) { const float a = bf_lo(u[k]), c = bf_hi(u[k]); s1[i >> 2] += a + c; s2[i >> 2] = fmaf(a, a, fmaf(c, c, s2[i >> 2])); }
            }
#pragma unroll
            for (int o = 16; o; o >>= 1)
#pragma unroll
              for (int rr = 0; rr < 2; rr++) { s1[rr] += __shfl_xor_sync(~0u, s1[rr], o); s2[rr] += __shfl_xor_sync(~0u, s2[rr], o); }
            if (lane == 0) *(float4*)&g_stats[b * 16 + r] = make_float4(s1[0], s2[0], s1[1], s2[1]);
          }
        }
        if (l == 1) { uint32_t rdy = 0; await_bit<true>(sb + W_X, 1, pn, rdy); mbar_hint(sb + B_QF + 8, 0); }
        if (l < 2) {
          float cs[8];
#pragma unroll
          for (int i = 0; i < 8; i++) cs[i] = 0.f;
          const uint4* wp = (const uint4*)(prm.wq[l] + (size_t)(bm * 128 + (lane >> 3)) * 3072 + hw * 1024 + bn * 64) + (lane & 7);
#pragma unroll 8
          for (int i = 0; i < 32; i++) {
            const uint4 v = __ldg(wp + (size_t)i * 4 * 384);
            cs[0] += bf_lo(v.x); cs[1] += bf_hi(v.x); cs[2] += bf_lo(v.y); cs[3] += bf_hi(v.y);
            cs[4] += bf_lo(v.z); cs[5] += bf_hi(v.z); cs[6] += bf_lo(v.w); cs[7] += bf_hi(v.w);
          }
#pragma unroll
          for (int i = 0; i < 8; i++) { cs[i] += __shfl_xor_sync(~0u, cs[i], 8); cs[i] += __shfl_xor_sync(~0u, cs[i], 16); }
          if (lane < 8) {
            float4* d = (float4*)(g_csp + ((l * 16 + bn) * 8 + bm) * 192 + hw * 64 + lane * 8);
            d[0] = make_float4(cs[0], cs[1], cs[2], cs[3]); d[1] = make_float4(cs[4], cs[5], cs[6], cs[7]);
          }
          __syncwarp();
          asm volatile("fence.acq_rel.gpu;" ::: "memory");
          e_red_relaxed(cnt_cs(l, bn));
          if (l == 0) e_red_relaxed(cnt_x(0, bm) + pn);
          poll_ge(lane < 8 && l == 0 ? cnt_x(0, bm) + lane : cnt_cs(l, bn), ep1 * (lane < 8 && l == 0 ? 6 : 24));
        }
        if (l > 0) {
          uint32_t rdy = 0;
#pragma unroll 1
          for (int j = 0; j < 8; j++) await_bit<true>(sb + W_X, l, j, rdy);
        }
#pragma unroll 1
        for (int it = hw * 32 + lane; it < 176; it += 96) {
          const bool rows = it < 128;
          const float4* p = rows ? (const float4*)(g_stats + bm * 256) + it : (const float4*)(g_csp + ((l & 1) * 16 + bn) * 8 * 192) + (it - 128);
          const int stride = rows ? 1024 : 48, np = rows && l == 0 ? 1 : 8;
          float4 a = make_float4(0.f, 0.f, 0.f, 0.f);
#pragma unroll
          for (int k = 0; k < 8; k++) if (k < np) { const float4 v = __ldcg(p + k * stride); a.x += v.x; a.y += v.y; a.z += v.z; a.w += v.w; }
          if (rows) {
            const float m0 = a.x * (1.f / 1024.f), m1 = a.z * (1.f / 1024.f);
            const float v0 = fmaxf(a.y * (1.f / 1024.f) - m0 * m0, 0.f), v1 = fmaxf(a.w * (1.f / 1024.f) - m1 * m1, 0.f);
            const float r0 = __fdividef(1.f, bf_round(sqrtf(bf_round(bf_round(v0) + 1e-5f)))), r1 = __fdividef(1.f, bf_round(sqrtf(bf_round(bf_round(v1) + 1e-5f))));
            *(float2*)(smem + RSTD + it * 8) = make_float2(r0, r1);
            *(uint32_t*)(smem + MEAN + it * 4) = pack2(-m0, -m1);
          } else {
            float2* d = (float2*)(smem + COLS) + ((it - 128) >> 2) * 8 + (it & 1) * 4 + ((it >> 1) & 1);
            d[0] = make_float2(a.y, a.x); d[2] = make_float2(a.w, a.z);
          }
        }
        __syncwarp();
        if (lane == 0) asm volatile("red.release.cta.shared.add.u32 [%0], 0x100;" ::"r"(sb + W_X) : "memory");
        if (hw == 2) {
          if (!(l & 1)) {
            bar_sync(NB_ST, 288);
            const volatile unsigned long long* hp = g_halo + ((size_t)(l >> 1) * 128 + b - 16) * 1024 + lane;
#pragma unroll 1
            for (int h = 0; h < 2; h++) {
              uint32_t t[16];
#pragma unroll
              for (int i = 0; i < 16; i++) t[i] = 0;
#pragma unroll 1
              for (uint32_t n = bm ? 0 : 100000u; n < 100000u; n++) {
                uint32_t miss = 0;
#pragma unroll
                for (int i = 0; i < 16; i++) {
                  const unsigned long long v = hp[h * 512 + i * 32];
                  t[i] = (uint32_t)v; miss |= (uint32_t)(v >> 32) ^ ep1;
                }
                if (__all_sync(~0u, !miss)) break;
              }
              const uint32_t r = (lane & 7) + ((lane >> 3) & 1) * 8, rv = lane >> 2;
#pragma unroll
              for (int jj = 0; jj < 2; jj++) stsm4(sb + 2 * h * ASC + r * 64 + (((2 * jj + (lane >> 4)) ^ ((r >> 1) & 3)) << 4), t[4 * jj], t[4 * jj + 1], t[4 * jj + 2], t[4 * jj + 3]);
              const uint32_t ad = sb + (2 * h + 1) * ASC + rv * 64 + (((lane & 3) ^ ((rv >> 1) & 3)) << 4);
              sts128(ad, t[8], t[10], t[12], t[14]); sts128(ad + 512, t[9], t[11], t[13], t[15]);
              bar_arrive(NB_HALO + h, 64);
            }
          } else {
            mbar_hint(sb + B_TF + 8, 0);
            poll_ge(cnt_kv(l >> 1, bn) + (lane & 7), ep1 * 2);
            const uint4* kp = (const uint4*)(g_kn + ((l >> 1) * 128 + bn * 8) * 32) + 2 * lane;
            const uint4 v = __ldcg(kp), u = __ldcg(kp + 1);
            const uint32_t mx = max(max(max(v.x, v.y), max(v.z, v.w)), max(max(u.x, u.y), max(u.z, u.w)));
            const uint32_t m0 = __reduce_max_sync(~0u, (lane & 2) ? 0u : mx), m1 = __reduce_max_sync(~0u, (lane & 2) ? mx : 0u);
            if (lane == 0) *(uint2*)(smem + KMAX) = make_uint2(m0, m1);
            __syncwarp();
            bar_arrive(NB_KN, 160); bar_arrive(NB_KN + 1, 160);
          }
        } else {
          bar_sync(NB_SIG + 2 * hw, 160); bar_sync(NB_SIG + 2 * hw + 1, 160);
          if (!(l & 1)) bar_arrive(NB_DONE, 96);
          asm volatile("fence.acq_rel.gpu;" ::: "memory");
          e_red_relaxed(cnt_o(l, 2 * bm, hw) + (bn >> 1));
          e_red_relaxed(cnt_o(l, 2 * bm + 1, hw) + (bn >> 1));
          if (hw == 1 && l == 1) { e_red_relaxed(cnt_ad(bn)); e_red_relaxed(cnt_ad(bn)); }
        }
        if (hw == 2) watch(cnt_o(l, pm, (lane >> 3) & 1) + (lane & 7), ep1 * 2, 0xFFFFu, l + 1, sb + W_O);
        if (hw < 2 && l < 3) {
          bar_sync(NB_X0, 320);
          if (hw == 0) {
            e_red(cnt_x(l + 1, bm) + pn);
          } else {
            mbar_wait(sb + B_PE + 8 * 3, l & 1);
            push_peer(sb + 2 * QSTG + po * 16384, sb + po * 16384, sb + B_QD, rank ^ 1);
            push_peer(sb + 3 * QSTG + po * 16384, sb + QSTG + po * 16384, sb + B_QD + 8, rank ^ 1);
          }
        }
      }
    }
  } else {
    asm volatile("setmaxnreg.inc.sync.aligned.u32 224;");
    const uint32_t zero = prm.zero;
    cluster_wait();
    const uint32_t ep1 = __shfl_sync(~0u, epoch + 1, 0);
#pragma unroll 1
    for (int l = 0; l < 4; l++) {
      {
        float acc[2][96];
#pragma unroll
        for (int i = 0; i < 96; i++) { acc[0][i] = 0.f; acc[1][i] = 0.f; }
        fence_regs(acc[0]); fence_regs(acc[1]);
        const bool early = l > 0 && wg == ((cta_id() >> 3) & 1);
#pragma unroll 1
        for (int kt = 0; kt < 14; kt++) {
          const int s = kt & 3;
          if (l > 0 && kt < 4 && kt != 1) mbar_wait(sb + (kt ? B_QD - 16 + 8 * kt : B_QL), (l + 1) & 1);
          if (!(early && kt < 4)) mbar_wait(sb + B_QF + 8 * s, (kt >> 2) & 1);
          const uint64_t da = mkdesc(sb + s * QSTG + wg * 16384, 16, 1024, 1), db = mkdesc(sb + s * QSTG + 32768, 8192, 1024, 1);
          wg_fence();
#pragma unroll
          for (int k = 0; k < 4; k++)
#pragma unroll
            for (int m = 0; m < 2; m++) wgmma_m64n192k16_ss_tb(acc[m], da + m * 512 + k * 2, db + k * 128, 1);
          wg_commit();
          wg_wait<1>();
          if (early && kt < 5) {
#pragma unroll 1
            for (int i = kt == 3 ? 0 : 3; i < kt; i++) { mbar_wait(sb + B_QF + 8 * i, 0); if (w == 0) e_arrive_both(sb + B_QE + 8 * i); }
          } else if (kt > 0 && w == 0) e_arrive_both(sb + B_QE + 8 * ((kt - 1) & 3));
          if (kt == KC) {
#pragma unroll 1
            for (uint32_t n = 0; n < 4000000u; n++) {
              uint32_t v;
              asm volatile("ld.acquire.cta.shared.u32 %0, [%1];" : "=r"(v) : "r"(sb + W_X) : "memory");
              if ((v >> 8) == (uint32_t)(l * 256 + 3)) break;
            }
            const int lane = lane_id();
            float nm[4];
#pragma unroll
            for (int i = 0; i < 4; i++) nm[i] = bf_lo(*(volatile unsigned short*)(smem + MEAN + (wg * 128 + w * 16 + (lane >> 2) + (i >> 1) * 64 + (i & 1) * 8) * 2));
            wg_wait<0>();
            fence_regs(acc[0]); fence_regs(acc[1]);
#pragma unroll
            for (int j = 0; j < 12; j++) {
              const float4 c = lds128f(sb + COLS + j * 64 + (lane & 3) * 16);
#pragma unroll
              for (int m = 0; m < 2; m++) {
                float* a = &acc[m][8 * j];
                a[0] = fmaf(nm[2 * m], c.y, a[0]); a[1] = fmaf(nm[2 * m], c.x, a[1]); a[2] = fmaf(nm[2 * m + 1], c.y, a[2]); a[3] = fmaf(nm[2 * m + 1], c.x, a[3]);
                a[4] = fmaf(nm[2 * m], c.w, a[4]); a[5] = fmaf(nm[2 * m], c.z, a[5]); a[6] = fmaf(nm[2 * m + 1], c.w, a[6]); a[7] = fmaf(nm[2 * m + 1], c.z, a[7]);
              }
            }
            fence_regs(acc[0]); fence_regs(acc[1]);
          }
        }
        auto part = [&](int s, int m, int k0, int k1) {
          const uint64_t da = mkdesc(sb + s * QSTG + wg * 16384 + m * 8192, 16, 1024, 1), db = mkdesc(sb + s * QSTG + 32768, 8192, 1024, 1);
          pin(zero);
          wg_fence();
#pragma unroll
          for (int k = k0; k < k1; k++) wgmma_m64n192k16_ss_tb(acc[m], da + k * 2, db + k * 128, 1);
          wg_commit();
          pin(zero);
        };
        mbar_wait(sb + B_QF + 16, 1);
        part(2, 1, 0, 4);
        wg_wait<1>();
        if (w == 0) e_arrive_both(sb + B_QE + 8);
        if (!(l & 1)) bar_arrive(NB_ST, 288);
        mbar_wait(sb + B_QF + 24, 1);
        part(3, 1, 0, 4);
        part(2, 0, 0, G1);
        IDS();
        const int g = lane >> 2, qd = lane & 3;
        float rs[2][2];
#pragma unroll
        for (int i = 0; i < 4; i++) rs[i >> 1][i & 1] = lds32f(sb + RSTD + (wg * 128 + w * 16 + g + (i >> 1) * 64 + (i & 1) * 8) * 4);
        auto scale = [&](int gi, int m, float sc) {
          const float r0 = rs[m][0] * sc, r1 = rs[m][1] * sc;
#pragma unroll
          for (int i = 0; i < 16; i++) acc[m][16 * gi + i] *= (i & 2) ? r1 : r0;
        };
        auto pack_b = [&](int gi, int m, uint32_t (&t)[8]) {
#pragma unroll
          for (int i = 0; i < 8; i++) t[i] = pack2(acc[m][16 * gi + 2 * i], acc[m][16 * gi + 2 * i + 1]);
        };
        auto norm_tile = [&](int gi, int m, uint32_t (&t)[8]) { scale(gi, m, 1.f); pack_b(gi, m, t); };
        auto pack_h = [&](int gi, int m, uint32_t (&t)[8]) {
#pragma unroll
          for (int i = 0; i < 8; i++) t[i] = pack2h(acc[m][16 * gi + 2 * i], acc[m][16 * gi + 2 * i + 1]);
        };
        uint32_t q[2][2][8], qn[2][2];
        const uint32_t srow = (lane & 7) + ((lane >> 3) & 1) * 8;
        const uint32_t row0 = wg * 128 + w * 16;
        auto put_kv = [&](int h, int v, int m, const uint32_t (&t)[8]) {
          const uint32_t base = sb + ((l & 1) ? (h ? 0 : T0) + v * 16384 : (2 * h + v) * ASC + 1024) + (row0 + m * 64) * 64;
          if (!v) {
#pragma unroll
            for (int jj = 0; jj < 2; jj++) stsm4(base + srow * 64 + (((2 * jj + (lane >> 4)) ^ ((srow >> 1) & 3)) << 4), t[4 * jj], t[4 * jj + 1], t[4 * jj + 2], t[4 * jj + 3]);
          } else {
            const uint32_t ad = base + g * 64 + ((qd ^ (g >> 1)) << 4);
            sts128(ad, t[0], t[2], t[4], t[6]); sts128(ad + 512, t[1], t[3], t[5], t[7]);
          }
        };
        auto send_halo = [&](int h, int v, const uint32_t (&t)[8]) {
          unsigned long long* hp = g_halo + ((size_t)(l >> 1) * 128 + b) * 1024 + h * 512 + v * 256 + lane;
#pragma unroll
          for (int i = 0; i < 8; i++) st_tagged(hp + i * 32, t[i], ep1);
        };
        auto put_kn = [&](int h, int m, uint32_t kn) {
          if (lane == 0) g_kn[((l >> 1) * 128 + bn * 8 + bm) * 32 + 16 * h + 8 * m + wg * 4 + w] = __uint_as_float(kn);
        };
        auto conv_tile1 = [&](int h) {
          uint32_t t[8], tv[8], kn = NOT_F16;
          norm_tile(4 + h, 1, tv);
          put_kv(h, 1, 1, tv);
          scale(2 + h, 1, 1.f);
          if (h == 0) { if (G1 < 4) part(2, 0, G1, 4); if (G2) part(3, 0, 0, G2); } else if (G3 < 4) part(3, 0, G3, 4);
          if (l & 1) {
            float n[2] = {0.f, 0.f};
#pragma unroll
            for (int i = 0; i < 16; i++) n[(i >> 1) & 1] = fmaf(acc[1][32 + 16 * h + i], acc[1][32 + 16 * h + i], n[(i >> 1) & 1]);
            const float a = ((qd & 1) ? n[1] : n[0]) + __shfl_xor_sync(~0u, (qd & 1) ? n[0] : n[1], 1);
            scale(h, 1, QSCALE / 128.f);
            kn = f16_class(__reduce_max_sync(~0u, __float_as_uint(a + __shfl_xor_sync(~0u, a, 2))), K_LO);
            put_kn(h, 1, kn);
          } else scale(h, 1, 1.f);
          if (kn == NOT_F16) pack_b(2 + h, 1, t); else pack_h(2 + h, 1, t);
          put_kv(h, 0, 1, t);
          if (!(l & 1) && row0 == 176 && bm < 7) { send_halo(h, 0, t); send_halo(h, 1, tv); }
        };
        mbar_wait(sb + B_QE + 8, 1);
        wg_wait<1>();
        fence_regs(acc[1]);
        conv_tile1(0);
        if (G2 < G3) part(3, 0, G2, G3);
        if (l & 1) { fence_async_smem(); bar_arrive(NB_ST, 288); }
        conv_tile1(1);
        wg_wait<(G2 > 0) + (G2 < G3) + (G3 < 4)>();
        if (w == 0) e_arrive_both(sb + B_QE + 16);
        wg_wait<0>();
        fence_regs(acc[0]);
        if (w == 0) e_arrive_both(sb + B_QE + 24);
        bf16* const op0 = [&] { IDS(); return g_os + (size_t)(bm * 256 + row0 + (lane >> 2)) * 1024 + bn * 32 + (lane & 3) * 8; }();
        auto put_o = [&](int h, int m, const float (&o)[16], float i0, float i1) {
          bf16* op = op0 + m * 65536 + h * 512;
          const uint4 a = make_uint4(pack2(o[0] * i0, o[1] * i0), pack2(o[4] * i0, o[5] * i0), pack2(o[8] * i0, o[9] * i0), pack2(o[12] * i0, o[13] * i0));
          const uint4 c = make_uint4(pack2(o[2] * i1, o[3] * i1), pack2(o[6] * i1, o[7] * i1), pack2(o[10] * i1, o[11] * i1), pack2(o[14] * i1, o[15] * i1));
          *(uint4*)op = a; *(uint4*)(op + 8 * 1024) = c;
          const uint32_t hi = __vimax3_u16x2(__vimax3_u16x2(a.x, a.y, a.z), __vimax3_u16x2(a.w, c.x, c.y), __vmaxu2(c.z, c.w));
          const uint32_t lo = __vimax3_s16x2(__vimax3_s16x2(a.x, a.y, a.z), __vimax3_s16x2(a.w, c.x, c.y), __vmaxs2(c.z, c.w));
          return __vmaxu2(hi & 0x7FFF7FFFu, lo & 0x7FFF7FFFu);
        };
        if (!(l & 1)) {
          auto conv_kv = [&](int h) {
            uint32_t t[8];
            norm_tile(2 + h, 0, t); put_kv(h, 0, 0, t);
            norm_tile(4 + h, 0, t); put_kv(h, 1, 0, t);
          };
          conv_kv(0);
          if (!PERHEAD) conv_kv(1);
          norm_tile(0, 0, q[0][0]); pack_b(0, 1, q[0][1]);
          bar_sync(NB_SC, 256);
          const bool e = g & 1, sel = 2 * qd + (g & 1) >= g + 2, first = bm == 0 && row0 == 0;
#pragma unroll 1
          for (int h = 0; h < 2; h++) {
            if (row0 == 0) bar_sync(NB_HALO + h, 64);
            float s[2][4][4];
            uint32_t vf[2][4][4], pf[2][2][4];
#pragma unroll
            for (int m = 0; m < 2; m++)
#pragma unroll
              for (int nt = 0; nt < 4; nt++) {
                uint32_t kf[4];
                const uint32_t r = row0 + m * 64 + 8 * nt + (lane & 7);
                ldsm4(sb + 2 * h * ASC + r * 64 + (((lane >> 3) ^ ((r >> 1) & 3)) << 4), kf);
                s[m][nt][0] = s[m][nt][1] = s[m][nt][2] = s[m][nt][3] = 0.f;
                mma16816(s[m][nt], q[0][m][0], q[0][m][1], q[0][m][2], q[0][m][3], kf[0], kf[1]);
                mma16816(s[m][nt], q[0][m][4], q[0][m][5], q[0][m][6], q[0][m][7], kf[2], kf[3]);
              }
#pragma unroll
            for (int m = 0; m < 2; m++)
#pragma unroll
              for (int i = 0; i < 4; i++) {
                const uint32_t r = row0 + m * 64 + 16 * (i >> 1) + srow, ch = 2 * (i & 1) + (lane >> 4);
                ldsm4t(sb + (2 * h + 1) * ASC + r * 64 + ((ch ^ ((r >> 1) & 3)) << 4), vf[m][i]);
              }
            float va[4], vb[4], mx[4];
#pragma unroll
            for (int i = 0; i < 4; i++) {
              const int m = i >> 1, hh = i & 1;
              const float a = e ? s[m][hh + 1][2 * hh + 1] : s[m][hh + 1][2 * hh];
              const float lo = e ? s[m][hh][2 * hh + 1] : s[m][hh][2 * hh], hi = e ? s[m][hh + 2][2 * hh + 1] : s[m][hh + 2][2 * hh];
              const uint32_t t = pack2(a, sel ? lo : hi);
              const uint32_t u = pack2(bf_lo(t) * 0.17677669529663687f, bf_hi(t) * 0.17677669529663687f);
              va[i] = (m == 0 && hh == 0 && first) ? -INFINITY : bf_lo(u);
              vb[i] = (m == 0 && first && sel) ? -INFINITY : bf_hi(u);
              mx[i] = fmaxf(va[i], vb[i]);
            }
#pragma unroll
            for (int i = 0; i < 4; i++) mx[i] = fmaxf(mx[i], __shfl_xor_sync(~0u, mx[i], 1));
#pragma unroll
            for (int i = 0; i < 4; i++) mx[i] = fmaxf(mx[i], __shfl_xor_sync(~0u, mx[i], 2));
#pragma unroll
            for (int i = 0; i < 4; i++) {
              va[i] = ex2((va[i] - mx[i]) * 1.4426950408889634f); vb[i] = ex2((vb[i] - mx[i]) * 1.4426950408889634f);
              mx[i] = va[i] + vb[i];
            }
#pragma unroll
            for (int i = 0; i < 4; i++) mx[i] += __shfl_xor_sync(~0u, mx[i], 1);
#pragma unroll
            for (int i = 0; i < 4; i++) mx[i] += __shfl_xor_sync(~0u, mx[i], 2);
#pragma unroll
            for (int i = 0; i < 4; i++) {
              const int m = i >> 1, hh = i & 1;
              const float inv = rcp(mx[i]);
              const uint32_t t = pack2(va[i] * inv, vb[i] * inv);
              const uint32_t pa = e ? t << 16 : t & 0xFFFFu, pb = e ? t & 0xFFFF0000u : t >> 16;
              pf[m][hh][hh + 1] = pa; pf[m][hh][hh] = sel ? pb : 0u; pf[m][hh][hh + 2] = sel ? 0u : pb; pf[m][hh][3 - 3 * hh] = 0u;
            }
#pragma unroll
            for (int m = 0; m < 2; m++) {
              float o[4][4];
#pragma unroll
              for (int j = 0; j < 4; j++) o[j][0] = o[j][1] = o[j][2] = o[j][3] = 0.f;
#pragma unroll
              for (int i = 0; i < 4; i++) {
                const int kk = i >> 1, jj = 2 * (i & 1);
                mma16816(o[jj], pf[m][0][2 * kk], pf[m][1][2 * kk], pf[m][0][2 * kk + 1], pf[m][1][2 * kk + 1], vf[m][i][0], vf[m][i][1]);
                mma16816(o[jj + 1], pf[m][0][2 * kk], pf[m][1][2 * kk], pf[m][0][2 * kk + 1], pf[m][1][2 * kk + 1], vf[m][i][2], vf[m][i][3]);
              }
              const float of[16] = {o[0][0], o[0][1], o[0][2], o[0][3], o[1][0], o[1][1], o[1][2], o[1][3], o[2][0], o[2][1], o[2][2], o[2][3], o[3][0], o[3][1], o[3][2], o[3][3]};
              put_o(h, m, of, 1.f, 1.f);
            }
            bar_arrive(NB_SIG + 2 * h + wg, 160);
            if (h == 0) {
              if (PERHEAD) conv_kv(1);
              norm_tile(1, 0, q[0][0]); pack_b(1, 1, q[0][1]);
              if (PERHEAD) bar_sync(NB_SC, 256);
            }
          }
        } else {
          auto conv_h = [&](int gi, int m, uint32_t (&t)[8]) {
            pack_h(gi, m, t);
            float d0[4] = {0.f, 0.f, 0.f, 0.f}, d1[4] = {0.f, 0.f, 0.f, 0.f};
            mma16816h(d0, t[0], t[1], t[2], t[3], t[0], t[2]); mma16816h(d1, t[0], t[1], t[2], t[3], t[1], t[3]);
            mma16816h(d0, t[4], t[5], t[6], t[7], t[4], t[6]); mma16816h(d1, t[4], t[5], t[6], t[7], t[5], t[7]);
            return (uint32_t)__reduce_max_sync(~0u, max(max(__float_as_int(d0[0]), __float_as_int(d0[1])), max(__float_as_int(d1[2]), __float_as_int(d1[3]))));
          };
#pragma unroll
          for (int h = 0; h < 2; h++) {
            uint32_t t[8], tv[8];
            scale(2 + h, 0, 1.f);
            const uint32_t kn = f16_class(conv_h(2 + h, 0, t), K_LO);
            if (h) {
#pragma unroll
              for (int i = 0; i < 2; i++) {
                scale(i, 0, QSCALE);
                qn[i][0] = f16_class(conv_h(i, 0, q[i][0]), K_LO);
                qn[i][1] = f16_class(conv_h(i, 1, q[i][1]), K_LO);
              }
            }
            norm_tile(4 + h, 0, tv);
            put_kv(h, 1, 0, tv);
            put_kn(h, 0, kn);
            if (kn == NOT_F16) pack_b(2 + h, 0, t);
            put_kv(h, 0, 0, t);
            fence_async_smem();
            bar_arrive(NB_KV + 12 * h, 288);
            if (h == 0) mbar_wait(sb + B_QF + 24, 1);
          }
          if (max(max(qn[0][0], qn[0][1]), max(qn[1][0], qn[1][1])) == NOT_F16) {
#pragma unroll
            for (int i = 0; i < 4; i++) if (qn[i >> 1][i & 1] == NOT_F16) pack_b(i >> 1, i & 1, q[i >> 1][i & 1]);
          }
          const bool elected = w == 0 && lane == 0;
          const uint64_t kd0 = mkdesc(sb + T0, 16, 512, 2);
          const uint64_t vd0 = mkdesc(sb + T0 + 16384, ONES - (T0 + 16384), 512, 2);
          constexpr uint64_t VSTEP = 64 - (64ull << 16);
          constexpr int RPC = NQ / 16, NC = 256 / NQ;
          float o[2][20], SA[2][NQ / 2];
          uint32_t SB[2][NQ / 4], PA[LA][4], PB[LB][4];
#pragma unroll
          for (int m = 0; m < 2; m++) {
#pragma unroll
            for (int i = 0; i < NQ / 2; i++) SA[m][i] = 0.f;
#pragma unroll
            for (int i = 0; i < NQ / 4; i++) SB[m][i] = 0u;
            fence_regs(SA[m]); fence_regs(SB[m]);
          }
          auto qka = [&](int b, int k, uint64_t d, int h = 0) { QK_A(SA[b], q[h][0][4 * k], q[h][0][4 * k + 1], q[h][0][4 * k + 2], q[h][0][4 * k + 3], d + 2 * k, k ? 1 : zero); };
          auto qkb = [&](int b, int k, uint64_t d, int h = 0) { QK_B(SB[b], q[h][1][4 * k], q[h][1][4 * k + 1], q[h][1][4 * k + 2], q[h][1][4 * k + 3], d + 2 * k, k ? 1 : zero); };
          auto pv = [&](int m, const uint32_t (&Px)[4], uint64_t vd) { wgmma_m64n40k16_rs_tb(o[m], Px[0], Px[1], Px[2], Px[3], vd, 1); };
          auto clear = [&]() {
#pragma unroll
            for (int i = 0; i < 20; i++) o[0][i] = o[1][i] = 0.f;
            fence_regs(o[0]); fence_regs(o[1]);
#pragma unroll
            for (int i = 0; i < 4; i++) PA[0][i] = PB[0][i] = PA[LA - 1][i] = PB[LB - 1][i] = zero;
          };
          mbar_wait(sb + B_TF, 0);
          wg_fence(); qka(0, 0, kd0); qkb(0, 0, kd0); qka(0, 1, kd0); qkb(0, 1, kd0); wg_commit();
          clear();
          wg_wait<0>(); fence_regs(SA[0]); fence_regs(SB[0]);
#pragma unroll 1
          for (int pass = 0; pass < 2; pass++) {
#pragma unroll 1
            for (int j = 0; j < 8; j++) {
              const uint32_t s = j & 3, sn = j < 7 ? (j + 1) & 3 : s, sp = j > 0 ? (j + 3) & 3 : s;
              const uint64_t kd = kd0 + s * 2048, vd = vd0 + s * (32 * VSTEP), kdn = kd0 + sn * 2048, vdp = vd0 + sp * (32 * VSTEP) + 16 * VSTEP;
              bool landed = false;
#pragma unroll
              for (int r = 0; r < 16; r++) {
                const int c = r / RPC, ro = r % RPC, cn = c + 1;
                if (r == 16 - RPC && !landed) mbar_wait(sb + B_TF + 8 * sn, ((j + 1) >> 2) & 1);
                wg_fence();
                const uint64_t kx = cn < NC ? kd + cn * NQ * 4 : kdn, va = (r >= LA ? vd : vdp) + (r - LA) * VSTEP, vb = (r >= LB ? vd : vdp) + (r - LB) * VSTEP;
                if (LAG & 4) { pv(0, PA[r % LA], va); pv(1, PB[r % LB], vb); }
#pragma unroll
                for (int k = 0; k < 2; k++) {
                  if (ro == ((OA >> (4 * k)) & 15)) qka(cn & 1, k, kx);
                  if (ro == ((OB >> (4 * k)) & 15)) qkb(cn & 1, k, kx);
                }
                if (!(LAG & 4)) {
                  if (ro == RPC - 1 || (LAG & 1)) wg_commit();
                  if (LAG & 8) { pv(1, PB[r % LB], vb); pv(0, PA[r % LA], va); } else { pv(0, PA[r % LA], va); pv(1, PB[r % LB], vb); }
                }
                wg_commit();
                if (r == 14 - RPC) landed = mbar_test(sb + B_TF + 8 * sn, ((j + 1) >> 2) & 1) || j == 7;
#pragma unroll
                for (int i = 0; i < 4; i++) {
                  if (LAG & 16) PB[r % LB][i] = exp2_h2(SB[c & 1][4 * ro + i]);
                  PA[r % LA][i] = pack2(ex2(SA[c & 1][8 * ro + 2 * i]), ex2(SA[c & 1][8 * ro + 2 * i + 1]));
                  if (!(LAG & 16)) PB[r % LB][i] = exp2_h2(SB[c & 1][4 * ro + i]);
                }
                if (r == 15 || ((LAG & 4) && ro == RPC - 1 && ((OA >> 4) == ro || (OB >> 4) == ro))) wg_wait<0>(); else if (ro == RPC - 1 || !(LAG & 2)) wg_wait<1>();
                if (ro == RPC - 1) { fence_regs(SA[cn & 1]); fence_regs(SB[cn & 1]); }
                if (r == (LA + LB > 2 ? 4 : RPC) && elected && j > 0) mbar_arrive(sb + B_TE + 8 * sp);
              }
            }
            int badm = 0;
            if (pass == 0) mbar_wait(sb + B_TF, 0);
            wg_fence();
            if (LA == 2) pv(0, PA[0], vd0 + 110 * VSTEP);
            if (LB == 2) pv(1, PB[0], vd0 + 110 * VSTEP);
            pv(0, PA[LA - 1], vd0 + 111 * VSTEP); pv(1, PB[LB - 1], vd0 + 111 * VSTEP); wg_commit();
            qka(0, 0, kd0, 1); qkb(0, 0, kd0, 1); qka(0, 1, kd0, 1); qkb(0, 1, kd0, 1); wg_commit();
            if (pass == 0) bar_sync(NB_KN + wg, 160);
            const float kmax = *(volatile float*)(smem + KMAX + 4 * pass);
            wg_wait<1>(); fence_regs(o[0]); fence_regs(o[1]);
            if (w == 0) e_arrive(sb + B_TE + 8 * 3);
#pragma unroll
            for (int m = 0; m < 2; m++) {
              const float of[16] = {o[m][0], o[m][1], o[m][2], o[m][3], o[m][4], o[m][5], o[m][6], o[m][7], o[m][8], o[m][9], o[m][10], o[m][11], o[m][12], o[m][13], o[m][14], o[m][15]};
              const uint32_t chk = put_o(pass, m, of, rcp(o[m][16]), rcp(o[m][18]));
              const bool bad = !(__uint_as_float(qn[0][m]) * kmax <= (m ? 0.875f * 0.875f : 112.f * 112.f)) || !(fminf(o[m][16], o[m][18]) >= 9.3e-10f) ||
                               !(o[m][16] + o[m][18] <= 3e38f) || ((chk + 0x00800080u) & 0x80008000u);
              badm |= __any_sync(~0u, bad) << m;
            }
            wg_wait<0>(); fence_regs(SA[0]); fence_regs(SB[0]);
            if (badm) {
#pragma unroll 1
              for (int m = 0; m < 2; m++) if ((badm >> m) & 1) {
                uint32_t qq[8]; float res[20];
#pragma unroll
                for (int i = 0; i < 8; i++) { qq[i] = m ? q[0][1][i] : q[0][0][i]; if ((m ? qn[0][1] : qn[0][0]) != NOT_F16) qq[i] = h2_to_bf2(qq[i]); }
                attn_slow(qq, m ? 128.f : 1.f, 2 * (cta_id() & 15) + pass, g_kn + ((l >> 1) * 128 + (cta_id() & 15) * 8) * 32 + 16 * pass, res, lane_id());
                const float of[16] = {res[0], res[1], res[2], res[3], res[4], res[5], res[6], res[7], res[8], res[9], res[10], res[11], res[12], res[13], res[14], res[15]};
                put_o(pass, m, of, rcp(res[16]), rcp(res[18]));
              }
            }
            bar_arrive(NB_SIG + 2 * pass + wg, 160);
            qn[0][0] = qn[1][0]; qn[0][1] = qn[1][1];
#pragma unroll
            for (int m = 0; m < 2; m++)
#pragma unroll
              for (int i = 0; i < 8; i++) q[0][m][i] = q[1][m][i];
            clear();
          }
        }
      }
      {
        float acc[64];
#pragma unroll
        for (int i = 0; i < 64; i++) acc[i] = 0.f;
        fence_regs(acc);
        uint32_t s = 0, lap = 0;
#pragma unroll 1
        for (int kt = 0; kt < 16; kt++) {
          mbar_wait(sb + B_PF + 8 * s, ((s < 4 ? l : 0) + lap) & 1);
          const uint64_t da = mkdesc(sb + pslot_a(s, l) + wg * 8192, 16, 1024, 1), db = mkdesc(sb + pslot_b(s, l), 8192, 1024, 1);
          wg_fence();
#pragma unroll
          for (int k = 0; k < 4; k++) wgmma_m64n128k16_ss_tb(acc, da + k * 2, db + k * 128, 1);
          wg_commit();
          wg_wait<1>();
          if (kt > 0 && w == 0) e_arrive_both(sb + B_PE + 8 * (s ? s - 1 : 5));
          if (++s == 6) { s = 0; lap++; }
        }
        IDS();
        const int g = lane >> 2, qd = lane & 3;
        const int r0 = wg * 64 + w * 16;
        const uint32_t r = r0 + (lane & 7) + ((lane >> 3) & 1) * 8;
        uint32_t x[8][4];
        mbar_wait(sb + B_RF, l & 1);
#pragma unroll
        for (int jj = 0; jj < 8; jj++) ldsm4(sb + ((l & 1) ? RES : 0) + (jj >> 2) * 16384 + r * 128 + ((((2 * jj + (lane >> 4)) & 7) ^ (r & 7)) << 4), x[jj]);
        wg_wait<0>();
        fence_regs(acc);
        bar_sync(NB_SC, 256);
        if (w == 0) e_arrive_both(sb + B_PE + 8 * 3);
        const CUtensorMap* mo = &prm.m[l == 3 ? M_OUT : M_XST];
#pragma unroll
        for (int jj = 0; jj < 8; jj++) {
#pragma unroll
          for (int i = 0; i < 4; i++) x[jj][i] = add_bf16x2(x[jj][i], pack2(acc[8 * jj + 2 * i], acc[8 * jj + 2 * i + 1]));
          stsm4(sb + (jj >> 2) * QSTG + po * 16384 + r * 128 + ((((2 * jj + (lane >> 4)) & 7) ^ (r & 7)) << 4), x[jj][0], x[jj][1], x[jj][2], x[jj][3]);
          if ((jj & 3) == 3) { fence_async_smem(); __syncwarp(); tma_st(mo, pn * 128 + (jj >> 2) * 64, pm * 128 + r0, sb + (jj >> 2) * QSTG + po * 16384 + r0 * 128); }
        }
        bulk_commit();
        if (l < 3) {
          bar_arrive(NB_X, 288);
          float s1[4] = {0.f, 0.f, 0.f, 0.f}, s2[4][4];
#pragma unroll
          for (int i = 0; i < 16; i++) s2[i >> 2][i & 3] = 0.f;
#pragma unroll
          for (int jj = 0; jj < 8; jj++) {
            mma16816(s1, x[jj][0], x[jj][1], x[jj][2], x[jj][3], 0x3f803f80u, 0x3f803f80u);
#pragma unroll
            for (int i = 0; i < 4; i++) mma1688(s2[i], x[jj][i & 2], x[jj][i | 1], x[jj][i]);
          }
          if (qd == (g >> 1)) {
            float2* sp = g_stats + pn * 2048 + pm * 128 + r0 + g;
            sp[0] = make_float2(s1[0], (g & 1) ? s2[0][1] + s2[2][1] : s2[0][0] + s2[2][0]);
            sp[8] = make_float2(s1[2], (g & 1) ? s2[1][3] + s2[3][3] : s2[1][2] + s2[3][2]);
          }
        }
        bulk_wait_n<0>();
        if (l < 3) bar_arrive(NB_X0, 320);
      }
    }
  }
  asm volatile("barrier.cluster.arrive.relaxed.aligned;\nbarrier.cluster.wait.aligned;" ::: "memory");
}

typedef CUresult (*EncodeFn)(CUtensorMap*, CUtensorMapDataType, cuuint32_t, void*, const cuuint64_t*, const cuuint64_t*, const cuuint32_t*,
                             const cuuint32_t*, CUtensorMapInterleave, CUtensorMapSwizzle, CUtensorMapL2promotion, CUtensorMapFloatOOBfill);

static void make_map(EncodeFn fn, CUtensorMap* m, const void* ptr, int rank, const uint64_t* dims, const uint64_t* strides, const uint32_t* box, CUtensorMapSwizzle sw) {
  cuuint64_t d[5], st[4];
  cuuint32_t bx[5], es[5];
  for (int i = 0; i < rank; i++) { d[i] = dims[i]; bx[i] = box[i]; es[i] = 1; if (i) st[i - 1] = strides[i - 1] * 2; }
  fn(m, CU_TENSOR_MAP_DATA_TYPE_BFLOAT16, rank, (void*)ptr, d, st, bx, es, CU_TENSOR_MAP_INTERLEAVE_NONE, sw,
     CU_TENSOR_MAP_L2_PROMOTION_L2_128B, CU_TENSOR_MAP_FLOAT_OOB_FILL_NONE);
}
static void map2(EncodeFn fn, CUtensorMap* m, const void* ptr, uint64_t inner, uint64_t outer, uint32_t bi, uint32_t bo, CUtensorMapSwizzle sw) {
  const uint64_t d[2] = {inner, outer}, st[1] = {inner};
  const uint32_t bx[2] = {bi, bo};
  make_map(fn, m, ptr, 2, d, st, bx, sw);
}

extern "C" void kernel_launch(void* const* d_in, const int* in_sizes, int n_in, void* d_out, int out_size) {
  (void)in_sizes; (void)n_in; (void)out_size;
  static EncodeFn enc = nullptr;
  static void *xs, *os, *kk, *vv, *ep;
  if (!enc) {
    void* p = nullptr;
    cudaDriverEntryPointQueryResult qr;
    cudaGetDriverEntryPoint("cuTensorMapEncodeTiled", &p, cudaEnableDefault, &qr);
    enc = (EncodeFn)p;
    cudaGetSymbolAddress(&xs, g_xs); cudaGetSymbolAddress(&os, g_os); cudaGetSymbolAddress(&kk, g_k); cudaGetSymbolAddress(&vv, g_v); cudaGetSymbolAddress(&ep, g_epoch);
    cudaFuncSetAttribute(fused_kernel, cudaFuncAttributeMaxDynamicSharedMemorySize, SMEM_BYTES);
  }
  Params prm;
  const CUtensorMapSwizzle S128 = CU_TENSOR_MAP_SWIZZLE_128B, S64 = CU_TENSOR_MAP_SWIZZLE_64B;
  map2(enc, &prm.m[M_X0A], d_in[0], 1024, 2048, 64, 256, S128);
  map2(enc, &prm.m[M_XSA], xs, 1024, 2048, 64, 256, S128);
  for (int t = 0; t < 2; t++) {
    const uint64_t d3[3] = {1024, 1024, 3}, s3[2] = {3072, 1024};
    const uint32_t b3[3] = {64, 64, 3};
    make_map(enc, &prm.m[M_WQA + t], d_in[1 + 3 * t], 3, d3, s3, b3, S128);
    const uint64_t d5[5] = {64, 32, 2, 16, 16}, s5[4] = {1024, 32 * 1024, 64 * 1024, 64};
    const uint32_t b5[5] = {64, 32, 1, 2, 2};
    make_map(enc, &prm.m[M_WOA + t], d_in[2 + 3 * t], 5, d5, s5, b5, S128);
    const uint64_t dr[3] = {64, 2048, 16}, sr[2] = {1024, 64};
    const uint32_t br[3] = {64, 128, 2};
    make_map(enc, &prm.m[M_X0R + t], t ? xs : d_in[0], 3, dr, sr, br, S128);
  }
  map2(enc, &prm.m[M_OS], os, 1024, 2048, 64, 64, S128);
  map2(enc, &prm.m[M_K], kk, 32, 65536, 32, 256, S64);
  map2(enc, &prm.m[M_V], vv, 32, 65536, 32, 256, S64);
  map2(enc, &prm.m[M_K4], kk, 32, 65536, 32, 64, S64);
  map2(enc, &prm.m[M_V4], vv, 32, 65536, 32, 64, S64);
  map2(enc, &prm.m[M_XSO], xs, 1024, 2048, 64, 128, S128);
  map2(enc, &prm.m[M_X0H], d_in[0], 1024, 2048, 64, 128, S128);
  map2(enc, &prm.m[M_XST], xs, 1024, 2048, 64, 16, S128);
  map2(enc, &prm.m[M_OUT], d_out, 1024, 2048, 64, 16, S128);
  prm.x0 = (const bf16*)d_in[0];
  prm.wq[0] = (const bf16*)d_in[1]; prm.wq[1] = (const bf16*)d_in[4];
  prm.epoch = (uint32_t*)ep;
  prm.zero = 0;
  for (int i = 0; i < 128; i++) prm.map[i] = remap(i);
  fused_kernel<<<128, 384, SMEM_BYTES>>>(prm);
}
```

```cpp
#include <cuda_runtime.h>
#include <cuda_bf16.h>
#include <cuda.h>
#include <stdint.h>

typedef __nv_bfloat16 bf16;

__device__ __forceinline__ void wgmma_m64n192k16_ss_tb(float (&d)[96], uint64_t da, uint64_t db, int scale_d) {
  asm volatile("{\n.reg .pred p;\nsetp.ne.b32 p, %98, 0;\n"
    "wgmma.mma_async.sync.aligned.m64n192k16.f32.bf16.bf16 "
    "{%0, %1, %2, %3, %4, %5, %6, %7, %8, %9, %10, %11, %12, %13, %14, %15, "
    "%16, %17, %18, %19, %20, %21, %22, %23, %24, %25, %26, %27, %28, %29, %30, %31, "
    "%32, %33, %34, %35, %36, %37, %38, %39, %40, %41, %42, %43, %44, %45, %46, %47, "
    "%48, %49, %50, %51, %52, %53, %54, %55, %56, %57, %58, %59, %60, %61, %62, %63, "
    "%64, %65, %66, %67, %68, %69, %70, %71, %72, %73, %74, %75, %76, %77, %78, %79, "
    "%80, %81, %82, %83, %84, %85, %86, %87, %88, %89, %90, %91, %92, %93, %94, %95}, "
    "%96, %97, p, 1, 1, 0, 1;\n}\n"
    : "+f"(d[0]), "+f"(d[1]), "+f"(d[2]), "+f"(d[3]), "+f"(d[4]), "+f"(d[5]), "+f"(d[6]), "+f"(d[7]),
      "+f"(d[8]), "+f"(d[9]), "+f"(d[10]), "+f"(d[11]), "+f"(d[12]), "+f"(d[13]), "+f"(d[14]), "+f"(d[15]),
      "+f"(d[16]), "+f"(d[17]), "+f"(d[18]), "+f"(d[19]), "+f"(d[20]), "+f"(d[21]), "+f"(d[22]), "+f"(d[23]),
      "+f"(d[24]), "+f"(d[25]), "+f"(d[26]), "+f"(d[27]), "+f"(d[28]), "+f"(d[29]), "+f"(d[30]), "+f"(d[31]),
      "+f"(d[32]), "+f"(d[33]), "+f"(d[34]), "+f"(d[35]), "+f"(d[36]), "+f"(d[37]), "+f"(d[38]), "+f"(d[39]),
      "+f"(d[40]), "+f"(d[41]), "+f"(d[42]), "+f"(d[43]), "+f"(d[44]), "+f"(d[45]), "+f"(d[46]), "+f"(d[47]),
      "+f"(d[48]), "+f"(d[49]), "+f"(d[50]), "+f"(d[51]), "+f"(d[52]), "+f"(d[53]), "+f"(d[54]), "+f"(d[55]),
      "+f"(d[56]), "+f"(d[57]), "+f"(d[58]), "+f"(d[59]), "+f"(d[60]), "+f"(d[61]), "+f"(d[62]), "+f"(d[63]),
      "+f"(d[64]), "+f"(d[65]), "+f"(d[66]), "+f"(d[67]), "+f"(d[68]), "+f"(d[69]), "+f"(d[70]), "+f"(d[71]),
      "+f"(d[72]), "+f"(d[73]), "+f"(d[74]), "+f"(d[75]), "+f"(d[76]), "+f"(d[77]), "+f"(d[78]), "+f"(d[79]),
      "+f"(d[80]), "+f"(d[81]), "+f"(d[82]), "+f"(d[83]), "+f"(d[84]), "+f"(d[85]), "+f"(d[86]), "+f"(d[87]),
      "+f"(d[88]), "+f"(d[89]), "+f"(d[90]), "+f"(d[91]), "+f"(d[92]), "+f"(d[93]), "+f"(d[94]), "+f"(d[95])
    : "l"(da), "l"(db), "r"(scale_d));
}

__device__ __forceinline__ void wgmma_m64n128k16_ss_tb(float (&d)[64], uint64_t da, uint64_t db, int scale_d) {
  asm volatile("{\n.reg .pred p;\nsetp.ne.b32 p, %66, 0;\n"
    "wgmma.mma_async.sync.aligned.m64n128k16.f32.bf16.bf16 "
    "{%0, %1, %2, %3, %4, %5, %6, %7, %8, %9, %10, %11, %12, %13, %14, %15, "
    "%16, %17, %18, %19, %20, %21, %22, %23, %24, %25, %26, %27, %28, %29, %30, %31, "
    "%32, %33, %34, %35, %36, %37, %38, %39, %40, %41, %42, %43, %44, %45, %46, %47, "
    "%48, %49, %50, %51, %52, %53, %54, %55, %56, %57, %58, %59, %60, %61, %62, %63}, "
    "%64, %65, p, 1, 1, 0, 1;\n}\n"
    : "+f"(d[0]), "+f"(d[1]), "+f"(d[2]), "+f"(d[3]), "+f"(d[4]), "+f"(d[5]), "+f"(d[6]), "+f"(d[7]),
      "+f"(d[8]), "+f"(d[9]), "+f"(d[10]), "+f"(d[11]), "+f"(d[12]), "+f"(d[13]), "+f"(d[14]), "+f"(d[15]),
      "+f"(d[16]), "+f"(d[17]), "+f"(d[18]), "+f"(d[19]), "+f"(d[20]), "+f"(d[21]), "+f"(d[22]), "+f"(d[23]),
      "+f"(d[24]), "+f"(d[25]), "+f"(d[26]), "+f"(d[27]), "+f"(d[28]), "+f"(d[29]), "+f"(d[30]), "+f"(d[31]),
      "+f"(d[32]), "+f"(d[33]), "+f"(d[34]), "+f"(d[35]), "+f"(d[36]), "+f"(d[37]), "+f"(d[38]), "+f"(d[39]),
      "+f"(d[40]), "+f"(d[41]), "+f"(d[42]), "+f"(d[43]), "+f"(d[44]), "+f"(d[45]), "+f"(d[46]), "+f"(d[47]),
      "+f"(d[48]), "+f"(d[49]), "+f"(d[50]), "+f"(d[51]), "+f"(d[52]), "+f"(d[53]), "+f"(d[54]), "+f"(d[55]),
      "+f"(d[56]), "+f"(d[57]), "+f"(d[58]), "+f"(d[59]), "+f"(d[60]), "+f"(d[61]), "+f"(d[62]), "+f"(d[63])
    : "l"(da), "l"(db), "r"(scale_d));
}

__device__ __forceinline__ void wgmma_m64n32k16_rs_nb_h(float (&d)[16], uint32_t a0, uint32_t a1, uint32_t a2, uint32_t a3, uint64_t db, int scale_d) {
  asm volatile("{\n.reg .pred p;\nsetp.ne.b32 p, %21, 0;\n"
    "wgmma.mma_async.sync.aligned.m64n32k16.f32.f16.f16 "
    "{%0, %1, %2, %3, %4, %5, %6, %7, %8, %9, %10, %11, %12, %13, %14, %15}, "
    "{%16, %17, %18, %19}, %20, p, 1, 1, 0;\n}\n"
    : "+f"(d[0]), "+f"(d[1]), "+f"(d[2]), "+f"(d[3]), "+f"(d[4]), "+f"(d[5]), "+f"(d[6]), "+f"(d[7]),
      "+f"(d[8]), "+f"(d[9]), "+f"(d[10]), "+f"(d[11]), "+f"(d[12]), "+f"(d[13]), "+f"(d[14]), "+f"(d[15])
    : "r"(a0), "r"(a1), "r"(a2), "r"(a3), "l"(db), "r"(scale_d));
}

__device__ __forceinline__ void wgmma_m64n32k16_rs_nb_hh(uint32_t (&d)[8], uint32_t a0, uint32_t a1, uint32_t a2, uint32_t a3, uint64_t db, int scale_d) {
  asm volatile("{\n.reg .pred p;\nsetp.ne.b32 p, %13, 0;\n"
    "wgmma.mma_async.sync.aligned.m64n32k16.f16.f16.f16 "
    "{%0, %1, %2, %3, %4, %5, %6, %7}, "
    "{%8, %9, %10, %11}, %12, p, 1, 1, 0;\n}\n"
    : "+r"(d[0]), "+r"(d[1]), "+r"(d[2]), "+r"(d[3]), "+r"(d[4]), "+r"(d[5]), "+r"(d[6]), "+r"(d[7])
    : "r"(a0), "r"(a1), "r"(a2), "r"(a3), "l"(db), "r"(scale_d));
}

__device__ __forceinline__ void wgmma_m64n64k16_rs_nb_h(float (&d)[32], uint32_t a0, uint32_t a1, uint32_t a2, uint32_t a3, uint64_t db, int scale_d) {
  asm volatile("{\n.reg .pred p;\nsetp.ne.b32 p, %37, 0;\n"
    "wgmma.mma_async.sync.aligned.m64n64k16.f32.f16.f16 "
    "{%0, %1, %2, %3, %4, %5, %6, %7, %8, %9, %10, %11, %12, %13, %14, %15, "
    "%16, %17, %18, %19, %20, %21, %22, %23, %24, %25, %26, %27, %28, %29, %30, %31}, "
    "{%32, %33, %34, %35}, %36, p, 1, 1, 0;\n}\n"
    : "+f"(d[0]), "+f"(d[1]), "+f"(d[2]), "+f"(d[3]), "+f"(d[4]), "+f"(d[5]), "+f"(d[6]), "+f"(d[7]),
      "+f"(d[8]), "+f"(d[9]), "+f"(d[10]), "+f"(d[11]), "+f"(d[12]), "+f"(d[13]), "+f"(d[14]), "+f"(d[15]),
      "+f"(d[16]), "+f"(d[17]), "+f"(d[18]), "+f"(d[19]), "+f"(d[20]), "+f"(d[21]), "+f"(d[22]), "+f"(d[23]),
      "+f"(d[24]), "+f"(d[25]), "+f"(d[26]), "+f"(d[27]), "+f"(d[28]), "+f"(d[29]), "+f"(d[30]), "+f"(d[31])
    : "r"(a0), "r"(a1), "r"(a2), "r"(a3), "l"(db), "r"(scale_d));
}

__device__ __forceinline__ void wgmma_m64n64k16_rs_nb_hh(uint32_t (&d)[16], uint32_t a0, uint32_t a1, uint32_t a2, uint32_t a3, uint64_t db, int scale_d) {
  asm volatile("{\n.reg .pred p;\nsetp.ne.b32 p, %21, 0;\n"
    "wgmma.mma_async.sync.aligned.m64n64k16.f16.f16.f16 "
    "{%0, %1, %2, %3, %4, %5, %6, %7, %8, %9, %10, %11, %12, %13, %14, %15}, "
    "{%16, %17, %18, %19}, %20, p, 1, 1, 0;\n}\n"
    : "+r"(d[0]), "+r"(d[1]), "+r"(d[2]), "+r"(d[3]), "+r"(d[4]), "+r"(d[5]), "+r"(d[6]), "+r"(d[7]),
      "+r"(d[8]), "+r"(d[9]), "+r"(d[10]), "+r"(d[11]), "+r"(d[12]), "+r"(d[13]), "+r"(d[14]), "+r"(d[15])
    : "r"(a0), "r"(a1), "r"(a2), "r"(a3), "l"(db), "r"(scale_d));
}

__device__ __forceinline__ void wgmma_m64n40k16_rs_tb(float (&d)[20], uint32_t a0, uint32_t a1, uint32_t a2, uint32_t a3, uint64_t db, int scale_d) {
  asm volatile("{\n.reg .pred p;\nsetp.ne.b32 p, %25, 0;\n"
    "wgmma.mma_async.sync.aligned.m64n40k16.f32.bf16.bf16 "
    "{%0, %1, %2, %3, %4, %5, %6, %7, %8, %9, %10, %11, %12, %13, %14, %15, "
    "%16, %17, %18, %19}, "
    "{%20, %21, %22, %23}, %24, p, 1, 1, 1;\n}\n"
    : "+f"(d[0]), "+f"(d[1]), "+f"(d[2]), "+f"(d[3]), "+f"(d[4]), "+f"(d[5]), "+f"(d[6]), "+f"(d[7]),
      "+f"(d[8]), "+f"(d[9]), "+f"(d[10]), "+f"(d[11]), "+f"(d[12]), "+f"(d[13]), "+f"(d[14]), "+f"(d[15]),
      "+f"(d[16]), "+f"(d[17]), "+f"(d[18]), "+f"(d[19])
    : "r"(a0), "r"(a1), "r"(a2), "r"(a3), "l"(db), "r"(scale_d));
}

#define DEVINL __device__ __forceinline__
#define HINT 4000
#define MWL mbar_wait_long
DEVINL void pin(uint32_t z) { asm volatile("{\n.reg .pred p;\nsetp.ne.u32 p, %0, 0;\nPIN:\n@p bra.uni PIN;\n}" ::"r"(z) : "memory"); }
DEVINL void wg_fence() { asm volatile("wgmma.fence.sync.aligned;" ::: "memory"); }
DEVINL void wg_commit() { asm volatile("wgmma.commit_group.sync.aligned;" ::: "memory"); }
template <int N> DEVINL void wg_wait() { asm volatile("wgmma.wait_group.sync.aligned %0;" ::"n"(N) : "memory"); }
DEVINL uint64_t mkdesc(uint32_t addr, uint32_t lbo, uint32_t sbo, int sw) {
  return (uint64_t)((addr & 0x3FFFF) >> 4) | ((uint64_t)(lbo >> 4) << 16) | ((uint64_t)(sbo >> 4) << 32) | ((uint64_t)sw << 62);
}
DEVINL void mbar_arrive(uint32_t bar) { asm volatile("mbarrier.arrive.shared::cta.b64 _, [%0];" ::"r"(bar) : "memory"); }
DEVINL bool mbar_try(uint32_t bar, uint32_t parity) {
  uint32_t ok;
  asm volatile("{\n.reg .pred p;\nmbarrier.try_wait.parity.shared::cta.b64 p, [%1], %2;\nselp.u32 %0, 1, 0, p;\n}" : "=r"(ok) : "r"(bar), "r"(parity) : "memory");
  return ok;
}
DEVINL bool mbar_test(uint32_t bar, uint32_t parity) {
  uint32_t ok;
  asm volatile("{\n.reg .pred p;\nmbarrier.test_wait.parity.shared::cta.b64 p, [%1], %2;\nselp.u32 %0, 1, 0, p;\n}" : "=r"(ok) : "r"(bar), "r"(parity) : "memory");
  return ok;
}
DEVINL void mbar_hint(uint32_t bar, uint32_t parity) {
#pragma unroll 1
  for (uint32_t n = 0; n < 16u; n++) if (mbar_try(bar, parity)) break;
}
DEVINL void mbar_wait(uint32_t bar, uint32_t parity) {
#pragma unroll 1
  for (uint32_t n = 0; n < 100000u; n++) if (mbar_try(bar, parity)) break;
}
DEVINL void mbar_wait_long(uint32_t bar, uint32_t parity) {
#pragma unroll 1
  for (uint32_t n = 0; n < 100000u; n++) {
    uint32_t ok;
    asm volatile("{\n.reg .pred p;\nmbarrier.try_wait.parity.shared::cta.b64 p, [%1], %2, %3;\nselp.u32 %0, 1, 0, p;\n}" : "=r"(ok) : "r"(bar), "r"(parity), "r"(HINT) : "memory");
    if (ok) break;
  }
}
#define EL(txt) "{\n.reg .pred pe;\nelect.sync _|pe, 0xffffffff;\n@pe " txt "\n}"
DEVINL void e_expect_tx(uint32_t bar, uint32_t bytes) { asm volatile(EL("mbarrier.arrive.expect_tx.shared::cta.b64 _, [%0], %1;") ::"r"(bar), "r"(bytes) : "memory"); }
DEVINL void e_init(uint32_t bar, uint32_t cnt) { asm volatile(EL("mbarrier.init.shared::cta.b64 [%0], %1;") ::"r"(bar), "r"(cnt) : "memory"); }
DEVINL void e_arrive(uint32_t bar) { asm volatile(EL("mbarrier.arrive.shared::cta.b64 _, [%0];") ::"r"(bar) : "memory"); }
DEVINL void e_red(uint32_t* p) { asm volatile(EL("red.release.gpu.global.add.u32 [%0], 1;") ::"l"(p) : "memory"); }
DEVINL void e_red_relaxed(uint32_t* p) { asm volatile(EL("red.relaxed.gpu.global.add.u32 [%0], 1;") ::"l"(p) : "memory"); }
DEVINL void tma_ld(uint32_t dst, const CUtensorMap* m, int c0, int c1, uint32_t bar) {
  asm volatile(EL("cp.async.bulk.tensor.2d.shared::cluster.global.mbarrier::complete_tx::bytes [%0], [%1, {%3, %4}], [%2];")
               ::"r"(dst), "l"(m), "r"(bar), "r"(c0), "r"(c1) : "memory");
}
DEVINL void tma_ld3(uint32_t dst, const CUtensorMap* m, int c0, int c1, int c2, uint32_t bar) {
  asm volatile(EL("cp.async.bulk.tensor.3d.shared::cluster.global.mbarrier::complete_tx::bytes [%0], [%1, {%3, %4, %5}], [%2];")
               ::"r"(dst), "l"(m), "r"(bar), "r"(c0), "r"(c1), "r"(c2) : "memory");
}
DEVINL void tma_ld5(uint32_t dst, const CUtensorMap* m, int c2, int c3, int c4, uint32_t bar) {
  asm volatile(EL("cp.async.bulk.tensor.5d.shared::cluster.global.mbarrier::complete_tx::bytes [%0], [%1, {0, 0, %3, %4, %5}], [%2];")
               ::"r"(dst), "l"(m), "r"(bar), "r"(c2), "r"(c3), "r"(c4) : "memory");
}
DEVINL void tma_ld_mc(uint32_t dst, const CUtensorMap* m, int c0, int c1, uint32_t bar) {
  asm volatile(EL("cp.async.bulk.tensor.2d.shared::cluster.global.mbarrier::complete_tx::bytes.multicast::cluster [%0], [%1, {%3, %4}], [%2], %5;")
               ::"r"(dst), "l"(m), "r"(bar), "r"(c0), "r"(c1), "h"((uint16_t)3) : "memory");
}
DEVINL void e_arrive_both(uint32_t bar) {
  asm volatile("{\n.reg .pred pe;\n.reg .b32 r0, r1;\nelect.sync _|pe, 0xffffffff;\nmapa.shared::cluster.u32 r0, %0, 0;\nmapa.shared::cluster.u32 r1, %0, 1;\n"
               "@pe mbarrier.arrive.shared::cluster.b64 _, [r0];\n@pe mbarrier.arrive.shared::cluster.b64 _, [r1];\n}" ::"r"(bar) : "memory");
}
DEVINL void push_peer(uint32_t dst, uint32_t src, uint32_t bar, uint32_t peer) {
  asm volatile("{\n.reg .pred pe;\n.reg .b32 d, b;\nelect.sync _|pe, 0xffffffff;\nmapa.shared::cluster.u32 d, %0, %3;\nmapa.shared::cluster.u32 b, %2, %3;\n"
               "@pe cp.async.bulk.shared::cluster.shared::cta.mbarrier::complete_tx::bytes [d], [%1], 16384, [b];\n}" ::"r"(dst), "r"(src), "r"(bar), "r"(peer) : "memory");
}
DEVINL void tma_st(const CUtensorMap* m, int c0, int c1, uint32_t src) {
  asm volatile(EL("cp.async.bulk.tensor.2d.global.shared::cta.bulk_group [%0, {%2, %3}], [%1];") ::"l"(m), "r"(src), "r"(c0), "r"(c1) : "memory");
}
DEVINL void bulk_commit() { asm volatile("cp.async.bulk.commit_group;" ::: "memory"); }
template <int N> DEVINL void bulk_wait_n() { asm volatile("cp.async.bulk.wait_group %0;\nbar.warp.sync 0xffffffff;" ::"n"(N) : "memory"); }
DEVINL void l2_prefetch(const void* g, uint32_t bytes) { asm volatile(EL("cp.async.bulk.prefetch.L2.global [%0], %1;") ::"l"(g), "r"(bytes) : "memory"); }
DEVINL void fence_async_smem() { asm volatile("fence.proxy.async.shared::cta;" ::: "memory"); }
DEVINL void fence_async_gl() { asm volatile("fence.proxy.async.global;" ::: "memory"); }
DEVINL void cluster_wait() { asm volatile("barrier.cluster.wait.aligned;" ::: "memory"); }
DEVINL void bar_sync(int id, int n) { asm volatile("bar.sync %0, %1;" ::"r"(id), "r"(n) : "memory"); }
DEVINL void bar_arrive(int id, int n) { asm volatile("bar.arrive %0, %1;" ::"r"(id), "r"(n) : "memory"); }
DEVINL uint32_t ld_acquire(const uint32_t* p) { uint32_t v; asm volatile("ld.acquire.gpu.global.u32 %0, [%1];" : "=r"(v) : "l"(p) : "memory"); return v; }
DEVINL void watch(const uint32_t* p, uint32_t target, uint32_t all, uint32_t tag, uint32_t slot) {
  uint32_t seen = 0;
#pragma unroll 1
  for (uint32_t n = 0; n < 200000u && seen != all; n++) {
    const uint32_t m = __ballot_sync(~0u, (int)(ld_acquire(p) - target) >= 0) & all;
    if (m != seen) { seen = m; asm volatile("st.release.cta.shared.u32 [%0], %1;" ::"r"(slot), "r"(tag << 16 | m) : "memory"); }
  }
}
template <bool RELAXED = false> DEVINL void await_bit(uint32_t slot, uint32_t tag, int j, uint32_t& rdy) {
  if ((rdy >> j) & 1) return;
#pragma unroll 1
  for (uint32_t n = 0; n < 8000000u; n++) {
    uint32_t v;
    asm volatile("ld.acquire.cta.shared.u32 %0, [%1];" : "=r"(v) : "r"(slot) : "memory");
    if ((v >> 16) == tag && ((v >> j) & 1)) { rdy = v; break; }
    if (RELAXED) __nanosleep(200);
  }
  asm volatile("fence.proxy.async.global;" ::: "memory");
}
DEVINL void poll_ge(const uint32_t* p, uint32_t target) {
#pragma unroll 1
  for (uint32_t n = 0; n < 200000u; n++) if (__all_sync(~0u, (int)(ld_acquire(p) - target) >= 0)) break;
}
DEVINL int lane_id() { int v; asm volatile("mov.u32 %0, %%laneid;" : "=r"(v)); return v; }
__host__ DEVINL int remap(int v) {
  const int c = v >> 1, u = c - 36, r = (u * 37) >> 8;
  const int L = max(c - 4 + max(r + 1, 0), (c - 4) >> 31 & (32 + 8 * c));
  return 2 * L + (v & 1);
}
DEVINL int block_id() { int v; asm volatile("mov.u32 %0, %%ctaid.x;" : "=r"(v)); return v; }
#define cta_id() prm.map[block_id()]
#define IDS() const int lane = lane_id(), b = cta_id(), bm = b >> 4, bn = b & 15, rank = b & 1, pm = 2 * bm + (bn >> 3), pn = bn & 7, po = pm & 1; \
  (void)lane; (void)bm; (void)bn; (void)rank; (void)pm; (void)pn; (void)po
DEVINL void st_tagged(unsigned long long* p, uint32_t v, uint32_t tag) {
  asm volatile("{\n.reg .b64 t;\nmov.b64 t, {%1, %2};\nst.relaxed.gpu.global.b64 [%0], t;\n}" ::"l"(p), "r"(v), "r"(tag) : "memory");
}
DEVINL float ex2(float x) { float y; asm("ex2.approx.ftz.f32 %0, %1;" : "=f"(y) : "f"(x)); return y; }
DEVINL float rcp(float x) { float y; asm("rcp.approx.ftz.f32 %0, %1;" : "=f"(y) : "f"(x)); return y; }
DEVINL uint32_t pack2(float lo, float hi) { uint32_t r; asm("cvt.rn.bf16x2.f32 %0, %1, %2;" : "=r"(r) : "f"(hi), "f"(lo)); return r; }
DEVINL float bf_lo(uint32_t w) { return __uint_as_float(w << 16); }
DEVINL float bf_hi(uint32_t w) { return __uint_as_float(w & 0xFFFF0000u); }
DEVINL float bf_round(float x) { return bf_lo(pack2(x, 0.f)); }
DEVINL uint32_t add_bf16x2(uint32_t a, uint32_t b) { uint32_t r; asm("add.rn.bf16x2 %0, %1, %2;" : "=r"(r) : "r"(a), "r"(b)); return r; }
DEVINL void stsm4(uint32_t addr, uint32_t a, uint32_t b, uint32_t c, uint32_t d) {
  asm volatile("stmatrix.sync.aligned.m8n8.x4.shared.b16 [%0], {%1, %2, %3, %4};" ::"r"(addr), "r"(a), "r"(b), "r"(c), "r"(d) : "memory");
}
DEVINL void ldsm4(uint32_t addr, uint32_t (&r)[4]) {
  asm volatile("ldmatrix.sync.aligned.m8n8.x4.shared.b16 {%0, %1, %2, %3}, [%4];" : "=r"(r[0]), "=r"(r[1]), "=r"(r[2]), "=r"(r[3]) : "r"(addr) : "memory");
}
DEVINL void ldsm4t(uint32_t addr, uint32_t (&r)[4]) {
  asm volatile("ldmatrix.sync.aligned.m8n8.x4.trans.shared.b16 {%0, %1, %2, %3}, [%4];" : "=r"(r[0]), "=r"(r[1]), "=r"(r[2]), "=r"(r[3]) : "r"(addr) : "memory");
}
DEVINL void sts128(uint32_t addr, uint32_t a, uint32_t b, uint32_t c, uint32_t d) {
  asm volatile("st.shared.v4.b32 [%0], {%1, %2, %3, %4};" ::"r"(addr), "r"(a), "r"(b), "r"(c), "r"(d) : "memory");
}
DEVINL float4 lds128f(uint32_t addr) { float4 v; asm volatile("ld.shared.v4.f32 {%0, %1, %2, %3}, [%4];" : "=f"(v.x), "=f"(v.y), "=f"(v.z), "=f"(v.w) : "r"(addr) : "memory"); return v; }
DEVINL float lds32f(uint32_t addr) { float v; asm volatile("ld.shared.f32 %0, [%1];" : "=f"(v) : "r"(addr) : "memory"); return v; }
DEVINL float2 lds64f(uint32_t addr) { float2 v; asm volatile("ld.shared.v2.f32 {%0, %1}, [%2];" : "=f"(v.x), "=f"(v.y) : "r"(addr) : "memory"); return v; }
DEVINL void mma16816(float (&d)[4], uint32_t a0, uint32_t a1, uint32_t a2, uint32_t a3, uint32_t b0, uint32_t b1) {
  asm("mma.sync.aligned.m16n8k16.row.col.f32.bf16.bf16.f32 {%0, %1, %2, %3}, {%4, %5, %6, %7}, {%8, %9}, {%0, %1, %2, %3};"
               : "+f"(d[0]), "+f"(d[1]), "+f"(d[2]), "+f"(d[3]) : "r"(a0), "r"(a1), "r"(a2), "r"(a3), "r"(b0), "r"(b1));
}
DEVINL void mma1688(float (&d)[4], uint32_t a0, uint32_t a1, uint32_t b0) {
  asm("mma.sync.aligned.m16n8k8.row.col.f32.bf16.bf16.f32 {%0, %1, %2, %3}, {%4, %5}, {%6}, {%0, %1, %2, %3};"
               : "+f"(d[0]), "+f"(d[1]), "+f"(d[2]), "+f"(d[3]) : "r"(a0), "r"(a1), "r"(b0));
}
DEVINL void mma16816h(float (&d)[4], uint32_t a0, uint32_t a1, uint32_t a2, uint32_t a3, uint32_t b0, uint32_t b1) {
  asm("mma.sync.aligned.m16n8k16.row.col.f32.f16.f16.f32 {%0, %1, %2, %3}, {%4, %5, %6, %7}, {%8, %9}, {%0, %1, %2, %3};"
               : "+f"(d[0]), "+f"(d[1]), "+f"(d[2]), "+f"(d[3]) : "r"(a0), "r"(a1), "r"(a2), "r"(a3), "r"(b0), "r"(b1));
}
template <int N> DEVINL void fence_regs(uint32_t (&d)[N]) {
#pragma unroll
  for (int i = 0; i < N; i++) asm volatile("" : "+r"(d[i])::"memory");
}
template <int N> DEVINL void fence_regs(float (&d)[N]) {
#pragma unroll
  for (int i = 0; i < N; i++) asm volatile("" : "+f"(d[i])::"memory");
}

__device__ __align__(1024) bf16 g_xs[2048 * 1024];
__device__ __align__(1024) bf16 g_os[2048 * 1024];
__device__ __align__(1024) bf16 g_k[32 * 2048 * 32];
__device__ __align__(1024) bf16 g_v[32 * 2048 * 32];
__device__ __align__(128) float2 g_stats[8 * 2048];
__device__ __align__(16) float g_csp[2 * 16 * 8 * 192];
__device__ __align__(128) float g_kn[2 * 128 * 32];
__device__ unsigned long long g_halo[2 * 128 * 32 * 32];
__device__ __align__(128) uint32_t g_cnt[256 * 32];
__device__ uint32_t g_epoch;

DEVINL uint32_t* cnt_x(int l, int bm) { return g_cnt + (l * 8 + bm) * 32; }
DEVINL uint32_t* cnt_o(int l, int pm, int h) { return g_cnt + (32 + (l * 16 + pm) * 2 + h) * 32; }
DEVINL uint32_t* cnt_kv(int lb, int bn) { return g_cnt + (160 + lb * 16 + bn) * 32; }
DEVINL uint32_t* cnt_ad(int bn) { return g_cnt + (192 + bn) * 32; }
DEVINL uint32_t* cnt_cs(int t, int bn) { return g_cnt + (208 + t * 16 + bn) * 32; }

DEVINL int qord(int i, int l, int pn) { return l == 0 ? i : i < 4 ? ((2 * pn) ^ (i & 2)) + (i & 1) : i - 4 < 2 * (pn & 6) ? i - 4 : i; }
struct Params {
  CUtensorMap m[17];
  const bf16* x0;
  const bf16* wq[2];
  uint32_t* epoch;
  uint32_t zero;
  int map[128];
};
enum { M_X0A = 0, M_XSA, M_WQA, M_WQB, M_WOA, M_WOB, M_OS, M_K, M_V, M_X0R, M_XSR, M_XSO, M_OUT, M_XST, M_X0H, M_K4, M_V4, M_COUNT };

constexpr uint32_t QSTG = 57344;
constexpr uint32_t T0 = 65536, TSTG = 32768;
constexpr uint32_t ONES = 229376;
constexpr uint32_t PSTG = 32768, RES = 196608;
constexpr uint32_t ASC = 17408;
constexpr uint32_t RSTD = 229376, MEAN = 230400, COLS = 230912, KMAX = 231680, B_QD = 231688, BARS = 232192, SMEM_BYTES = 232448;
constexpr uint32_t B_QF = BARS, B_QE = BARS + 32, B_TF = BARS + 64, B_TE = BARS + 96, B_PF = BARS + 128, B_PE = BARS + 176,
                   B_RF = BARS + 224, W_X = BARS + 232, W_O = BARS + 236, B_QL = BARS + 240, B_PA = BARS + 248;
enum { NB_ST = 1, NB_KV = 2  , NB_DONE = 3, NB_SC = 4, NB_SIG = 5  , NB_KN = 9  , NB_X = 11, NB_HALO = 12  , NB_X0 = 15 };

DEVINL uint32_t pslot_b(uint32_t s, int l) { return ((((l & 1) ? 0x320415u : 0x468795u) >> (4 * s)) & 15) * 16384u; }
DEVINL uint32_t pslot_a(uint32_t s, int l) { return ((((l & 1) ? 0xBA7896u : 0x32DCBAu) >> (4 * s)) & 15) * 16384u; }

#define G1 2
#define G2 0
#define G3 2
#define KC (11 + 2 * wg)
#define NA2 2
#define RESI 9
#define PERHEAD 1
#define LA 1
#define LB 1
#define PFETCH 0
#define NQ 32
#define OA 0x10
#define OB 0x10
#define LAG 2
#define QK_A wgmma_m64n32k16_rs_nb_h
#define QK_B wgmma_m64n32k16_rs_nb_hh
constexpr float QSCALE = 0.17677669529663687f * 1.4426950408889634f;

DEVINL uint32_t hfma2(uint32_t a, uint32_t b, uint32_t c) { uint32_t r; asm("fma.rn.f16x2 %0, %1, %2, %3;" : "=r"(r) : "r"(a), "r"(b), "r"(c)); return r; }
DEVINL uint32_t pack2h(float lo, float hi) { uint32_t r; asm("cvt.rn.f16x2.f32 %0, %1, %2;" : "=r"(r) : "f"(hi), "f"(lo)); return r; }
DEVINL uint32_t h2_to_bf2(uint32_t h) {
  float a, b;
  asm("{\n.reg .b16 l, h;\nmov.b32 {l, h}, %2;\ncvt.f32.f16 %0, l;\ncvt.f32.f16 %1, h;\n}" : "=f"(a), "=f"(b) : "r"(h));
  return pack2(a, b);
}
DEVINL uint32_t exp2_h2(uint32_t s) {
  const uint32_t r = hfma2(s, 0x00800080u, 0x007E007Eu);
  const uint32_t g = hfma2(hfma2(r, 0xF800F800u, 0x33FD33FDu), 0x44004400u, s);
  return r * 128u + hfma2(hfma2(g, g, 0x0DE10DE1u), g, 0x00300030u);
}
constexpr uint32_t NOT_F16 = 0x7FC00000u, K_LO = 0x35000000u  ;
DEVINL uint32_t f16_class(uint32_t norm2, uint32_t lo) { return norm2 - lo > 0x4E800000u - lo ? NOT_F16 : norm2; }

DEVINL void attn_slow(const uint32_t (&q)[8], float up, int head, const float* kn, float (&res)[20], int lane) {
  const int g = lane >> 2, qd = lane & 3;
  const bf16* kb = g_k + (size_t)head * 2048 * 32;
  const bf16* vb = g_v + (size_t)head * 2048 * 32;
  float o[4][4], m0 = -INFINITY, m1 = -INFINITY, l0 = 0.f, l1 = 0.f;
#pragma unroll
  for (int j = 0; j < 4; j++) { o[j][0] = o[j][1] = o[j][2] = o[j][3] = 0.f; }
#pragma unroll 1
  for (int k0 = 0; k0 < 2048; k0 += 16) {
    float s[2][4];
    const bool kh = __float_as_uint(__ldcg(kn + (k0 >> 8) * 32 + ((k0 >> 6) & 1) * 8 + ((k0 >> 7) & 1) * 4 + ((k0 >> 4) & 3))) != NOT_F16;
#pragma unroll
    for (int nt = 0; nt < 2; nt++) {
      s[nt][0] = s[nt][1] = s[nt][2] = s[nt][3] = 0.f;
      const uint32_t* kp = (const uint32_t*)(kb + (size_t)(k0 + nt * 8 + g) * 32) + qd;
      uint32_t kf[4];
#pragma unroll
      for (int i = 0; i < 4; i++) { kf[i] = __ldcg(kp + 4 * i); if (kh) kf[i] = h2_to_bf2(kf[i]); }
      mma16816(s[nt], q[0], q[1], q[2], q[3], kf[0], kf[1]);
      mma16816(s[nt], q[4], q[5], q[6], q[7], kf[2], kf[3]);
      s[nt][0] *= up; s[nt][1] *= up; s[nt][2] *= up; s[nt][3] *= up;
    }
    float a0 = fmaxf(fmaxf(s[0][0], s[0][1]), fmaxf(s[1][0], s[1][1]));
    float a1 = fmaxf(fmaxf(s[0][2], s[0][3]), fmaxf(s[1][2], s[1][3]));
    a0 = fmaxf(a0, __shfl_xor_sync(~0u, a0, 1)); a0 = fmaxf(a0, __shfl_xor_sync(~0u, a0, 2));
    a1 = fmaxf(a1, __shfl_xor_sync(~0u, a1, 1)); a1 = fmaxf(a1, __shfl_xor_sync(~0u, a1, 2));
    const float n0 = fmaxf(m0, a0), n1 = fmaxf(m1, a1);
    const float c0 = (m0 == n0) ? 1.f : ex2(m0 - n0), c1 = (m1 == n1) ? 1.f : ex2(m1 - n1);
    m0 = n0; m1 = n1;
    const uint32_t p0 = pack2(ex2(s[0][0] - n0), ex2(s[0][1] - n0)), p1 = pack2(ex2(s[0][2] - n1), ex2(s[0][3] - n1));
    const uint32_t p2 = pack2(ex2(s[1][0] - n0), ex2(s[1][1] - n0)), p3 = pack2(ex2(s[1][2] - n1), ex2(s[1][3] - n1));
    l0 = l0 * c0 + bf_lo(p0) + bf_hi(p0) + bf_lo(p2) + bf_hi(p2);
    l1 = l1 * c1 + bf_lo(p1) + bf_hi(p1) + bf_lo(p3) + bf_hi(p3);
#pragma unroll
    for (int j = 0; j < 4; j++) {
      o[j][0] *= c0; o[j][1] *= c0; o[j][2] *= c1; o[j][3] *= c1;
      const unsigned short* vp = (const unsigned short*)(vb + (size_t)(k0 + 2 * qd) * 32 + j * 8 + g);
      const uint32_t b0 = (uint32_t)__ldcg(vp) | ((uint32_t)__ldcg(vp + 32) << 16);
      const uint32_t b1 = (uint32_t)__ldcg(vp + 256) | ((uint32_t)__ldcg(vp + 288) << 16);
      mma16816(o[j], p0, p1, p2, p3, b0, b1);
    }
  }
  l0 += __shfl_xor_sync(~0u, l0, 1); l0 += __shfl_xor_sync(~0u, l0, 2);
  l1 += __shfl_xor_sync(~0u, l1, 1); l1 += __shfl_xor_sync(~0u, l1, 2);
#pragma unroll
  for (int j = 0; j < 4; j++) { res[4 * j] = o[j][0]; res[4 * j + 1] = o[j][1]; res[4 * j + 2] = o[j][2]; res[4 * j + 3] = o[j][3]; }
  res[16] = l0; res[18] = l1;
}

__global__ void __cluster_dims__(2, 1, 1) __launch_bounds__(384, 1) fused_kernel(const __grid_constant__ Params prm) {
  extern __shared__ __align__(1024) char smem[];
  const uint32_t sb = (uint32_t)__cvta_generic_to_shared(smem);
  const int tid = threadIdx.x;
  const int wid = __shfl_sync(0xffffffffu, tid >> 5, 0), wg = wid >> 2, w = wid & 3;
  const int bm = remap(blockIdx.x) >> 4, bn = remap(blockIdx.x) & 15;
  auto first_tile = [&](int kt) {
    e_expect_tx(sb + B_QF + 8 * kt, QSTG);
    tma_ld(sb + kt * QSTG, &prm.m[M_X0A], kt * 64, bm * 256, sb + B_QF + 8 * kt);
    tma_ld3(sb + kt * QSTG + 32768, &prm.m[M_WQA], bn * 64, kt * 64, 0, sb + B_QF + 8 * kt);
  };
  if (wid == 8) {
    e_init(sb + B_QF, 1);
    asm volatile("fence.mbarrier_init.release.cluster;" ::: "memory");
    first_tile(0);
  }
  if (wid < 8) {
#pragma unroll
    for (int i = 0; i < 4; i++) {
      const uint32_t cnt = (uint32_t)((i == 0 ? 0x14112140 : i == 1 ? 0x04112141 : i == 2 ? 0x14412141 : 0x24412141) >> (4 * wid)) & 7;
      if (cnt) e_init(sb + BARS + 32 * wid + 8 * i, cnt);
    }
    if (wid == 0 || wid == 7) e_init(sb + B_QD + (wid & 1) * 8, 1);
    if (tid == 255) *(uint2*)(smem + W_X) = make_uint2(0u, 0u);
    asm volatile("fence.mbarrier_init.release.cluster;" ::: "memory");
  }
  const uint32_t epoch = *(volatile uint32_t*)prm.epoch;
  __syncthreads();
  asm volatile("barrier.cluster.arrive.relaxed.aligned;" ::: "memory");

  if (wg == 2) {
    asm volatile("setmaxnreg.dec.sync.aligned.u32 56;");
    const uint32_t ep1 = epoch + 1;
    if (w == 0) {
      first_tile(1);
      mbar_wait(sb + B_QF, 0);
      first_tile(2); first_tile(3);
#pragma unroll 1
      for (int kt = 4; kt < 16; kt++) l2_prefetch(prm.wq[0] + kt * 196608 + blockIdx.x * 1536, 3072);
      cluster_wait();
#pragma unroll 1
      for (int l = 0; l < 4; l++) {
        IDS();
        const CUtensorMap* mw = &prm.m[M_WQA + (l & 1)];
        const CUtensorMap* mh = &prm.m[l == 0 ? M_X0H : M_XSO];
        const CUtensorMap* mo = &prm.m[M_WOA + (l & 1)];
        auto q_b = [&](int i) {
          const int s = i & 3;
          mbar_wait(sb + B_QE + 8 * s, ((i >> 2) & 1) ^ 1);
          e_expect_tx(sb + B_QF + 8 * s, QSTG);
          tma_ld3(sb + s * QSTG + 32768, mw, bn * 64, qord(i, l, pn) * 64, 0, sb + B_QF + 8 * s);
        };
        uint32_t rdy = l ? 0u : ~0u;
        auto q_a = [&](int i) {
          const int kt = qord(i, l, pn);
          await_bit(sb + W_X, l, kt >> 1, rdy);
          tma_ld_mc(sb + (i & 3) * QSTG + rank * 16384, mh, kt * 64, bm * 256 + rank * 128, sb + B_QF + 8 * (i & 3));
        };
        if (l > 0) {
#pragma unroll 1
          for (int i = 0; i < 4; i++) {
            const int kt = qord(i, l, pn);
            await_bit(sb + W_X, l, kt >> 1, rdy);
            e_expect_tx(sb + B_QF + 8 * i, 16384);
            tma_ld(sb + i * QSTG + (po ^ 1) * 16384, &prm.m[M_XSO], kt * 64, (pm ^ 1) * 128, sb + B_QF + 8 * i);
          }
        }
#pragma unroll 1
        for (int i = 4; i < 16; i++) {
          q_b(i); q_a(i);
        }
        if (l & 1) {
          if (l == 3) poll_ge(cnt_ad(bn), ep1 * 16);
          const int krow = 2 * bn * 2048 + bm * 256;
          uint32_t* kvc = cnt_kv(l >> 1, bn);
#pragma unroll 1
          for (int m = 1; m >= 0; m--) {
            bar_sync(m ? NB_ST : NB_KV, 288);
#pragma unroll
            for (int i = 0; i < 4; i++) tma_st(&prm.m[M_K4 + (i >> 1)], 0, krow + (i & 1) * 128 + m * 64, sb + T0 + i * 8192 + m * 4096);
            if (m) {
              sts128(sb + ONES + lane * 32, 0x3f803f80u, 0x3f803f80u, 0x3f803f80u, 0x3f803f80u);
              sts128(sb + ONES + lane * 32 + 16, 0x3f803f80u, 0x3f803f80u, 0x3f803f80u, 0x3f803f80u);
              fence_async_smem();
              __syncwarp();
            }
          }
          e_arrive(sb + B_TF);
          bulk_commit(); bulk_wait_n<0>();
          e_red(kvc + bm);
          bar_sync(NB_KV + 12, 288);
          tma_st(&prm.m[M_K], 0, krow + 2048, sb);
          tma_st(&prm.m[M_V], 0, krow + 2048, sb + 16384);
          bulk_commit();
          uint32_t seen = 0;
#pragma unroll 1
          for (int it = 1; it < 16; it++) {
            const int s = it & 3, blk = it;
            if (it == 4) { bulk_wait_n<0>(); e_red(kvc + bm); }
            if (it == 12) { e_expect_tx(sb + B_RF, 32768); tma_ld3(sb + RES, &prm.m[M_XSR], 0, pm * 128, 2 * pn, sb + B_RF); }
            if (it == 2 || it == 3) mbar_wait(sb + B_TF + 8 * (it - 1), 0);
            MWL(sb + B_TE + 8 * s, ((it >> 2) & 1) ^ 1);
            if (it < 8) {
#pragma unroll 1
              for (uint32_t n = 0; n < 200000u && !((seen >> it) & 1); n++)
                seen = __ballot_sync(~0u, (int)(ld_acquire(kvc + ((bm + lane) & 7)) - (ep1 * 2 - 1)) >= 0);
              fence_async_gl();
            } else if (it == 8) { poll_ge(kvc + (lane & 7), ep1 * 2); fence_async_gl(); bar_arrive(NB_HALO, 64); }
            else if (it == 15) bar_arrive(NB_HALO + 1, 64);
            const int row = (2 * bn + (it >> 3)) * 2048 + ((bm + blk) & 7) * 256;
            e_expect_tx(sb + B_TF + 8 * s, 32768);
            tma_ld(sb + T0 + s * TSTG, &prm.m[M_K], 0, row, sb + B_TF + 8 * s);
            tma_ld(sb + T0 + s * TSTG + 16384, &prm.m[M_V], 0, row, sb + B_TF + 8 * s);
          }
        }
        auto p_b = [&](int i, uint32_t s, uint32_t par) {
          mbar_wait(sb + B_PE + 8 * s, par ^ 1);
          e_expect_tx(sb + B_PF + 8 * s, PSTG);
          tma_ld5(sb + pslot_b(s, l), mo, i >> 3, 2 * (i & 7), 2 * pn, sb + B_PF + 8 * s);
        };
        auto p_a = [&](int i, uint32_t s) {
          await_bit(sb + W_O, l + 1, i, rdy);
          tma_ld_mc(sb + pslot_a(s, l) + rank * 8192, &prm.m[M_OS], i * 64, pm * 128 + rank * 64, sb + B_PF + 8 * s);
        };
        auto p_a2 = [&](int i) {
          await_bit(sb + W_O, l + 1, i, rdy);
          tma_ld(sb + pslot_a(i, l), &prm.m[M_OS], i * 64, pm * 128, sb + B_PF + 8 * i);
          tma_ld(sb + pslot_a(i, l) + 8192, &prm.m[M_OS], i * 64, pm * 128 + 64, sb + B_PF + 8 * i);
        };
        rdy = 0;
        if (l & 1) {
#pragma unroll 1
          for (int u = 0; u < 6; u++) { const int i = (0x205413 >> (4 * u)) & 7; if (u == 4) MWL(sb + B_TE, 1); p_b(i, i, i < 4 ? 1 : 0); }
#pragma unroll 1
          for (int u = 0; u < 6; u++) {
            const int i = (0x542130 >> (4 * u)) & 7;
            if (!(u & 1)) MWL(sb + B_TE + 8 + 4 * u, 1);
            p_a2(i);
          }
        } else {
#pragma unroll 1
          for (int u = 0; u < 5; u++) { const int i = (0x32140 >> (4 * u)) & 7; if (!(u & 5)) mbar_wait(sb + B_QE + 8 + 4 * u, 1); p_b(i, i, 0); }
          mbar_wait(sb + B_QE + 24, 1);
#pragma unroll 1
          for (int i = 0; i < 4; i++) { if (i < NA2) p_a2(i); else p_a(i, i); }
          bar_sync(NB_DONE, 96);
          e_arrive_both(sb + B_PA);
          p_b(5, 5, 0);
          mbar_wait(sb + B_PA, (l >> 1) & 1);
          p_a(4, 4); p_a(5, 5);
        }
        uint32_t s = 0, lap = 1;
#pragma unroll 1
        for (int i = 6; i < 16; i++) {
          if (i == RESI && !(l & 1)) { e_expect_tx(sb + B_RF, 32768); tma_ld3(sb, &prm.m[l == 0 ? M_X0R : M_XSR], 0, pm * 128, 2 * pn, sb + B_RF); }
          p_b(i, s, ((s < 4 ? l : 0) + lap) & 1);
          p_a(i, s);
          if (++s == 6) { s = 0; lap++; }
        }
        const CUtensorMap* mn = &prm.m[M_WQA + ((l + 1) & 1)];
        if (l < 3) {
          mbar_wait(sb + B_PE + 8 * 4, 1); mbar_wait(sb + B_PE + 8 * 5, 1);
          tma_ld3(sb + 32768, mn, bn * 64, 2 * pn * 64, 0, sb + B_QL);
          mbar_wait(sb + B_PE + 8 * 0, l & 1);
          tma_ld3(sb + QSTG + 32768, mn, bn * 64, (2 * pn + 1) * 64, 0, sb + B_QL);
          mbar_wait(sb + B_PE + 8 * 1, l & 1);
          e_expect_tx(sb + B_QD, 40960);
          tma_ld3(sb + 2 * QSTG + 32768, mn, bn * 64, ((2 * pn) ^ 2) * 64, 0, sb + B_QD);
          bar_sync(NB_X, 288);
          e_expect_tx(sb + B_QL, 49152);
          e_expect_tx(sb + B_QD + 8, 40960);
          tma_ld3(sb + 3 * QSTG + 32768, mn, bn * 64, (((2 * pn) ^ 2) + 1) * 64, 0, sb + B_QD + 8);
        }
      }
      if (blockIdx.x == 0 && lane_id() == 0) *(volatile uint32_t*)prm.epoch = ep1;
    } else {
      const int hw = w - 1;
      if (hw == 1 && lane_id() < M_COUNT) asm volatile("prefetch.tensormap [%0];" ::"l"(&prm.m[lane_id()]) : "memory");
      cluster_wait();
      mbar_wait(sb + B_QF, 0);
#pragma unroll 1
      for (int l = 0; l < 4; l++) {
        IDS();
        if (hw == 2 && l > 0) watch(cnt_x(l, bm) + (lane & 7), ep1 * 2, 0xFFu, l, sb + W_X);
        if (l == 0) {
#pragma unroll 1
          for (int r = 2 * hw; r < 16; r += 6) {
            const uint4* p = (const uint4*)(prm.x0 + (size_t)(b * 16 + r) * 1024) + lane;
            float s1[2] = {0.f, 0.f}, s2[2] = {0.f, 0.f};
#pragma unroll
            for (int i = 0; i < 8; i++) {
              const uint4 v = __ldg(p + 32 * i);
              const uint32_t u[4] = {v.x, v.y, v.z, v.w};
#pragma unroll
              for (int k = 0; k < 4; k++) { const float a = bf_lo(u[k]), c = bf_hi(u[k]); s1[i >> 2] += a + c; s2[i >> 2] = fmaf(a, a, fmaf(c, c, s2[i >> 2])); }
            }
#pragma unroll
            for (int o = 16; o; o >>= 1)
#pragma unroll
              for (int rr = 0; rr < 2; rr++) { s1[rr] += __shfl_xor_sync(~0u, s1[rr], o); s2[rr] += __shfl_xor_sync(~0u, s2[rr], o); }
            if (lane == 0) *(float4*)&g_stats[b * 16 + r] = make_float4(s1[0], s2[0], s1[1], s2[1]);
          }
        }
        if (l == 1) { uint32_t rdy = 0; await_bit<true>(sb + W_X, 1, pn, rdy); mbar_hint(sb + B_QF + 8, 0); }
        if (l < 2) {
          float cs[8];
#pragma unroll
          for (int i = 0; i < 8; i++) cs[i] = 0.f;
          const uint4* wp = (const uint4*)(prm.wq[l] + (size_t)(bm * 128 + (lane >> 3)) * 3072 + hw * 1024 + bn * 64) + (lane & 7);
#pragma unroll 8
          for (int i = 0; i < 32; i++) {
            const uint4 v = __ldg(wp + (size_t)i * 4 * 384);
            cs[0] += bf_lo(v.x); cs[1] += bf_hi(v.x); cs[2] += bf_lo(v.y); cs[3] += bf_hi(v.y);
            cs[4] += bf_lo(v.z); cs[5] += bf_hi(v.z); cs[6] += bf_lo(v.w); cs[7] += bf_hi(v.w);
          }
#pragma unroll
          for (int i = 0; i < 8; i++) { cs[i] += __shfl_xor_sync(~0u, cs[i], 8); cs[i] += __shfl_xor_sync(~0u, cs[i], 16); }
          if (lane < 8) {
            float4* d = (float4*)(g_csp + ((l * 16 + bn) * 8 + bm) * 192 + hw * 64 + lane * 8);
            d[0] = make_float4(cs[0], cs[1], cs[2], cs[3]); d[1] = make_float4(cs[4], cs[5], cs[6], cs[7]);
          }
          __syncwarp();
          asm volatile("fence.acq_rel.gpu;" ::: "memory");
          e_red_relaxed(cnt_cs(l, bn));
          if (l == 0) e_red_relaxed(cnt_x(0, bm) + pn);
          poll_ge(lane < 8 && l == 0 ? cnt_x(0, bm) + lane : cnt_cs(l, bn), ep1 * (lane < 8 && l == 0 ? 6 : 24));
        }
        if (l > 0) {
          uint32_t rdy = 0;
#pragma unroll 1
          for (int j = 0; j < 8; j++) await_bit<true>(sb + W_X, l, j, rdy);
        }
#pragma unroll 1
        for (int it = hw * 32 + lane; it < 176; it += 96) {
          const bool rows = it < 128;
          const float4* p = rows ? (const float4*)(g_stats + bm * 256) + it : (const float4*)(g_csp + ((l & 1) * 16 + bn) * 8 * 192) + (it - 128);
          const int stride = rows ? 1024 : 48, np = rows && l == 0 ? 1 : 8;
          float4 a = make_float4(0.f, 0.f, 0.f, 0.f);
#pragma unroll
          for (int k = 0; k < 8; k++) if (k < np) { const float4 v = __ldcg(p + k * stride); a.x += v.x; a.y += v.y; a.z += v.z; a.w += v.w; }
          if (rows) {
            const float m0 = a.x * (1.f / 1024.f), m1 = a.z * (1.f / 1024.f);
            const float v0 = fmaxf(a.y * (1.f / 1024.f) - m0 * m0, 0.f), v1 = fmaxf(a.w * (1.f / 1024.f) - m1 * m1, 0.f);
            const float r0 = __fdividef(1.f, bf_round(sqrtf(bf_round(bf_round(v0) + 1e-5f)))), r1 = __fdividef(1.f, bf_round(sqrtf(bf_round(bf_round(v1) + 1e-5f))));
            *(float2*)(smem + RSTD + it * 8) = make_float2(r0, r1);
            *(uint32_t*)(smem + MEAN + it * 4) = pack2(-m0, -m1);
          } else {
            float2* d = (float2*)(smem + COLS) + ((it - 128) >> 2) * 8 + (it & 1) * 4 + ((it >> 1) & 1);
            d[0] = make_float2(a.y, a.x); d[2] = make_float2(a.w, a.z);
          }
        }
        __syncwarp();
        if (lane == 0) asm volatile("red.release.cta.shared.add.u32 [%0], 0x100;" ::"r"(sb + W_X) : "memory");
        if (hw == 2) {
          if (!(l & 1)) {
            bar_sync(NB_ST, 288);
            const volatile unsigned long long* hp = g_halo + ((size_t)(l >> 1) * 128 + b - 16) * 1024 + lane;
#pragma unroll 1
            for (int h = 0; h < 2; h++) {
              uint32_t t[16];
#pragma unroll
              for (int i = 0; i < 16; i++) t[i] = 0;
#pragma unroll 1
              for (uint32_t n = bm ? 0 : 100000u; n < 100000u; n++) {
                uint32_t miss = 0;
#pragma unroll
                for (int i = 0; i < 16; i++) {
                  const unsigned long long v = hp[h * 512 + i * 32];
                  t[i] = (uint32_t)v; miss |= (uint32_t)(v >> 32) ^ ep1;
                }
                if (__all_sync(~0u, !miss)) break;
              }
              const uint32_t r = (lane & 7) + ((lane >> 3) & 1) * 8, rv = lane >> 2;
#pragma unroll
              for (int jj = 0; jj < 2; jj++) stsm4(sb + 2 * h * ASC + r * 64 + (((2 * jj + (lane >> 4)) ^ ((r >> 1) & 3)) << 4), t[4 * jj], t[4 * jj + 1], t[4 * jj + 2], t[4 * jj + 3]);
              const uint32_t ad = sb + (2 * h + 1) * ASC + rv * 64 + (((lane & 3) ^ ((rv >> 1) & 3)) << 4);
              sts128(ad, t[8], t[10], t[12], t[14]); sts128(ad + 512, t[9], t[11], t[13], t[15]);
              bar_arrive(NB_HALO + h, 64);
            }
          } else {
            bar_sync(NB_HALO, 64);
            const uint4* kp = (const uint4*)(g_kn + ((l >> 1) * 128 + bn * 8) * 32) + 2 * lane;
            const uint4 v = __ldcg(kp), u = __ldcg(kp + 1);
            const uint32_t mx = max(max(max(v.x, v.y), max(v.z, v.w)), max(max(u.x, u.y), max(u.z, u.w)));
            const uint32_t m0 = __reduce_max_sync(~0u, (lane & 2) ? 0u : mx), m1 = __reduce_max_sync(~0u, (lane & 2) ? mx : 0u);
            if (lane == 0) *(uint2*)(smem + KMAX) = make_uint2(m0, m1);
            __syncwarp();
            bar_arrive(NB_KN, 160); bar_arrive(NB_KN + 1, 160);
            bar_sync(NB_HALO + 1, 64);
            watch(cnt_o(l, pm, 0) + (lane & 7), ep1 * 2, 0xFFu, l + 1, sb + W_O);
          }
        } else {
          bar_sync(NB_SIG + 2 * hw, 160); bar_sync(NB_SIG + 2 * hw + 1, 160);
          if (!(l & 1)) bar_arrive(NB_DONE, 96);
          if (hw == (l & 1)) bar_arrive((l & 1) ? NB_DONE : NB_KN, 64);
          asm volatile("fence.acq_rel.gpu;" ::: "memory");
          e_red_relaxed(cnt_o(l, 2 * bm, hw) + (bn >> 1));
          e_red_relaxed(cnt_o(l, 2 * bm + 1, hw) + (bn >> 1));
          if (hw == 1 && l == 1) { e_red_relaxed(cnt_ad(bn)); e_red_relaxed(cnt_ad(bn)); }
        }
        if (hw == 2) { bar_sync((l & 1) ? NB_DONE : NB_KN, 64); watch(cnt_o(l, pm, (lane >> 3) & 1) + (lane & 7), ep1 * 2, 0xFFFFu, l + 1, sb + W_O); }
        if (hw < 2 && l < 3) {
          bar_sync(NB_X0, 320);
          if (hw == 0) {
            e_red(cnt_x(l + 1, bm) + pn);
          } else {
            mbar_wait(sb + B_PE + 8 * 3, l & 1);
            push_peer(sb + 2 * QSTG + po * 16384, sb + po * 16384, sb + B_QD, rank ^ 1);
            push_peer(sb + 3 * QSTG + po * 16384, sb + QSTG + po * 16384, sb + B_QD + 8, rank ^ 1);
          }
        }
      }
    }
  } else {
    asm volatile("setmaxnreg.inc.sync.aligned.u32 224;");
    const uint32_t zero = prm.zero;
    cluster_wait();
    const uint32_t ep1 = __shfl_sync(~0u, epoch + 1, 0);
#pragma unroll 1
    for (int l = 0; l < 4; l++) {
      {
        float acc[2][96];
#pragma unroll
        for (int i = 0; i < 96; i++) { acc[0][i] = 0.f; acc[1][i] = 0.f; }
        fence_regs(acc[0]); fence_regs(acc[1]);
        const bool early = l > 0 && wg == ((cta_id() >> 3) & 1);
#pragma unroll 1
        for (int kt = 0; kt < 14; kt++) {
          const int s = kt & 3;
          if (l > 0 && kt < 4 && kt != 1) mbar_wait(sb + (kt ? B_QD - 16 + 8 * kt : B_QL), (l + 1) & 1);
          if (!(early && kt < 4)) mbar_wait(sb + B_QF + 8 * s, (kt >> 2) & 1);
          const uint64_t da = mkdesc(sb + s * QSTG + wg * 16384, 16, 1024, 1), db = mkdesc(sb + s * QSTG + 32768, 8192, 1024, 1);
          wg_fence();
#pragma unroll
          for (int k = 0; k < 4; k++)
#pragma unroll
            for (int m = 0; m < 2; m++) wgmma_m64n192k16_ss_tb(acc[m], da + m * 512 + k * 2, db + k * 128, 1);
          wg_commit();
          wg_wait<1>();
          if (early && kt < 5) {
#pragma unroll 1
            for (int i = kt == 3 ? 0 : 3; i < kt; i++) { mbar_wait(sb + B_QF + 8 * i, 0); if (w == 0) e_arrive_both(sb + B_QE + 8 * i); }
          } else if (kt > 0 && w == 0) e_arrive_both(sb + B_QE + 8 * ((kt - 1) & 3));
          if (kt == KC) {
#pragma unroll 1
            for (uint32_t n = 0; n < 4000000u; n++) {
              uint32_t v;
              asm volatile("ld.acquire.cta.shared.u32 %0, [%1];" : "=r"(v) : "r"(sb + W_X) : "memory");
              if ((v >> 8) == (uint32_t)(l * 256 + 3)) break;
            }
            const int lane = lane_id();
            float nm[4];
#pragma unroll
            for (int i = 0; i < 4; i++) nm[i] = bf_lo(*(volatile unsigned short*)(smem + MEAN + (wg * 128 + w * 16 + (lane >> 2) + (i >> 1) * 64 + (i & 1) * 8) * 2));
            wg_wait<0>();
            fence_regs(acc[0]); fence_regs(acc[1]);
#pragma unroll
            for (int j = 0; j < 12; j++) {
              const float4 c = lds128f(sb + COLS + j * 64 + (lane & 3) * 16);
#pragma unroll
              for (int m = 0; m < 2; m++) {
                float* a = &acc[m][8 * j];
                a[0] = fmaf(nm[2 * m], c.y, a[0]); a[1] = fmaf(nm[2 * m], c.x, a[1]); a[2] = fmaf(nm[2 * m + 1], c.y, a[2]); a[3] = fmaf(nm[2 * m + 1], c.x, a[3]);
                a[4] = fmaf(nm[2 * m], c.w, a[4]); a[5] = fmaf(nm[2 * m], c.z, a[5]); a[6] = fmaf(nm[2 * m + 1], c.w, a[6]); a[7] = fmaf(nm[2 * m + 1], c.z, a[7]);
              }
            }
            fence_regs(acc[0]); fence_regs(acc[1]);
          }
        }
        auto part = [&](int s, int m, int k0, int k1) {
          const uint64_t da = mkdesc(sb + s * QSTG + wg * 16384 + m * 8192, 16, 1024, 1), db = mkdesc(sb + s * QSTG + 32768, 8192, 1024, 1);
          pin(zero);
          wg_fence();
#pragma unroll
          for (int k = k0; k < k1; k++) wgmma_m64n192k16_ss_tb(acc[m], da + k * 2, db + k * 128, 1);
          wg_commit();
          pin(zero);
        };
        mbar_wait(sb + B_QF + 16, 1);
        part(2, 1, 0, 4);
        wg_wait<1>();
        if (w == 0) e_arrive_both(sb + B_QE + 8);
        if (!(l & 1)) bar_arrive(NB_ST, 288);
        mbar_wait(sb + B_QF + 24, 1);
        part(3, 1, 0, 4);
        part(2, 0, 0, G1);
        IDS();
        const int g = lane >> 2, qd = lane & 3;
        float rs[2][2];
#pragma unroll
        for (int i = 0; i < 4; i++) rs[i >> 1][i & 1] = lds32f(sb + RSTD + (wg * 128 + w * 16 + g + (i >> 1) * 64 + (i & 1) * 8) * 4);
        auto scale = [&](int gi, int m, float sc) {
          const float r0 = rs[m][0] * sc, r1 = rs[m][1] * sc;
#pragma unroll
          for (int i = 0; i < 16; i++) acc[m][16 * gi + i] *= (i & 2) ? r1 : r0;
        };
        auto pack_b = [&](int gi, int m, uint32_t (&t)[8]) {
#pragma unroll
          for (int i = 0; i < 8; i++) t[i] = pack2(acc[m][16 * gi + 2 * i], acc[m][16 * gi + 2 * i + 1]);
        };
        auto norm_tile = [&](int gi, int m, uint32_t (&t)[8]) { scale(gi, m, 1.f); pack_b(gi, m, t); };
        auto pack_h = [&](int gi, int m, uint32_t (&t)[8]) {
#pragma unroll
          for (int i = 0; i < 8; i++) t[i] = pack2h(acc[m][16 * gi + 2 * i], acc[m][16 * gi + 2 * i + 1]);
        };
        uint32_t q[2][2][8], qn[2][2];
        const uint32_t srow = (lane & 7) + ((lane >> 3) & 1) * 8;
        const uint32_t row0 = wg * 128 + w * 16;
        auto put_kv = [&](int h, int v, int m, const uint32_t (&t)[8]) {
          const uint32_t base = sb + ((l & 1) ? (h ? 0 : T0) + v * 16384 : (2 * h + v) * ASC + 1024) + (row0 + m * 64) * 64;
          if (!v) {
#pragma unroll
            for (int jj = 0; jj < 2; jj++) stsm4(base + srow * 64 + (((2 * jj + (lane >> 4)) ^ ((srow >> 1) & 3)) << 4), t[4 * jj], t[4 * jj + 1], t[4 * jj + 2], t[4 * jj + 3]);
          } else {
            const uint32_t ad = base + g * 64 + ((qd ^ (g >> 1)) << 4);
            sts128(ad, t[0], t[2], t[4], t[6]); sts128(ad + 512, t[1], t[3], t[5], t[7]);
          }
        };
        auto send_halo = [&](int h, int v, const uint32_t (&t)[8]) {
          unsigned long long* hp = g_halo + ((size_t)(l >> 1) * 128 + b) * 1024 + h * 512 + v * 256 + lane;
#pragma unroll
          for (int i = 0; i < 8; i++) st_tagged(hp + i * 32, t[i], ep1);
        };
        auto put_kn = [&](int h, int m, uint32_t kn) {
          if (lane == 0) g_kn[((l >> 1) * 128 + bn * 8 + bm) * 32 + 16 * h + 8 * m + wg * 4 + w] = __uint_as_float(kn);
        };
        auto conv_tile1 = [&](int h) {
          uint32_t t[8], tv[8], kn = NOT_F16;
          norm_tile(4 + h, 1, tv);
          put_kv(h, 1, 1, tv);
          scale(2 + h, 1, 1.f);
          if (h == 0) { if (G1 < 4) part(2, 0, G1, 4); if (G2) part(3, 0, 0, G2); } else if (G3 < 4) part(3, 0, G3, 4);
          if (l & 1) {
            float n[2] = {0.f, 0.f};
#pragma unroll
            for (int i = 0; i < 16; i++) n[(i >> 1) & 1] = fmaf(acc[1][32 + 16 * h + i], acc[1][32 + 16 * h + i], n[(i >> 1) & 1]);
            const float a = ((qd & 1) ? n[1] : n[0]) + __shfl_xor_sync(~0u, (qd & 1) ? n[0] : n[1], 1);
            scale(h, 1, QSCALE / 128.f);
            kn = f16_class(__reduce_max_sync(~0u, __float_as_uint(a + __shfl_xor_sync(~0u, a, 2))), K_LO);
            put_kn(h, 1, kn);
          } else scale(h, 1, 1.f);
          if (kn == NOT_F16) pack_b(2 + h, 1, t); else pack_h(2 + h, 1, t);
          put_kv(h, 0, 1, t);
          if (!(l & 1) && row0 == 176 && bm < 7) { send_halo(h, 0, t); send_halo(h, 1, tv); }
        };
        mbar_wait(sb + B_QE + 8, 1);
        wg_wait<1>();
        fence_regs(acc[1]);
        conv_tile1(0);
        if (G2 < G3) part(3, 0, G2, G3);
        if (l & 1) { fence_async_smem(); bar_arrive(NB_ST, 288); }
        conv_tile1(1);
        wg_wait<(G2 > 0) + (G2 < G3) + (G3 < 4)>();
        if (w == 0) e_arrive_both(sb + B_QE + 16);
        wg_wait<0>();
        fence_regs(acc[0]);
        if (w == 0) e_arrive_both(sb + B_QE + 24);
        bf16* const op0 = [&] { IDS(); return g_os + (size_t)(bm * 256 + row0 + (lane >> 2)) * 1024 + bn * 32 + (lane & 3) * 8; }();
        auto put_o = [&](int h, int m, const float (&o)[16], float i0, float i1) {
          bf16* op = op0 + m * 65536 + h * 512;
          const uint4 a = make_uint4(pack2(o[0] * i0, o[1] * i0), pack2(o[4] * i0, o[5] * i0), pack2(o[8] * i0, o[9] * i0), pack2(o[12] * i0, o[13] * i0));
          const uint4 c = make_uint4(pack2(o[2] * i1, o[3] * i1), pack2(o[6] * i1, o[7] * i1), pack2(o[10] * i1, o[11] * i1), pack2(o[14] * i1, o[15] * i1));
          *(uint4*)op = a; *(uint4*)(op + 8 * 1024) = c;
          const uint32_t hi = __vimax3_u16x2(__vimax3_u16x2(a.x, a.y, a.z), __vimax3_u16x2(a.w, c.x, c.y), __vmaxu2(c.z, c.w));
          const uint32_t lo = __vimax3_s16x2(__vimax3_s16x2(a.x, a.y, a.z), __vimax3_s16x2(a.w, c.x, c.y), __vmaxs2(c.z, c.w));
          return __vmaxu2(hi & 0x7FFF7FFFu, lo & 0x7FFF7FFFu);
        };
        if (!(l & 1)) {
          auto conv_kv = [&](int h) {
            uint32_t t[8];
            norm_tile(2 + h, 0, t); put_kv(h, 0, 0, t);
            norm_tile(4 + h, 0, t); put_kv(h, 1, 0, t);
          };
          conv_kv(0);
          if (!PERHEAD) conv_kv(1);
          norm_tile(0, 0, q[0][0]); pack_b(0, 1, q[0][1]);
          bar_sync(NB_SC, 256);
          const bool e = g & 1, sel = 2 * qd + (g & 1) >= g + 2, first = bm == 0 && row0 == 0;
#pragma unroll 1
          for (int h = 0; h < 2; h++) {
            if (row0 == 0) bar_sync(NB_HALO + h, 64);
            float s[2][4][4];
            uint32_t vf[2][4][4], pf[2][2][4];
#pragma unroll
            for (int m = 0; m < 2; m++)
#pragma unroll
              for (int nt = 0; nt < 4; nt++) {
                uint32_t kf[4];
                const uint32_t r = row0 + m * 64 + 8 * nt + (lane & 7);
                ldsm4(sb + 2 * h * ASC + r * 64 + (((lane >> 3) ^ ((r >> 1) & 3)) << 4), kf);
                s[m][nt][0] = s[m][nt][1] = s[m][nt][2] = s[m][nt][3] = 0.f;
                mma16816(s[m][nt], q[0][m][0], q[0][m][1], q[0][m][2], q[0][m][3], kf[0], kf[1]);
                mma16816(s[m][nt], q[0][m][4], q[0][m][5], q[0][m][6], q[0][m][7], kf[2], kf[3]);
              }
#pragma unroll
            for (int m = 0; m < 2; m++)
#pragma unroll
              for (int i = 0; i < 4; i++) {
                const uint32_t r = row0 + m * 64 + 16 * (i >> 1) + srow, ch = 2 * (i & 1) + (lane >> 4);
                ldsm4t(sb + (2 * h + 1) * ASC + r * 64 + ((ch ^ ((r >> 1) & 3)) << 4), vf[m][i]);
              }
            float va[4], vb[4], mx[4];
#pragma unroll
            for (int i = 0; i < 4; i++) {
              const int m = i >> 1, hh = i & 1;
              const float a = e ? s[m][hh + 1][2 * hh + 1] : s[m][hh + 1][2 * hh];
              const float lo = e ? s[m][hh][2 * hh + 1] : s[m][hh][2 * hh], hi = e ? s[m][hh + 2][2 * hh + 1] : s[m][hh + 2][2 * hh];
              const uint32_t t = pack2(a, sel ? lo : hi);
              const uint32_t u = pack2(bf_lo(t) * 0.17677669529663687f, bf_hi(t) * 0.17677669529663687f);
              va[i] = (m == 0 && hh == 0 && first) ? -INFINITY : bf_lo(u);
              vb[i] = (m == 0 && first && sel) ? -INFINITY : bf_hi(u);
              mx[i] = fmaxf(va[i], vb[i]);
            }
#pragma unroll
            for (int i = 0; i < 4; i++) mx[i] = fmaxf(mx[i], __shfl_xor_sync(~0u, mx[i], 1));
#pragma unroll
            for (int i = 0; i < 4; i++) mx[i] = fmaxf(mx[i], __shfl_xor_sync(~0u, mx[i], 2));
#pragma unroll
            for (int i = 0; i < 4; i++) {
              va[i] = ex2((va[i] - mx[i]) * 1.4426950408889634f); vb[i] = ex2((vb[i] - mx[i]) * 1.4426950408889634f);
              mx[i] = va[i] + vb[i];
            }
#pragma unroll
            for (int i = 0; i < 4; i++) mx[i] += __shfl_xor_sync(~0u, mx[i], 1);
#pragma unroll
            for (int i = 0; i < 4; i++) mx[i] += __shfl_xor_sync(~0u, mx[i], 2);
#pragma unroll
            for (int i = 0; i < 4; i++) {
              const int m = i >> 1, hh = i & 1;
              const float inv = rcp(mx[i]);
              const uint32_t t = pack2(va[i] * inv, vb[i] * inv);
              const uint32_t pa = e ? t << 16 : t & 0xFFFFu, pb = e ? t & 0xFFFF0000u : t >> 16;
              pf[m][hh][hh + 1] = pa; pf[m][hh][hh] = sel ? pb : 0u; pf[m][hh][hh + 2] = sel ? 0u : pb; pf[m][hh][3 - 3 * hh] = 0u;
            }
#pragma unroll
            for (int m = 0; m < 2; m++) {
              float o[4][4];
#pragma unroll
              for (int j = 0; j < 4; j++) o[j][0] = o[j][1] = o[j][2] = o[j][3] = 0.f;
#pragma unroll
              for (int i = 0; i < 4; i++) {
                const int kk = i >> 1, jj = 2 * (i & 1);
                mma16816(o[jj], pf[m][0][2 * kk], pf[m][1][2 * kk], pf[m][0][2 * kk + 1], pf[m][1][2 * kk + 1], vf[m][i][0], vf[m][i][1]);
                mma16816(o[jj + 1], pf[m][0][2 * kk], pf[m][1][2 * kk], pf[m][0][2 * kk + 1], pf[m][1][2 * kk + 1], vf[m][i][2], vf[m][i][3]);
              }
              const float of[16] = {o[0][0], o[0][1], o[0][2], o[0][3], o[1][0], o[1][1], o[1][2], o[1][3], o[2][0], o[2][1], o[2][2], o[2][3], o[3][0], o[3][1], o[3][2], o[3][3]};
              put_o(h, m, of, 1.f, 1.f);
            }
            bar_arrive(NB_SIG + 2 * h + wg, 160);
            if (h == 0) {
              if (PERHEAD) conv_kv(1);
              norm_tile(1, 0, q[0][0]); pack_b(1, 1, q[0][1]);
              if (PERHEAD) bar_sync(NB_SC, 256);
            }
          }
        } else {
          auto conv_h = [&](int gi, int m, uint32_t (&t)[8]) {
            pack_h(gi, m, t);
            float d0[4] = {0.f, 0.f, 0.f, 0.f}, d1[4] = {0.f, 0.f, 0.f, 0.f};
            mma16816h(d0, t[0], t[1], t[2], t[3], t[0], t[2]); mma16816h(d1, t[0], t[1], t[2], t[3], t[1], t[3]);
            mma16816h(d0, t[4], t[5], t[6], t[7], t[4], t[6]); mma16816h(d1, t[4], t[5], t[6], t[7], t[5], t[7]);
            return (uint32_t)__reduce_max_sync(~0u, max(max(__float_as_int(d0[0]), __float_as_int(d0[1])), max(__float_as_int(d1[2]), __float_as_int(d1[3]))));
          };
#pragma unroll
          for (int h = 0; h < 2; h++) {
            uint32_t t[8], tv[8];
            scale(2 + h, 0, 1.f);
            const uint32_t kn = f16_class(conv_h(2 + h, 0, t), K_LO);
            if (h) {
#pragma unroll
              for (int i = 0; i < 2; i++) {
                scale(i, 0, QSCALE);
                qn[i][0] = f16_class(conv_h(i, 0, q[i][0]), K_LO);
                qn[i][1] = f16_class(conv_h(i, 1, q[i][1]), K_LO);
              }
            }
            norm_tile(4 + h, 0, tv);
            put_kv(h, 1, 0, tv);
            put_kn(h, 0, kn);
            if (kn == NOT_F16) pack_b(2 + h, 0, t);
            put_kv(h, 0, 0, t);
            fence_async_smem();
            bar_arrive(NB_KV + 12 * h, 288);
            if (h == 0) mbar_wait(sb + B_QF + 24, 1);
          }
          if (max(max(qn[0][0], qn[0][1]), max(qn[1][0], qn[1][1])) == NOT_F16) {
#pragma unroll
            for (int i = 0; i < 4; i++) if (qn[i >> 1][i & 1] == NOT_F16) pack_b(i >> 1, i & 1, q[i >> 1][i & 1]);
          }
          const bool elected = w == 0 && lane == 0;
          const uint64_t kd0 = mkdesc(sb + T0, 16, 512, 2);
          const uint64_t vd0 = mkdesc(sb + T0 + 16384, ONES - (T0 + 16384), 512, 2);
          constexpr uint64_t VSTEP = 64 - (64ull << 16);
          constexpr int RPC = NQ / 16, NC = 256 / NQ;
          float o[2][20], SA[2][NQ / 2];
          uint32_t SB[2][NQ / 4], PA[LA][4], PB[LB][4];
#pragma unroll
          for (int m = 0; m < 2; m++) {
#pragma unroll
            for (int i = 0; i < NQ / 2; i++) SA[m][i] = 0.f;
#pragma unroll
            for (int i = 0; i < NQ / 4; i++) SB[m][i] = 0u;
            fence_regs(SA[m]); fence_regs(SB[m]);
          }
          auto qka = [&](int b, int k, uint64_t d, int h = 0) { QK_A(SA[b], q[h][0][4 * k], q[h][0][4 * k + 1], q[h][0][4 * k + 2], q[h][0][4 * k + 3], d + 2 * k, k ? 1 : zero); };
          auto qkb = [&](int b, int k, uint64_t d, int h = 0) { QK_B(SB[b], q[h][1][4 * k], q[h][1][4 * k + 1], q[h][1][4 * k + 2], q[h][1][4 * k + 3], d + 2 * k, k ? 1 : zero); };
          auto pv = [&](int m, const uint32_t (&Px)[4], uint64_t vd) { wgmma_m64n40k16_rs_tb(o[m], Px[0], Px[1], Px[2], Px[3], vd, 1); };
          auto clear = [&]() {
#pragma unroll
            for (int i = 0; i < 20; i++) o[0][i] = o[1][i] = 0.f;
            fence_regs(o[0]); fence_regs(o[1]);
#pragma unroll
            for (int i = 0; i < 4; i++) PA[0][i] = PB[0][i] = PA[LA - 1][i] = PB[LB - 1][i] = zero;
          };
          mbar_wait(sb + B_TF, 0);
          wg_fence(); qka(0, 0, kd0); qkb(0, 0, kd0); qka(0, 1, kd0); qkb(0, 1, kd0); wg_commit();
          clear();
          wg_wait<0>(); fence_regs(SA[0]); fence_regs(SB[0]);
#pragma unroll 1
          for (int pass = 0; pass < 2; pass++) {
#pragma unroll 1
            for (int j = 0; j < 8; j++) {
              const uint32_t s = j & 3, sn = j < 7 ? (j + 1) & 3 : s, sp = j > 0 ? (j + 3) & 3 : s;
              const uint64_t kd = kd0 + s * 2048, vd = vd0 + s * (32 * VSTEP), kdn = kd0 + sn * 2048, vdp = vd0 + sp * (32 * VSTEP) + 16 * VSTEP;
              bool landed = false;
#pragma unroll
              for (int r = 0; r < 16; r++) {
                const int c = r / RPC, ro = r % RPC, cn = c + 1;
                if (r == 16 - RPC && !landed) mbar_wait(sb + B_TF + 8 * sn, ((j + 1) >> 2) & 1);
                wg_fence();
                const uint64_t kx = cn < NC ? kd + cn * NQ * 4 : kdn, va = (r >= LA ? vd : vdp) + (r - LA) * VSTEP, vb = (r >= LB ? vd : vdp) + (r - LB) * VSTEP;
                if (LAG & 4) { pv(0, PA[r % LA], va); pv(1, PB[r % LB], vb); }
#pragma unroll
                for (int k = 0; k < 2; k++) {
                  if (ro == ((OA >> (4 * k)) & 15)) qka(cn & 1, k, kx);
                  if (ro == ((OB >> (4 * k)) & 15)) qkb(cn & 1, k, kx);
                }
                if (!(LAG & 4)) {
                  if (ro == RPC - 1 || (LAG & 1)) wg_commit();
                  if (LAG & 8) { pv(1, PB[r % LB], vb); pv(0, PA[r % LA], va); } else { pv(0, PA[r % LA], va); pv(1, PB[r % LB], vb); }
                }
                wg_commit();
                if (r == 14 - RPC) landed = mbar_test(sb + B_TF + 8 * sn, ((j + 1) >> 2) & 1) || j == 7;
#pragma unroll
                for (int i = 0; i < 4; i++) {
                  if (LAG & 16) PB[r % LB][i] = exp2_h2(SB[c & 1][4 * ro + i]);
                  PA[r % LA][i] = pack2(ex2(SA[c & 1][8 * ro + 2 * i]), ex2(SA[c & 1][8 * ro + 2 * i + 1]));
                  if (!(LAG & 16)) PB[r % LB][i] = exp2_h2(SB[c & 1][4 * ro + i]);
                }
                if (r == 15 || ((LAG & 4) && ro == RPC - 1 && ((OA >> 4) == ro || (OB >> 4) == ro))) wg_wait<0>(); else if (ro == RPC - 1 || !(LAG & 2)) wg_wait<1>();
                if (ro == RPC - 1) { fence_regs(SA[cn & 1]); fence_regs(SB[cn & 1]); }
                if (r == (LA + LB > 2 ? 4 : RPC) && elected && j > 0) mbar_arrive(sb + B_TE + 8 * sp);
              }
            }
            int badm = 0;
            if (pass == 0) mbar_wait(sb + B_TF, 0);
            wg_fence();
            if (LA == 2) pv(0, PA[0], vd0 + 110 * VSTEP);
            if (LB == 2) pv(1, PB[0], vd0 + 110 * VSTEP);
            pv(0, PA[LA - 1], vd0 + 111 * VSTEP); pv(1, PB[LB - 1], vd0 + 111 * VSTEP); wg_commit();
            qka(0, 0, kd0, 1); qkb(0, 0, kd0, 1); qka(0, 1, kd0, 1); qkb(0, 1, kd0, 1); wg_commit();
            if (pass == 0) bar_sync(NB_KN + wg, 160);
            const float kmax = *(volatile float*)(smem + KMAX + 4 * pass);
            wg_wait<1>(); fence_regs(o[0]); fence_regs(o[1]);
            if (w == 0) e_arrive(sb + B_TE + 8 * 3);
#pragma unroll
            for (int m = 0; m < 2; m++) {
              const float of[16] = {o[m][0], o[m][1], o[m][2], o[m][3], o[m][4], o[m][5], o[m][6], o[m][7], o[m][8], o[m][9], o[m][10], o[m][11], o[m][12], o[m][13], o[m][14], o[m][15]};
              const uint32_t chk = put_o(pass, m, of, rcp(o[m][16]), rcp(o[m][18]));
              const bool bad = !(__uint_as_float(qn[0][m]) * kmax <= (m ? 0.875f * 0.875f : 112.f * 112.f)) || !(fminf(o[m][16], o[m][18]) >= 9.3e-10f) ||
                               !(o[m][16] + o[m][18] <= 3e38f) || ((chk + 0x00800080u) & 0x80008000u);
              badm |= __any_sync(~0u, bad) << m;
            }
            wg_wait<0>(); fence_regs(SA[0]); fence_regs(SB[0]);
            if (badm) {
#pragma unroll 1
              for (int m = 0; m < 2; m++) if ((badm >> m) & 1) {
                uint32_t qq[8]; float res[20];
#pragma unroll
                for (int i = 0; i < 8; i++) { qq[i] = m ? q[0][1][i] : q[0][0][i]; if ((m ? qn[0][1] : qn[0][0]) != NOT_F16) qq[i] = h2_to_bf2(qq[i]); }
                attn_slow(qq, m ? 128.f : 1.f, 2 * (cta_id() & 15) + pass, g_kn + ((l >> 1) * 128 + (cta_id() & 15) * 8) * 32 + 16 * pass, res, lane_id());
                const float of[16] = {res[0], res[1], res[2], res[3], res[4], res[5], res[6], res[7], res[8], res[9], res[10], res[11], res[12], res[13], res[14], res[15]};
                put_o(pass, m, of, rcp(res[16]), rcp(res[18]));
              }
            }
            bar_arrive(NB_SIG + 2 * pass + wg, 160);
            qn[0][0] = qn[1][0]; qn[0][1] = qn[1][1];
#pragma unroll
            for (int m = 0; m < 2; m++)
#pragma unroll
              for (int i = 0; i < 8; i++) q[0][m][i] = q[1][m][i];
            clear();
          }
        }
      }
      {
        float acc[64];
#pragma unroll
        for (int i = 0; i < 64; i++) acc[i] = 0.f;
        fence_regs(acc);
        uint32_t s = 0, lap = 0;
#pragma unroll 1
        for (int kt = 0; kt < 16; kt++) {
          mbar_wait(sb + B_PF + 8 * s, ((s < 4 ? l : 0) + lap) & 1);
          const uint64_t da = mkdesc(sb + pslot_a(s, l) + wg * 8192, 16, 1024, 1), db = mkdesc(sb + pslot_b(s, l), 8192, 1024, 1);
          wg_fence();
#pragma unroll
          for (int k = 0; k < 4; k++) wgmma_m64n128k16_ss_tb(acc, da + k * 2, db + k * 128, 1);
          wg_commit();
          wg_wait<1>();
          if (kt > 0 && w == 0) e_arrive_both(sb + B_PE + 8 * (s ? s - 1 : 5));
          if (++s == 6) { s = 0; lap++; }
        }
        IDS();
        const int g = lane >> 2, qd = lane & 3;
        const int r0 = wg * 64 + w * 16;
        const uint32_t r = r0 + (lane & 7) + ((lane >> 3) & 1) * 8;
        uint32_t x[8][4];
        mbar_wait(sb + B_RF, l & 1);
#pragma unroll
        for (int jj = 0; jj < 8; jj++) ldsm4(sb + ((l & 1) ? RES : 0) + (jj >> 2) * 16384 + r * 128 + ((((2 * jj + (lane >> 4)) & 7) ^ (r & 7)) << 4), x[jj]);
        wg_wait<0>();
        fence_regs(acc);
        bar_sync(NB_SC, 256);
        if (w == 0) e_arrive_both(sb + B_PE + 8 * 3);
        const CUtensorMap* mo = &prm.m[l == 3 ? M_OUT : M_XST];
#pragma unroll
        for (int jj = 0; jj < 8; jj++) {
#pragma unroll
          for (int i = 0; i < 4; i++) x[jj][i] = add_bf16x2(x[jj][i], pack2(acc[8 * jj + 2 * i], acc[8 * jj + 2 * i + 1]));
          stsm4(sb + (jj >> 2) * QSTG + po * 16384 + r * 128 + ((((2 * jj + (lane >> 4)) & 7) ^ (r & 7)) << 4), x[jj][0], x[jj][1], x[jj][2], x[jj][3]);
          if ((jj & 3) == 3) { fence_async_smem(); __syncwarp(); tma_st(mo, pn * 128 + (jj >> 2) * 64, pm * 128 + r0, sb + (jj >> 2) * QSTG + po * 16384 + r0 * 128); }
        }
        bulk_commit();
        if (l < 3) {
          bar_arrive(NB_X, 288);
          float s1[4] = {0.f, 0.f, 0.f, 0.f}, s2[4][4];
#pragma unroll
          for (int i = 0; i < 16; i++) s2[i >> 2][i & 3] = 0.f;
#pragma unroll
          for (int jj = 0; jj < 8; jj++) {
            mma16816(s1, x[jj][0], x[jj][1], x[jj][2], x[jj][3], 0x3f803f80u, 0x3f803f80u);
#pragma unroll
            for (int i = 0; i < 4; i++) mma1688(s2[i], x[jj][i & 2], x[jj][i | 1], x[jj][i]);
          }
          if (qd == (g >> 1)) {
            float2* sp = g_stats + pn * 2048 + pm * 128 + r0 + g;
            sp[0] = make_float2(s1[0], (g & 1) ? s2[0][1] + s2[2][1] : s2[0][0] + s2[2][0]);
            sp[8] = make_float2(s1[2], (g & 1) ? s2[1][3] + s2[3][3] : s2[1][2] + s2[3][2]);
          }
        }
        bulk_wait_n<0>();
        if (l < 3) bar_arrive(NB_X0, 320);
      }
    }
  }
  asm volatile("barrier.cluster.arrive.relaxed.aligned;\nbarrier.cluster.wait.aligned;" ::: "memory");
}

typedef CUresult (*EncodeFn)(CUtensorMap*, CUtensorMapDataType, cuuint32_t, void*, const cuuint64_t*, const cuuint64_t*, const cuuint32_t*,
                             const cuuint32_t*, CUtensorMapInterleave, CUtensorMapSwizzle, CUtensorMapL2promotion, CUtensorMapFloatOOBfill);

static void make_map(EncodeFn fn, CUtensorMap* m, const void* ptr, int rank, const uint64_t* dims, const uint64_t* strides, const uint32_t* box, CUtensorMapSwizzle sw) {
  cuuint64_t d[5], st[4];
  cuuint32_t bx[5], es[5];
  for (int i = 0; i < rank; i++) { d[i] = dims[i]; bx[i] = box[i]; es[i] = 1; if (i) st[i - 1] = strides[i - 1] * 2; }
  fn(m, CU_TENSOR_MAP_DATA_TYPE_BFLOAT16, rank, (void*)ptr, d, st, bx, es, CU_TENSOR_MAP_INTERLEAVE_NONE, sw,
     CU_TENSOR_MAP_L2_PROMOTION_L2_128B, CU_TENSOR_MAP_FLOAT_OOB_FILL_NONE);
}
static void map2(EncodeFn fn, CUtensorMap* m, const void* ptr, uint64_t inner, uint64_t outer, uint32_t bi, uint32_t bo, CUtensorMapSwizzle sw) {
  const uint64_t d[2] = {inner, outer}, st[1] = {inner};
  const uint32_t bx[2] = {bi, bo};
  make_map(fn, m, ptr, 2, d, st, bx, sw);
}

extern "C" void kernel_launch(void* const* d_in, const int* in_sizes, int n_in, void* d_out, int out_size) {
  (void)in_sizes; (void)n_in; (void)out_size;
  static EncodeFn enc = nullptr;
  static void *xs, *os, *kk, *vv, *ep;
  if (!enc) {
    void* p = nullptr;
    cudaDriverEntryPointQueryResult qr;
    cudaGetDriverEntryPoint("cuTensorMapEncodeTiled", &p, cudaEnableDefault, &qr);
    enc = (EncodeFn)p;
    cudaGetSymbolAddress(&xs, g_xs); cudaGetSymbolAddress(&os, g_os); cudaGetSymbolAddress(&kk, g_k); cudaGetSymbolAddress(&vv, g_v); cudaGetSymbolAddress(&ep, g_epoch);
    cudaFuncSetAttribute(fused_kernel, cudaFuncAttributeMaxDynamicSharedMemorySize, SMEM_BYTES);
  }
  Params prm;
  const CUtensorMapSwizzle S128 = CU_TENSOR_MAP_SWIZZLE_128B, S64 = CU_TENSOR_MAP_SWIZZLE_64B;
  map2(enc, &prm.m[M_X0A], d_in[0], 1024, 2048, 64, 256, S128);
  map2(enc, &prm.m[M_XSA], xs, 1024, 2048, 64, 256, S128);
  for (int t = 0; t < 2; t++) {
    const uint64_t d3[3] = {1024, 1024, 3}, s3[2] = {3072, 1024};
    const uint32_t b3[3] = {64, 64, 3};
    make_map(enc, &prm.m[M_WQA + t], d_in[1 + 3 * t], 3, d3, s3, b3, S128);
    const uint64_t d5[5] = {64, 32, 2, 16, 16}, s5[4] = {1024, 32 * 1024, 64 * 1024, 64};
    const uint32_t b5[5] = {64, 32, 1, 2, 2};
    make_map(enc, &prm.m[M_WOA + t], d_in[2 + 3 * t], 5, d5, s5, b5, S128);
    const uint64_t dr[3] = {64, 2048, 16}, sr[2] = {1024, 64};
    const uint32_t br[3] = {64, 128, 2};
    make_map(enc, &prm.m[M_X0R + t], t ? xs : d_in[0], 3, dr, sr, br, S128);
  }
  map2(enc, &prm.m[M_OS], os, 1024, 2048, 64, 64, S128);
  map2(enc, &prm.m[M_K], kk, 32, 65536, 32, 256, S64);
  map2(enc, &prm.m[M_V], vv, 32, 65536, 32, 256, S64);
  map2(enc, &prm.m[M_K4], kk, 32, 65536, 32, 64, S64);
  map2(enc, &prm.m[M_V4], vv, 32, 65536, 32, 64, S64);
  map2(enc, &prm.m[M_XSO], xs, 1024, 2048, 64, 128, S128);
  map2(enc, &prm.m[M_X0H], d_in[0], 1024, 2048, 64, 128, S128);
  map2(enc, &prm.m[M_XST], xs, 1024, 2048, 64, 16, S128);
  map2(enc, &prm.m[M_OUT], d_out, 1024, 2048, 64, 16, S128);
  prm.x0 = (const bf16*)d_in[0];
  prm.wq[0] = (const bf16*)d_in[1]; prm.wq[1] = (const bf16*)d_in[4];
  prm.epoch = (uint32_t*)ep;
  prm.zero = 0;
  for (int i = 0; i < 128; i++) prm.map[i] = remap(i);
  fused_kernel<<<128, 384, SMEM_BYTES>>>(prm);
}
```

```cpp
#include <cuda_runtime.h>
#include <cuda_bf16.h>
#include <cuda.h>
#include <stdint.h>

typedef __nv_bfloat16 bf16;

__device__ __forceinline__ void wgmma_m64n192k16_ss_tb(float (&d)[96], uint64_t da, uint64_t db, int scale_d) {
  asm volatile("{\n.reg .pred p;\nsetp.ne.b32 p, %98, 0;\n"
    "wgmma.mma_async.sync.aligned.m64n192k16.f32.bf16.bf16 "
    "{%0, %1, %2, %3, %4, %5, %6, %7, %8, %9, %10, %11, %12, %13, %14, %15, "
    "%16, %17, %18, %19, %20, %21, %22, %23, %24, %25, %26, %27, %28, %29, %30, %31, "
    "%32, %33, %34, %35, %36, %37, %38, %39, %40, %41, %42, %43, %44, %45, %46, %47, "
    "%48, %49, %50, %51, %52, %53, %54, %55, %56, %57, %58, %59, %60, %61, %62, %63, "
    "%64, %65, %66, %67, %68, %69, %70, %71, %72, %73, %74, %75, %76, %77, %78, %79, "
    "%80, %81, %82, %83, %84, %85, %86, %87, %88, %89, %90, %91, %92, %93, %94, %95}, "
    "%96, %97, p, 1, 1, 0, 1;\n}\n"
    : "+f"(d[0]), "+f"(d[1]), "+f"(d[2]), "+f"(d[3]), "+f"(d[4]), "+f"(d[5]), "+f"(d[6]), "+f"(d[7]),
      "+f"(d[8]), "+f"(d[9]), "+f"(d[10]), "+f"(d[11]), "+f"(d[12]), "+f"(d[13]), "+f"(d[14]), "+f"(d[15]),
      "+f"(d[16]), "+f"(d[17]), "+f"(d[18]), "+f"(d[19]), "+f"(d[20]), "+f"(d[21]), "+f"(d[22]), "+f"(d[23]),
      "+f"(d[24]), "+f"(d[25]), "+f"(d[26]), "+f"(d[27]), "+f"(d[28]), "+f"(d[29]), "+f"(d[30]), "+f"(d[31]),
      "+f"(d[32]), "+f"(d[33]), "+f"(d[34]), "+f"(d[35]), "+f"(d[36]), "+f"(d[37]), "+f"(d[38]), "+f"(d[39]),
      "+f"(d[40]), "+f"(d[41]), "+f"(d[42]), "+f"(d[43]), "+f"(d[44]), "+f"(d[45]), "+f"(d[46]), "+f"(d[47]),
      "+f"(d[48]), "+f"(d[49]), "+f"(d[50]), "+f"(d[51]), "+f"(d[52]), "+f"(d[53]), "+f"(d[54]), "+f"(d[55]),
      "+f"(d[56]), "+f"(d[57]), "+f"(d[58]), "+f"(d[59]), "+f"(d[60]), "+f"(d[61]), "+f"(d[62]), "+f"(d[63]),
      "+f"(d[64]), "+f"(d[65]), "+f"(d[66]), "+f"(d[67]), "+f"(d[68]), "+f"(d[69]), "+f"(d[70]), "+f"(d[71]),
      "+f"(d[72]), "+f"(d[73]), "+f"(d[74]), "+f"(d[75]), "+f"(d[76]), "+f"(d[77]), "+f"(d[78]), "+f"(d[79]),
      "+f"(d[80]), "+f"(d[81]), "+f"(d[82]), "+f"(d[83]), "+f"(d[84]), "+f"(d[85]), "+f"(d[86]), "+f"(d[87]),
      "+f"(d[88]), "+f"(d[89]), "+f"(d[90]), "+f"(d[91]), "+f"(d[92]), "+f"(d[93]), "+f"(d[94]), "+f"(d[95])
    : "l"(da), "l"(db), "r"(scale_d));
}

__device__ __forceinline__ void wgmma_m64n128k16_ss_tb(float (&d)[64], uint64_t da, uint64_t db, int scale_d) {
  asm volatile("{\n.reg .pred p;\nsetp.ne.b32 p, %66, 0;\n"
    "wgmma.mma_async.sync.aligned.m64n128k16.f32.bf16.bf16 "
    "{%0, %1, %2, %3, %4, %5, %6, %7, %8, %9, %10, %11, %12, %13, %14, %15, "
    "%16, %17, %18, %19, %20, %21, %22, %23, %24, %25, %26, %27, %28, %29, %30, %31, "
    "%32, %33, %34, %35, %36, %37, %38, %39, %40, %41, %42, %43, %44, %45, %46, %47, "
    "%48, %49, %50, %51, %52, %53, %54, %55, %56, %57, %58, %59, %60, %61, %62, %63}, "
    "%64, %65, p, 1, 1, 0, 1;\n}\n"
    : "+f"(d[0]), "+f"(d[1]), "+f"(d[2]), "+f"(d[3]), "+f"(d[4]), "+f"(d[5]), "+f"(d[6]), "+f"(d[7]),
      "+f"(d[8]), "+f"(d[9]), "+f"(d[10]), "+f"(d[11]), "+f"(d[12]), "+f"(d[13]), "+f"(d[14]), "+f"(d[15]),
      "+f"(d[16]), "+f"(d[17]), "+f"(d[18]), "+f"(d[19]), "+f"(d[20]), "+f"(d[21]), "+f"(d[22]), "+f"(d[23]),
      "+f"(d[24]), "+f"(d[25]), "+f"(d[26]), "+f"(d[27]), "+f"(d[28]), "+f"(d[29]), "+f"(d[30]), "+f"(d[31]),
      "+f"(d[32]), "+f"(d[33]), "+f"(d[34]), "+f"(d[35]), "+f"(d[36]), "+f"(d[37]), "+f"(d[38]), "+f"(d[39]),
      "+f"(d[40]), "+f"(d[41]), "+f"(d[42]), "+f"(d[43]), "+f"(d[44]), "+f"(d[45]), "+f"(d[46]), "+f"(d[47]),
      "+f"(d[48]), "+f"(d[49]), "+f"(d[50]), "+f"(d[51]), "+f"(d[52]), "+f"(d[53]), "+f"(d[54]), "+f"(d[55]),
      "+f"(d[56]), "+f"(d[57]), "+f"(d[58]), "+f"(d[59]), "+f"(d[60]), "+f"(d[61]), "+f"(d[62]), "+f"(d[63])
    : "l"(da), "l"(db), "r"(scale_d));
}

__device__ __forceinline__ void wgmma_m64n32k16_rs_nb_h(float (&d)[16], uint32_t a0, uint32_t a1, uint32_t a2, uint32_t a3, uint64_t db, int scale_d) {
  asm volatile("{\n.reg .pred p;\nsetp.ne.b32 p, %21, 0;\n"
    "wgmma.mma_async.sync.aligned.m64n32k16.f32.f16.f16 "
    "{%0, %1, %2, %3, %4, %5, %6, %7, %8, %9, %10, %11, %12, %13, %14, %15}, "
    "{%16, %17, %18, %19}, %20, p, 1, 1, 0;\n}\n"
    : "+f"(d[0]), "+f"(d[1]), "+f"(d[2]), "+f"(d[3]), "+f"(d[4]), "+f"(d[5]), "+f"(d[6]), "+f"(d[7]),
      "+f"(d[8]), "+f"(d[9]), "+f"(d[10]), "+f"(d[11]), "+f"(d[12]), "+f"(d[13]), "+f"(d[14]), "+f"(d[15])
    : "r"(a0), "r"(a1), "r"(a2), "r"(a3), "l"(db), "r"(scale_d));
}

__device__ __forceinline__ void wgmma_m64n32k16_rs_nb_hh(uint32_t (&d)[8], uint32_t a0, uint32_t a1, uint32_t a2, uint32_t a3, uint64_t db, int scale_d) {
  asm volatile("{\n.reg .pred p;\nsetp.ne.b32 p, %13, 0;\n"
    "wgmma.mma_async.sync.aligned.m64n32k16.f16.f16.f16 "
    "{%0, %1, %2, %3, %4, %5, %6, %7}, "
    "{%8, %9, %10, %11}, %12, p, 1, 1, 0;\n}\n"
    : "+r"(d[0]), "+r"(d[1]), "+r"(d[2]), "+r"(d[3]), "+r"(d[4]), "+r"(d[5]), "+r"(d[6]), "+r"(d[7])
    : "r"(a0), "r"(a1), "r"(a2), "r"(a3), "l"(db), "r"(scale_d));
}

__device__ __forceinline__ void wgmma_m64n64k16_rs_nb_h(float (&d)[32], uint32_t a0, uint32_t a1, uint32_t a2, uint32_t a3, uint64_t db, int scale_d) {
  asm volatile("{\n.reg .pred p;\nsetp.ne.b32 p, %37, 0;\n"
    "wgmma.mma_async.sync.aligned.m64n64k16.f32.f16.f16 "
    "{%0, %1, %2, %3, %4, %5, %6, %7, %8, %9, %10, %11, %12, %13, %14, %15, "
    "%16, %17, %18, %19, %20, %21, %22, %23, %24, %25, %26, %27, %28, %29, %30, %31}, "
    "{%32, %33, %34, %35}, %36, p, 1, 1, 0;\n}\n"
    : "+f"(d[0]), "+f"(d[1]), "+f"(d[2]), "+f"(d[3]), "+f"(d[4]), "+f"(d[5]), "+f"(d[6]), "+f"(d[7]),
      "+f"(d[8]), "+f"(d[9]), "+f"(d[10]), "+f"(d[11]), "+f"(d[12]), "+f"(d[13]), "+f"(d[14]), "+f"(d[15]),
      "+f"(d[16]), "+f"(d[17]), "+f"(d[18]), "+f"(d[19]), "+f"(d[20]), "+f"(d[21]), "+f"(d[22]), "+f"(d[23]),
      "+f"(d[24]), "+f"(d[25]), "+f"(d[26]), "+f"(d[27]), "+f"(d[28]), "+f"(d[29]), "+f"(d[30]), "+f"(d[31])
    : "r"(a0), "r"(a1), "r"(a2), "r"(a3), "l"(db), "r"(scale_d));
}

__device__ __forceinline__ void wgmma_m64n64k16_rs_nb_hh(uint32_t (&d)[16], uint32_t a0, uint32_t a1, uint32_t a2, uint32_t a3, uint64_t db, int scale_d) {
  asm volatile("{\n.reg .pred p;\nsetp.ne.b32 p, %21, 0;\n"
    "wgmma.mma_async.sync.aligned.m64n64k16.f16.f16.f16 "
    "{%0, %1, %2, %3, %4, %5, %6, %7, %8, %9, %10, %11, %12, %13, %14, %15}, "
    "{%16, %17, %18, %19}, %20, p, 1, 1, 0;\n}\n"
    : "+r"(d[0]), "+r"(d[1]), "+r"(d[2]), "+r"(d[3]), "+r"(d[4]), "+r"(d[5]), "+r"(d[6]), "+r"(d[7]),
      "+r"(d[8]), "+r"(d[9]), "+r"(d[10]), "+r"(d[11]), "+r"(d[12]), "+r"(d[13]), "+r"(d[14]), "+r"(d[15])
    : "r"(a0), "r"(a1), "r"(a2), "r"(a3), "l"(db), "r"(scale_d));
}

__device__ __forceinline__ void wgmma_m64n40k16_rs_tb(float (&d)[20], uint32_t a0, uint32_t a1, uint32_t a2, uint32_t a3, uint64_t db, int scale_d) {
  asm volatile("{\n.reg .pred p;\nsetp.ne.b32 p, %25, 0;\n"
    "wgmma.mma_async.sync.aligned.m64n40k16.f32.bf16.bf16 "
    "{%0, %1, %2, %3, %4, %5, %6, %7, %8, %9, %10, %11, %12, %13, %14, %15, "
    "%16, %17, %18, %19}, "
    "{%20, %21, %22, %23}, %24, p, 1, 1, 1;\n}\n"
    : "+f"(d[0]), "+f"(d[1]), "+f"(d[2]), "+f"(d[3]), "+f"(d[4]), "+f"(d[5]), "+f"(d[6]), "+f"(d[7]),
      "+f"(d[8]), "+f"(d[9]), "+f"(d[10]), "+f"(d[11]), "+f"(d[12]), "+f"(d[13]), "+f"(d[14]), "+f"(d[15]),
      "+f"(d[16]), "+f"(d[17]), "+f"(d[18]), "+f"(d[19])
    : "r"(a0), "r"(a1), "r"(a2), "r"(a3), "l"(db), "r"(scale_d));
}

#define DEVINL __device__ __forceinline__
#define PSLEEP 0
#define XLATE 1
#define PLATE 1
#define HINT 4000
#define MWL mbar_wait_long
DEVINL void pin(uint32_t z) { asm volatile("{\n.reg .pred p;\nsetp.ne.u32 p, %0, 0;\nPIN:\n@p bra.uni PIN;\n}" ::"r"(z) : "memory"); }
DEVINL void wg_fence() { asm volatile("wgmma.fence.sync.aligned;" ::: "memory"); }
DEVINL void wg_commit() { asm volatile("wgmma.commit_group.sync.aligned;" ::: "memory"); }
template <int N> DEVINL void wg_wait() { asm volatile("wgmma.wait_group.sync.aligned %0;" ::"n"(N) : "memory"); }
DEVINL uint64_t mkdesc(uint32_t addr, uint32_t lbo, uint32_t sbo, int sw) {
  return (uint64_t)((addr & 0x3FFFF) >> 4) | ((uint64_t)(lbo >> 4) << 16) | ((uint64_t)(sbo >> 4) << 32) | ((uint64_t)sw << 62);
}
DEVINL void mbar_arrive(uint32_t bar) { asm volatile("mbarrier.arrive.shared::cta.b64 _, [%0];" ::"r"(bar) : "memory"); }
DEVINL bool mbar_try(uint32_t bar, uint32_t parity) {
  uint32_t ok;
  asm volatile("{\n.reg .pred p;\nmbarrier.try_wait.parity.shared::cta.b64 p, [%1], %2;\nselp.u32 %0, 1, 0, p;\n}" : "=r"(ok) : "r"(bar), "r"(parity) : "memory");
  return ok;
}
DEVINL bool mbar_test(uint32_t bar, uint32_t parity) {
  uint32_t ok;
  asm volatile("{\n.reg .pred p;\nmbarrier.test_wait.parity.shared::cta.b64 p, [%1], %2;\nselp.u32 %0, 1, 0, p;\n}" : "=r"(ok) : "r"(bar), "r"(parity) : "memory");
  return ok;
}
DEVINL void mbar_hint(uint32_t bar, uint32_t parity) {
#pragma unroll 1
  for (uint32_t n = 0; n < 16u; n++) if (mbar_try(bar, parity)) break;
}
DEVINL void mbar_wait(uint32_t bar, uint32_t parity) {
#pragma unroll 1
  for (uint32_t n = 0; n < 100000u; n++) if (mbar_try(bar, parity)) break;
}
DEVINL void mbar_wait_long(uint32_t bar, uint32_t parity) {
#pragma unroll 1
  for (uint32_t n = 0; n < 100000u; n++) {
    uint32_t ok;
    asm volatile("{\n.reg .pred p;\nmbarrier.try_wait.parity.shared::cta.b64 p, [%1], %2, %3;\nselp.u32 %0, 1, 0, p;\n}" : "=r"(ok) : "r"(bar), "r"(parity), "r"(HINT) : "memory");
    if (ok) break;
  }
}
#define EL(txt) "{\n.reg .pred pe;\nelect.sync _|pe, 0xffffffff;\n@pe " txt "\n}"
DEVINL void e_expect_tx(uint32_t bar, uint32_t bytes) { asm volatile(EL("mbarrier.arrive.expect_tx.shared::cta.b64 _, [%0], %1;") ::"r"(bar), "r"(bytes) : "memory"); }
DEVINL void e_init(uint32_t bar, uint32_t cnt) { asm volatile(EL("mbarrier.init.shared::cta.b64 [%0], %1;") ::"r"(bar), "r"(cnt) : "memory"); }
DEVINL void e_arrive(uint32_t bar) { asm volatile(EL("mbarrier.arrive.shared::cta.b64 _, [%0];") ::"r"(bar) : "memory"); }
DEVINL void e_red(uint32_t* p) { asm volatile(EL("red.release.gpu.global.add.u32 [%0], 1;") ::"l"(p) : "memory"); }
DEVINL void e_red_relaxed(uint32_t* p) { asm volatile(EL("red.relaxed.gpu.global.add.u32 [%0], 1;") ::"l"(p) : "memory"); }
DEVINL void tma_ld(uint32_t dst, const CUtensorMap* m, int c0, int c1, uint32_t bar) {
  asm volatile(EL("cp.async.bulk.tensor.2d.shared::cluster.global.mbarrier::complete_tx::bytes [%0], [%1, {%3, %4}], [%2];")
               ::"r"(dst), "l"(m), "r"(bar), "r"(c0), "r"(c1) : "memory");
}
DEVINL void tma_ld3(uint32_t dst, const CUtensorMap* m, int c0, int c1, int c2, uint32_t bar) {
  asm volatile(EL("cp.async.bulk.tensor.3d.shared::cluster.global.mbarrier::complete_tx::bytes [%0], [%1, {%3, %4, %5}], [%2];")
               ::"r"(dst), "l"(m), "r"(bar), "r"(c0), "r"(c1), "r"(c2) : "memory");
}
DEVINL void tma_ld5(uint32_t dst, const CUtensorMap* m, int c2, int c3, int c4, uint32_t bar) {
  asm volatile(EL("cp.async.bulk.tensor.5d.shared::cluster.global.mbarrier::complete_tx::bytes [%0], [%1, {0, 0, %3, %4, %5}], [%2];")
               ::"r"(dst), "l"(m), "r"(bar), "r"(c2), "r"(c3), "r"(c4) : "memory");
}
DEVINL void tma_ld_mc(uint32_t dst, const CUtensorMap* m, int c0, int c1, uint32_t bar) {
  asm volatile(EL("cp.async.bulk.tensor.2d.shared::cluster.global.mbarrier::complete_tx::bytes.multicast::cluster [%0], [%1, {%3, %4}], [%2], %5;")
               ::"r"(dst), "l"(m), "r"(bar), "r"(c0), "r"(c1), "h"((uint16_t)3) : "memory");
}
DEVINL void e_arrive_both(uint32_t bar) {
  asm volatile("{\n.reg .pred pe;\n.reg .b32 r0, r1;\nelect.sync _|pe, 0xffffffff;\nmapa.shared::cluster.u32 r0, %0, 0;\nmapa.shared::cluster.u32 r1, %0, 1;\n"
               "@pe mbarrier.arrive.shared::cluster.b64 _, [r0];\n@pe mbarrier.arrive.shared::cluster.b64 _, [r1];\n}" ::"r"(bar) : "memory");
}
DEVINL void push_peer(uint32_t dst, uint32_t src, uint32_t bar, uint32_t peer) {
  asm volatile("{\n.reg .pred pe;\n.reg .b32 d, b;\nelect.sync _|pe, 0xffffffff;\nmapa.shared::cluster.u32 d, %0, %3;\nmapa.shared::cluster.u32 b, %2, %3;\n"
               "@pe cp.async.bulk.shared::cluster.shared::cta.mbarrier::complete_tx::bytes [d], [%1], 16384, [b];\n}" ::"r"(dst), "r"(src), "r"(bar), "r"(peer) : "memory");
}
DEVINL void tma_st(const CUtensorMap* m, int c0, int c1, uint32_t src) {
  asm volatile(EL("cp.async.bulk.tensor.2d.global.shared::cta.bulk_group [%0, {%2, %3}], [%1];") ::"l"(m), "r"(src), "r"(c0), "r"(c1) : "memory");
}
DEVINL void bulk_commit() { asm volatile("cp.async.bulk.commit_group;" ::: "memory"); }
template <int N> DEVINL void bulk_wait_n() { asm volatile("cp.async.bulk.wait_group %0;\nbar.warp.sync 0xffffffff;" ::"n"(N) : "memory"); }
DEVINL void l2_prefetch(const void* g, uint32_t bytes) { asm volatile(EL("cp.async.bulk.prefetch.L2.global [%0], %1;") ::"l"(g), "r"(bytes) : "memory"); }
DEVINL void fence_async_smem() { asm volatile("fence.proxy.async.shared::cta;" ::: "memory"); }
DEVINL void fence_async_gl() { asm volatile("fence.proxy.async.global;" ::: "memory"); }
DEVINL void cluster_wait() { asm volatile("barrier.cluster.wait.aligned;" ::: "memory"); }
DEVINL void bar_sync(int id, int n) { asm volatile("bar.sync %0, %1;" ::"r"(id), "r"(n) : "memory"); }
DEVINL void bar_arrive(int id, int n) { asm volatile("bar.arrive %0, %1;" ::"r"(id), "r"(n) : "memory"); }
DEVINL uint32_t ld_acquire(const uint32_t* p) { uint32_t v; asm volatile("ld.acquire.gpu.global.u32 %0, [%1];" : "=r"(v) : "l"(p) : "memory"); return v; }
DEVINL void watch(const uint32_t* p, uint32_t target, uint32_t all, uint32_t tag, uint32_t slot) {
  uint32_t seen = 0;
#pragma unroll 1
  for (uint32_t n = 0; n < 200000u && seen != all; n++) {
    const uint32_t m = __ballot_sync(~0u, (int)(ld_acquire(p) - target) >= 0) & all;
    if (m != seen) { seen = m; asm volatile("st.release.cta.shared.u32 [%0], %1;" ::"r"(slot), "r"(tag << 16 | m) : "memory"); }
  }
}
template <bool RELAXED = false> DEVINL void await_bit(uint32_t slot, uint32_t tag, int j, uint32_t& rdy) {
  if ((rdy >> j) & 1) return;
#pragma unroll 1
  for (uint32_t n = 0; n < 8000000u; n++) {
    uint32_t v;
    asm volatile("ld.acquire.cta.shared.u32 %0, [%1];" : "=r"(v) : "r"(slot) : "memory");
    if ((v >> 16) == tag && ((v >> j) & 1)) { rdy = v; break; }
    if (RELAXED) __nanosleep(200); else if (PSLEEP) __nanosleep(PSLEEP);
  }
  asm volatile("fence.proxy.async.global;" ::: "memory");
}
DEVINL void poll_ge(const uint32_t* p, uint32_t target) {
#pragma unroll 1
  for (uint32_t n = 0; n < 200000u; n++) if (__all_sync(~0u, (int)(ld_acquire(p) - target) >= 0)) break;
}
DEVINL int lane_id() { int v; asm volatile("mov.u32 %0, %%laneid;" : "=r"(v)); return v; }
__host__ DEVINL int remap(int v) {
  const int c = v >> 1, u = c - 36, r = (u * 37) >> 8;
  const int L = max(c - 4 + max(r + 1, 0), (c - 4) >> 31 & (32 + 8 * c));
  return 2 * L + (v & 1);
}
DEVINL int block_id() { int v; asm volatile("mov.u32 %0, %%ctaid.x;" : "=r"(v)); return v; }
#define cta_id() prm.map[block_id()]
#define IDS() const int lane = lane_id(), b = cta_id(), bm = b >> 4, bn = b & 15, rank = b & 1, pm = 2 * bm + (bn >> 3), pn = bn & 7, po = pm & 1; \
  (void)lane; (void)bm; (void)bn; (void)rank; (void)pm; (void)pn; (void)po
DEVINL void st_tagged(unsigned long long* p, uint32_t v, uint32_t tag) {
  asm volatile("{\n.reg .b64 t;\nmov.b64 t, {%1, %2};\nst.relaxed.gpu.global.b64 [%0], t;\n}" ::"l"(p), "r"(v), "r"(tag) : "memory");
}
DEVINL float ex2(float x) { float y; asm("ex2.approx.ftz.f32 %0, %1;" : "=f"(y) : "f"(x)); return y; }
DEVINL float rcp(float x) { float y; asm("rcp.approx.ftz.f32 %0, %1;" : "=f"(y) : "f"(x)); return y; }
DEVINL uint32_t pack2(float lo, float hi) { uint32_t r; asm("cvt.rn.bf16x2.f32 %0, %1, %2;" : "=r"(r) : "f"(hi), "f"(lo)); return r; }
DEVINL float bf_lo(uint32_t w) { return __uint_as_float(w << 16); }
DEVINL float bf_hi(uint32_t w) { return __uint_as_float(w & 0xFFFF0000u); }
DEVINL float bf_round(float x) { return bf_lo(pack2(x, 0.f)); }
DEVINL uint32_t add_bf16x2(uint32_t a, uint32_t b) { uint32_t r; asm("add.rn.bf16x2 %0, %1, %2;" : "=r"(r) : "r"(a), "r"(b)); return r; }
DEVINL void stsm4(uint32_t addr, uint32_t a, uint32_t b, uint32_t c, uint32_t d) {
  asm volatile("stmatrix.sync.aligned.m8n8.x4.shared.b16 [%0], {%1, %2, %3, %4};" ::"r"(addr), "r"(a), "r"(b), "r"(c), "r"(d) : "memory");
}
DEVINL void ldsm4(uint32_t addr, uint32_t (&r)[4]) {
  asm volatile("ldmatrix.sync.aligned.m8n8.x4.shared.b16 {%0, %1, %2, %3}, [%4];" : "=r"(r[0]), "=r"(r[1]), "=r"(r[2]), "=r"(r[3]) : "r"(addr) : "memory");
}
DEVINL void ldsm4t(uint32_t addr, uint32_t (&r)[4]) {
  asm volatile("ldmatrix.sync.aligned.m8n8.x4.trans.shared.b16 {%0, %1, %2, %3}, [%4];" : "=r"(r[0]), "=r"(r[1]), "=r"(r[2]), "=r"(r[3]) : "r"(addr) : "memory");
}
DEVINL void sts128(uint32_t addr, uint32_t a, uint32_t b, uint32_t c, uint32_t d) {
  asm volatile("st.shared.v4.b32 [%0], {%1, %2, %3, %4};" ::"r"(addr), "r"(a), "r"(b), "r"(c), "r"(d) : "memory");
}
DEVINL float4 lds128f(uint32_t addr) { float4 v; asm volatile("ld.shared.v4.f32 {%0, %1, %2, %3}, [%4];" : "=f"(v.x), "=f"(v.y), "=f"(v.z), "=f"(v.w) : "r"(addr) : "memory"); return v; }
DEVINL float lds32f(uint32_t addr) { float v; asm volatile("ld.shared.f32 %0, [%1];" : "=f"(v) : "r"(addr) : "memory"); return v; }
DEVINL float2 lds64f(uint32_t addr) { float2 v; asm volatile("ld.shared.v2.f32 {%0, %1}, [%2];" : "=f"(v.x), "=f"(v.y) : "r"(addr) : "memory"); return v; }
DEVINL void mma16816(float (&d)[4], uint32_t a0, uint32_t a1, uint32_t a2, uint32_t a3, uint32_t b0, uint32_t b1) {
  asm("mma.sync.aligned.m16n8k16.row.col.f32.bf16.bf16.f32 {%0, %1, %2, %3}, {%4, %5, %6, %7}, {%8, %9}, {%0, %1, %2, %3};"
               : "+f"(d[0]), "+f"(d[1]), "+f"(d[2]), "+f"(d[3]) : "r"(a0), "r"(a1), "r"(a2), "r"(a3), "r"(b0), "r"(b1));
}
DEVINL void mma1688(float (&d)[4], uint32_t a0, uint32_t a1, uint32_t b0) {
  asm("mma.sync.aligned.m16n8k8.row.col.f32.bf16.bf16.f32 {%0, %1, %2, %3}, {%4, %5}, {%6}, {%0, %1, %2, %3};"
               : "+f"(d[0]), "+f"(d[1]), "+f"(d[2]), "+f"(d[3]) : "r"(a0), "r"(a1), "r"(b0));
}
DEVINL void mma16816h(float (&d)[4], uint32_t a0, uint32_t a1, uint32_t a2, uint32_t a3, uint32_t b0, uint32_t b1) {
  asm("mma.sync.aligned.m16n8k16.row.col.f32.f16.f16.f32 {%0, %1, %2, %3}, {%4, %5, %6, %7}, {%8, %9}, {%0, %1, %2, %3};"
               : "+f"(d[0]), "+f"(d[1]), "+f"(d[2]), "+f"(d[3]) : "r"(a0), "r"(a1), "r"(a2), "r"(a3), "r"(b0), "r"(b1));
}
template <int N> DEVINL void fence_regs(uint32_t (&d)[N]) {
#pragma unroll
  for (int i = 0; i < N; i++) asm volatile("" : "+r"(d[i])::"memory");
}
template <int N> DEVINL void fence_regs(float (&d)[N]) {
#pragma unroll
  for (int i = 0; i < N; i++) asm volatile("" : "+f"(d[i])::"memory");
}

__device__ __align__(1024) bf16 g_xs[2048 * 1024];
__device__ __align__(1024) bf16 g_os[2048 * 1024];
__device__ __align__(1024) bf16 g_k[32 * 2048 * 32];
__device__ __align__(1024) bf16 g_v[32 * 2048 * 32];
__device__ __align__(128) float2 g_stats[8 * 2048];
__device__ __align__(16) float g_csp[2 * 16 * 8 * 192];
__device__ __align__(128) float g_kn[2 * 128 * 32];
__device__ unsigned long long g_halo[2 * 128 * 32 * 32];
__device__ __align__(128) uint32_t g_cnt[256 * 32];
__device__ uint32_t g_epoch;

DEVINL uint32_t* cnt_x(int l, int bm) { return g_cnt + (l * 8 + bm) * 32; }
DEVINL uint32_t* cnt_o(int l, int pm, int h) { return g_cnt + (32 + (l * 16 + pm) * 2 + h) * 32; }
DEVINL uint32_t* cnt_kv(int lb, int bn) { return g_cnt + (160 + lb * 16 + bn) * 32; }
DEVINL uint32_t* cnt_ad(int bn) { return g_cnt + (192 + bn) * 32; }
DEVINL uint32_t* cnt_cs(int t, int bn) { return g_cnt + (208 + t * 16 + bn) * 32; }

DEVINL int qord(int i, int l, int pn) { return l == 0 ? i : i < 4 ? ((2 * pn) ^ (i & 2)) + (i & 1) : i - 4 < 2 * (pn & 6) ? i - 4 : i; }
struct Params {
  CUtensorMap m[17];
  const bf16* x0;
  const bf16* wq[2];
  const bf16* wo[2];
  uint32_t* epoch;
  uint32_t zero;
  int map[128];
};
enum { M_X0A = 0, M_XSA, M_WQA, M_WQB, M_WOA, M_WOB, M_OS, M_K, M_V, M_X0R, M_XSR, M_XSO, M_OUT, M_XST, M_X0H, M_K4, M_V4, M_COUNT };

constexpr uint32_t QSTG = 57344;
constexpr uint32_t T0 = 65536, TSTG = 32768;
constexpr uint32_t ONES = 229376;
constexpr uint32_t PSTG = 32768, RES = 196608;
constexpr uint32_t ASC = 17408;
constexpr uint32_t RSTD = 229376, MEAN = 230400, COLS = 230912, KMAX = 231680, B_QD = 231688, BARS = 232192, SMEM_BYTES = 232448;
constexpr uint32_t B_QF = BARS, B_QE = BARS + 32, B_TF = BARS + 64, B_TE = BARS + 96, B_PF = BARS + 128, B_PE = BARS + 176,
                   B_RF = BARS + 224, W_X = BARS + 232, W_O = BARS + 236, B_QL = BARS + 240, B_PA = BARS + 248;
enum { NB_ST = 1, NB_KV = 2  , NB_DONE = 3, NB_SC = 4, NB_SIG = 5  , NB_KN = 9  , NB_X = 11, NB_HALO = 12  , NB_X0 = 15 };

DEVINL uint32_t pslot_b(uint32_t s, int l) { return ((((l & 1) ? 0x320415u : 0x468795u) >> (4 * s)) & 15) * 16384u; }
DEVINL uint32_t pslot_a(uint32_t s, int l) { return ((((l & 1) ? 0xBA7896u : 0x32DCBAu) >> (4 * s)) & 15) * 16384u; }

#define G1 2
#define G2 0
#define G3 2
#define KC (11 + 2 * wg)
#define NA2 2
#define RESI 9
#define PERHEAD 1
#define LA 1
#define LB 1
#define PFETCH 0
#define PFW 3
#define PFI 8
#define NQ 32
#define OA 0x10
#define OB 0x10
#define LAG 2
#define QK_A wgmma_m64n32k16_rs_nb_h
#define QK_B wgmma_m64n32k16_rs_nb_hh
constexpr float QSCALE = 0.17677669529663687f * 1.4426950408889634f;

DEVINL uint32_t hfma2(uint32_t a, uint32_t b, uint32_t c) { uint32_t r; asm("fma.rn.f16x2 %0, %1, %2, %3;" : "=r"(r) : "r"(a), "r"(b), "r"(c)); return r; }
DEVINL uint32_t pack2h(float lo, float hi) { uint32_t r; asm("cvt.rn.f16x2.f32 %0, %1, %2;" : "=r"(r) : "f"(hi), "f"(lo)); return r; }
DEVINL uint32_t h2_to_bf2(uint32_t h) {
  float a, b;
  asm("{\n.reg .b16 l, h;\nmov.b32 {l, h}, %2;\ncvt.f32.f16 %0, l;\ncvt.f32.f16 %1, h;\n}" : "=f"(a), "=f"(b) : "r"(h));
  return pack2(a, b);
}
DEVINL uint32_t exp2_h2(uint32_t s) {
  const uint32_t r = hfma2(s, 0x00800080u, 0x007E007Eu);
  const uint32_t g = hfma2(hfma2(r, 0xF800F800u, 0x33FD33FDu), 0x44004400u, s);
  return r * 128u + hfma2(hfma2(g, g, 0x0DE10DE1u), g, 0x00300030u);
}
constexpr uint32_t NOT_F16 = 0x7FC00000u, K_LO = 0x35000000u  ;
DEVINL uint32_t f16_class(uint32_t norm2, uint32_t lo) { return norm2 - lo > 0x4E800000u - lo ? NOT_F16 : norm2; }

DEVINL void attn_slow(const uint32_t (&q)[8], float up, int head, const float* kn, float (&res)[20], int lane) {
  const int g = lane >> 2, qd = lane & 3;
  const bf16* kb = g_k + (size_t)head * 2048 * 32;
  const bf16* vb = g_v + (size_t)head * 2048 * 32;
  float o[4][4], m0 = -INFINITY, m1 = -INFINITY, l0 = 0.f, l1 = 0.f;
#pragma unroll
  for (int j = 0; j < 4; j++) { o[j][0] = o[j][1] = o[j][2] = o[j][3] = 0.f; }
#pragma unroll 1
  for (int k0 = 0; k0 < 2048; k0 += 16) {
    float s[2][4];
    const bool kh = __float_as_uint(__ldcg(kn + (k0 >> 8) * 32 + ((k0 >> 6) & 1) * 8 + ((k0 >> 7) & 1) * 4 + ((k0 >> 4) & 3))) != NOT_F16;
#pragma unroll
    for (int nt = 0; nt < 2; nt++) {
      s[nt][0] = s[nt][1] = s[nt][2] = s[nt][3] = 0.f;
      const uint32_t* kp = (const uint32_t*)(kb + (size_t)(k0 + nt * 8 + g) * 32) + qd;
      uint32_t kf[4];
#pragma unroll
      for (int i = 0; i < 4; i++) { kf[i] = __ldcg(kp + 4 * i); if (kh) kf[i] = h2_to_bf2(kf[i]); }
      mma16816(s[nt], q[0], q[1], q[2], q[3], kf[0], kf[1]);
      mma16816(s[nt], q[4], q[5], q[6], q[7], kf[2], kf[3]);
      s[nt][0] *= up; s[nt][1] *= up; s[nt][2] *= up; s[nt][3] *= up;
    }
    float a0 = fmaxf(fmaxf(s[0][0], s[0][1]), fmaxf(s[1][0], s[1][1]));
    float a1 = fmaxf(fmaxf(s[0][2], s[0][3]), fmaxf(s[1][2], s[1][3]));
    a0 = fmaxf(a0, __shfl_xor_sync(~0u, a0, 1)); a0 = fmaxf(a0, __shfl_xor_sync(~0u, a0, 2));
    a1 = fmaxf(a1, __shfl_xor_sync(~0u, a1, 1)); a1 = fmaxf(a1, __shfl_xor_sync(~0u, a1, 2));
    const float n0 = fmaxf(m0, a0), n1 = fmaxf(m1, a1);
    const float c0 = (m0 == n0) ? 1.f : ex2(m0 - n0), c1 = (m1 == n1) ? 1.f : ex2(m1 - n1);
    m0 = n0; m1 = n1;
    const uint32_t p0 = pack2(ex2(s[0][0] - n0), ex2(s[0][1] - n0)), p1 = pack2(ex2(s[0][2] - n1), ex2(s[0][3] - n1));
    const uint32_t p2 = pack2(ex2(s[1][0] - n0), ex2(s[1][1] - n0)), p3 = pack2(ex2(s[1][2] - n1), ex2(s[1][3] - n1));
    l0 = l0 * c0 + bf_lo(p0) + bf_hi(p0) + bf_lo(p2) + bf_hi(p2);
    l1 = l1 * c1 + bf_lo(p1) + bf_hi(p1) + bf_lo(p3) + bf_hi(p3);
#pragma unroll
    for (int j = 0; j < 4; j++) {
      o[j][0] *= c0; o[j][1] *= c0; o[j][2] *= c1; o[j][3] *= c1;
      const unsigned short* vp = (const unsigned short*)(vb + (size_t)(k0 + 2 * qd) * 32 + j * 8 + g);
      const uint32_t b0 = (uint32_t)__ldcg(vp) | ((uint32_t)__ldcg(vp + 32) << 16);
      const uint32_t b1 = (uint32_t)__ldcg(vp + 256) | ((uint32_t)__ldcg(vp + 288) << 16);
      mma16816(o[j], p0, p1, p2, p3, b0, b1);
    }
  }
  l0 += __shfl_xor_sync(~0u, l0, 1); l0 += __shfl_xor_sync(~0u, l0, 2);
  l1 += __shfl_xor_sync(~0u, l1, 1); l1 += __shfl_xor_sync(~0u, l1, 2);
#pragma unroll
  for (int j = 0; j < 4; j++) { res[4 * j] = o[j][0]; res[4 * j + 1] = o[j][1]; res[4 * j + 2] = o[j][2]; res[4 * j + 3] = o[j][3]; }
  res[16] = l0; res[18] = l1;
}

__global__ void __cluster_dims__(2, 1, 1) __launch_bounds__(384, 1) fused_kernel(const __grid_constant__ Params prm) {
  extern __shared__ __align__(1024) char smem[];
  const uint32_t sb = (uint32_t)__cvta_generic_to_shared(smem);
  const int tid = threadIdx.x;
  const int wid = __shfl_sync(0xffffffffu, tid >> 5, 0), wg = wid >> 2, w = wid & 3;
  const int bm = remap(blockIdx.x) >> 4, bn = remap(blockIdx.x) & 15;
  auto first_tile = [&](int kt) {
    e_expect_tx(sb + B_QF + 8 * kt, QSTG);
    tma_ld(sb + kt * QSTG, &prm.m[M_X0A], kt * 64, bm * 256, sb + B_QF + 8 * kt);
    tma_ld3(sb + kt * QSTG + 32768, &prm.m[M_WQA], bn * 64, kt * 64, 0, sb + B_QF + 8 * kt);
  };
  if (wid == 8) {
    e_init(sb + B_QF, 1);
    asm volatile("fence.mbarrier_init.release.cluster;" ::: "memory");
    first_tile(0);
  }
  if (wid < 8) {
#pragma unroll
    for (int i = 0; i < 4; i++) {
      const uint32_t cnt = (uint32_t)((i == 0 ? 0x14112140 : i == 1 ? 0x04112141 : i == 2 ? 0x14412141 : 0x24412141) >> (4 * wid)) & 7;
      if (cnt) e_init(sb + BARS + 32 * wid + 8 * i, cnt);
    }
    if (wid == 0 || wid == 7) e_init(sb + B_QD + (wid & 1) * 8, 1);
    if (tid == 255) *(uint2*)(smem + W_X) = make_uint2(0u, 0u);
    asm volatile("fence.mbarrier_init.release.cluster;" ::: "memory");
  }
  const uint32_t epoch = *(volatile uint32_t*)prm.epoch;
  __syncthreads();
  asm volatile("barrier.cluster.arrive.relaxed.aligned;" ::: "memory");

  if (wg == 2) {
    asm volatile("setmaxnreg.dec.sync.aligned.u32 56;");
    const uint32_t ep1 = epoch + 1;
    if (w == 0) {
      first_tile(1);
      mbar_wait(sb + B_QF, 0);
      first_tile(2); first_tile(3);
#pragma unroll 1
      for (int kt = 4; kt < 16; kt++) l2_prefetch(prm.wq[0] + kt * 196608 + blockIdx.x * 1536, 3072);
      cluster_wait();
#pragma unroll 1
      for (int l = 0; l < 4; l++) {
        IDS();
        const CUtensorMap* mw = &prm.m[M_WQA + (l & 1)];
        const CUtensorMap* mh = &prm.m[l == 0 ? M_X0H : M_XSO];
        const CUtensorMap* mo = &prm.m[M_WOA + (l & 1)];
        auto q_b = [&](int i) {
          const int s = i & 3;
          mbar_wait(sb + B_QE + 8 * s, ((i >> 2) & 1) ^ 1);
          e_expect_tx(sb + B_QF + 8 * s, QSTG);
          tma_ld3(sb + s * QSTG + 32768, mw, bn * 64, qord(i, l, pn) * 64, 0, sb + B_QF + 8 * s);
        };
        uint32_t rdy = l ? 0u : ~0u;
        auto q_a = [&](int i) {
          const int kt = qord(i, l, pn);
          await_bit(sb + W_X, l, kt >> 1, rdy);
          tma_ld_mc(sb + (i & 3) * QSTG + rank * 16384, mh, kt * 64, bm * 256 + rank * 128, sb + B_QF + 8 * (i & 3));
        };
        if (l > 0) {
#pragma unroll 1
          for (int i = 0; i < 4; i++) {
            const int kt = qord(i, l, pn);
            await_bit(sb + W_X, l, kt >> 1, rdy);
            e_expect_tx(sb + B_QF + 8 * i, 16384);
            tma_ld(sb + i * QSTG + (po ^ 1) * 16384, &prm.m[M_XSO], kt * 64, (pm ^ 1) * 128, sb + B_QF + 8 * i);
          }
        }
#pragma unroll 1
        for (int i = 4; i < 16; i++) {
          q_b(i); q_a(i);
          if (l == 0 && (PFW & 1) && i >= PFI && i < PFI + 4) l2_prefetch(prm.wq[1] + (blockIdx.x * 4 + i - PFI) * 6144, 12288);
          if (l < 2 && (PFW & 2) && i == PFI + 4) l2_prefetch(prm.wo[l] + blockIdx.x * 8192, 16384);
        }
        if (l & 1) {
          if (l == 3) poll_ge(cnt_ad(bn), ep1 * 16);
          const int krow = 2 * bn * 2048 + bm * 256;
          uint32_t* kvc = cnt_kv(l >> 1, bn);
#pragma unroll 1
          for (int m = 1; m >= 0; m--) {
            bar_sync(m ? NB_ST : NB_KV, 288);
#pragma unroll
            for (int i = 0; i < 4; i++) tma_st(&prm.m[M_K4 + (i >> 1)], 0, krow + (i & 1) * 128 + m * 64, sb + T0 + i * 8192 + m * 4096);
            if (m) {
              sts128(sb + ONES + lane * 32, 0x3f803f80u, 0x3f803f80u, 0x3f803f80u, 0x3f803f80u);
              sts128(sb + ONES + lane * 32 + 16, 0x3f803f80u, 0x3f803f80u, 0x3f803f80u, 0x3f803f80u);
              fence_async_smem();
              __syncwarp();
            }
          }
          e_arrive(sb + B_TF);
          bulk_commit(); bulk_wait_n<0>();
          e_red(kvc + bm);
          bar_sync(NB_KV + 12, 288);
          tma_st(&prm.m[M_K], 0, krow + 2048, sb);
          tma_st(&prm.m[M_V], 0, krow + 2048, sb + 16384);
          bulk_commit();
          uint32_t seen = 0;
#pragma unroll 1
          for (int it = 1; it < 16; it++) {
            const int s = it & 3, blk = it;
            if (it == 4) { bulk_wait_n<0>(); e_red(kvc + bm); }
            if (it == 12) { e_expect_tx(sb + B_RF, 32768); tma_ld3(sb + RES, &prm.m[M_XSR], 0, pm * 128, 2 * pn, sb + B_RF); }
            if (it == 2 || it == 3) mbar_wait(sb + B_TF + 8 * (it - 1), 0);
            MWL(sb + B_TE + 8 * s, ((it >> 2) & 1) ^ 1);
            if (it < 8) {
#pragma unroll 1
              for (uint32_t n = 0; n < 200000u && !((seen >> it) & 1); n++)
                seen = __ballot_sync(~0u, (int)(ld_acquire(kvc + ((bm + lane) & 7)) - (ep1 * 2 - 1)) >= 0);
              fence_async_gl();
            } else if (it == 8) { poll_ge(kvc + (lane & 7), ep1 * 2); fence_async_gl(); bar_arrive(NB_HALO, 64); }
            else if (it == 15) bar_arrive(NB_HALO + 1, 64);
            const int row = (2 * bn + (it >> 3)) * 2048 + ((bm + blk) & 7) * 256;
            e_expect_tx(sb + B_TF + 8 * s, 32768);
            tma_ld(sb + T0 + s * TSTG, &prm.m[M_K], 0, row, sb + B_TF + 8 * s);
            tma_ld(sb + T0 + s * TSTG + 16384, &prm.m[M_V], 0, row, sb + B_TF + 8 * s);
          }
        }
        auto p_b = [&](int i, uint32_t s, uint32_t par) {
          mbar_wait(sb + B_PE + 8 * s, par ^ 1);
          e_expect_tx(sb + B_PF + 8 * s, PSTG);
          tma_ld5(sb + pslot_b(s, l), mo, i >> 3, 2 * (i & 7), 2 * pn, sb + B_PF + 8 * s);
        };
        auto p_a = [&](int i, uint32_t s) {
          await_bit(sb + W_O, l + 1, i, rdy);
          tma_ld_mc(sb + pslot_a(s, l) + rank * 8192, &prm.m[M_OS], i * 64, pm * 128 + rank * 64, sb + B_PF + 8 * s);
        };
        auto p_a2 = [&](int i) {
          await_bit(sb + W_O, l + 1, i, rdy);
          tma_ld(sb + pslot_a(i, l), &prm.m[M_OS], i * 64, pm * 128, sb + B_PF + 8 * i);
          tma_ld(sb + pslot_a(i, l) + 8192, &prm.m[M_OS], i * 64, pm * 128 + 64, sb + B_PF + 8 * i);
        };
        rdy = 0;
        if (l & 1) {
#pragma unroll 1
          for (int u = 0; u < 6; u++) { const int i = (0x205413 >> (4 * u)) & 7; if (u == 4) MWL(sb + B_TE, 1); p_b(i, i, i < 4 ? 1 : 0); }
#pragma unroll 1
          for (int u = 0; u < 6; u++) {
            const int i = (0x542130 >> (4 * u)) & 7;
            if (!(u & 1)) MWL(sb + B_TE + 8 + 4 * u, 1);
            p_a2(i);
          }
        } else {
#pragma unroll 1
          for (int u = 0; u < 5; u++) { const int i = (0x32140 >> (4 * u)) & 7; if (!(u & 5)) mbar_wait(sb + B_QE + 8 + 4 * u, 1); p_b(i, i, 0); }
          mbar_wait(sb + B_QE + 24, 1);
          if (PLATE) bar_sync(NB_KN, 96);
#pragma unroll 1
          for (int i = 0; i < 4; i++) { if (i < NA2) p_a2(i); else p_a(i, i); }
          bar_sync(NB_DONE, 96);
          e_arrive_both(sb + B_PA);
          p_b(5, 5, 0);
          mbar_wait(sb + B_PA, (l >> 1) & 1);
          p_a(4, 4); p_a(5, 5);
        }
        uint32_t s = 0, lap = 1;
#pragma unroll 1
        for (int i = 6; i < 16; i++) {
          if (i == RESI && !(l & 1)) { e_expect_tx(sb + B_RF, 32768); tma_ld3(sb, &prm.m[l == 0 ? M_X0R : M_XSR], 0, pm * 128, 2 * pn, sb + B_RF); }
          p_b(i, s, ((s < 4 ? l : 0) + lap) & 1);
          p_a(i, s);
          if (++s == 6) { s = 0; lap++; }
        }
        const CUtensorMap* mn = &prm.m[M_WQA + ((l + 1) & 1)];
        if (l < 3) {
          mbar_wait(sb + B_PE + 8 * 4, 1); mbar_wait(sb + B_PE + 8 * 5, 1);
          tma_ld3(sb + 32768, mn, bn * 64, 2 * pn * 64, 0, sb + B_QL);
          mbar_wait(sb + B_PE + 8 * 0, l & 1);
          tma_ld3(sb + QSTG + 32768, mn, bn * 64, (2 * pn + 1) * 64, 0, sb + B_QL);
          mbar_wait(sb + B_PE + 8 * 1, l & 1);
          e_expect_tx(sb + B_QD, 40960);
          tma_ld3(sb + 2 * QSTG + 32768, mn, bn * 64, ((2 * pn) ^ 2) * 64, 0, sb + B_QD);
          bar_sync(NB_X, 288);
          e_expect_tx(sb + B_QL, 49152);
          e_expect_tx(sb + B_QD + 8, 40960);
          tma_ld3(sb + 3 * QSTG + 32768, mn, bn * 64, (((2 * pn) ^ 2) + 1) * 64, 0, sb + B_QD + 8);
        }
      }
      if (blockIdx.x == 0 && lane_id() == 0) *(volatile uint32_t*)prm.epoch = ep1;
    } else {
      const int hw = w - 1;
      if (hw == 1 && lane_id() < M_COUNT) asm volatile("prefetch.tensormap [%0];" ::"l"(&prm.m[lane_id()]) : "memory");
      cluster_wait();
      mbar_wait(sb + B_QF, 0);
#pragma unroll 1
      for (int l = 0; l < 4; l++) {
        IDS();
        if (hw == 2 && l > 0) watch(cnt_x(l, bm) + (lane & 7), ep1 * 2, 0xFFu, l, sb + W_X);
        if (l == 0) {
#pragma unroll 1
          for (int r = 2 * hw; r < 16; r += 6) {
            const uint4* p = (const uint4*)(prm.x0 + (size_t)(b * 16 + r) * 1024) + lane;
            float s1[2] = {0.f, 0.f}, s2[2] = {0.f, 0.f};
#pragma unroll
            for (int i = 0; i < 8; i++) {
              const uint4 v = __ldg(p + 32 * i);
              const uint32_t u[4] = {v.x, v.y, v.z, v.w};
#pragma unroll
              for (int k = 0; k < 4; k++) { const float a = bf_lo(u[k]), c = bf_hi(u[k]); s1[i >> 2] += a + c; s2[i >> 2] = fmaf(a, a, fmaf(c, c, s2[i >> 2])); }
            }
#pragma unroll
            for (int o = 16; o; o >>= 1)
#pragma unroll
              for (int rr = 0; rr < 2; rr++) { s1[rr] += __shfl_xor_sync(~0u, s1[rr], o); s2[rr] += __shfl_xor_sync(~0u, s2[rr], o); }
            if (lane == 0) *(float4*)&g_stats[b * 16 + r] = make_float4(s1[0], s2[0], s1[1], s2[1]);
          }
        }
        if (l == 1) { uint32_t rdy = 0; await_bit<true>(sb + W_X, 1, pn, rdy); mbar_hint(sb + B_QF + 8, 0); }
        if (l < 2) {
          float cs[8];
#pragma unroll
          for (int i = 0; i < 8; i++) cs[i] = 0.f;
          const uint4* wp = (const uint4*)(prm.wq[l] + (size_t)(bm * 128 + (lane >> 3)) * 3072 + hw * 1024 + bn * 64) + (lane & 7);
#pragma unroll 8
          for (int i = 0; i < 32; i++) {
            const uint4 v = __ldg(wp + (size_t)i * 4 * 384);
            cs[0] += bf_lo(v.x); cs[1] += bf_hi(v.x); cs[2] += bf_lo(v.y); cs[3] += bf_hi(v.y);
            cs[4] += bf_lo(v.z); cs[5] += bf_hi(v.z); cs[6] += bf_lo(v.w); cs[7] += bf_hi(v.w);
          }
#pragma unroll
          for (int i = 0; i < 8; i++) { cs[i] += __shfl_xor_sync(~0u, cs[i], 8); cs[i] += __shfl_xor_sync(~0u, cs[i], 16); }
          if (lane < 8) {
            float4* d = (float4*)(g_csp + ((l * 16 + bn) * 8 + bm) * 192 + hw * 64 + lane * 8);
            d[0] = make_float4(cs[0], cs[1], cs[2], cs[3]); d[1] = make_float4(cs[4], cs[5], cs[6], cs[7]);
          }
          __syncwarp();
          asm volatile("fence.acq_rel.gpu;" ::: "memory");
          e_red_relaxed(cnt_cs(l, bn));
          if (l == 0) e_red_relaxed(cnt_x(0, bm) + pn);
          poll_ge(lane < 8 && l == 0 ? cnt_x(0, bm) + lane : cnt_cs(l, bn), ep1 * (lane < 8 && l == 0 ? 6 : 24));
        }
        if (l > 0) {
          uint32_t rdy = 0;
#pragma unroll 1
          for (int j = 0; j < 8; j++) await_bit<true>(sb + W_X, l, j, rdy);
        }
#pragma unroll 1
        for (int it = hw * 32 + lane; it < 176; it += 96) {
          const bool rows = it < 128;
          const float4* p = rows ? (const float4*)(g_stats + bm * 256) + it : (const float4*)(g_csp + ((l & 1) * 16 + bn) * 8 * 192) + (it - 128);
          const int stride = rows ? 1024 : 48, np = rows && l == 0 ? 1 : 8;
          float4 a = make_float4(0.f, 0.f, 0.f, 0.f);
#pragma unroll
          for (int k = 0; k < 8; k++) if (k < np) { const float4 v = __ldcg(p + k * stride); a.x += v.x; a.y += v.y; a.z += v.z; a.w += v.w; }
          if (rows) {
            const float m0 = a.x * (1.f / 1024.f), m1 = a.z * (1.f / 1024.f);
            const float v0 = fmaxf(a.y * (1.f / 1024.f) - m0 * m0, 0.f), v1 = fmaxf(a.w * (1.f / 1024.f) - m1 * m1, 0.f);
            const float r0 = __fdividef(1.f, bf_round(sqrtf(bf_round(bf_round(v0) + 1e-5f)))), r1 = __fdividef(1.f, bf_round(sqrtf(bf_round(bf_round(v1) + 1e-5f))));
            *(float2*)(smem + RSTD + it * 8) = make_float2(r0, r1);
            *(uint32_t*)(smem + MEAN + it * 4) = pack2(-m0, -m1);
          } else {
            float2* d = (float2*)(smem + COLS) + ((it - 128) >> 2) * 8 + (it & 1) * 4 + ((it >> 1) & 1);
            d[0] = make_float2(a.y, a.x); d[2] = make_float2(a.w, a.z);
          }
        }
        __syncwarp();
        if (lane == 0) asm volatile("red.release.cta.shared.add.u32 [%0], 0x100;" ::"r"(sb + W_X) : "memory");
        if (hw == 2) {
          if (!(l & 1)) {
            bar_sync(NB_ST, 288);
            const volatile unsigned long long* hp = g_halo + ((size_t)(l >> 1) * 128 + b - 16) * 1024 + lane;
#pragma unroll 1
            for (int h = 0; h < 2; h++) {
              uint32_t t[16];
#pragma unroll
              for (int i = 0; i < 16; i++) t[i] = 0;
#pragma unroll 1
              for (uint32_t n = bm ? 0 : 100000u; n < 100000u; n++) {
                uint32_t miss = 0;
#pragma unroll
                for (int i = 0; i < 16; i++) {
                  const unsigned long long v = hp[h * 512 + i * 32];
                  t[i] = (uint32_t)v; miss |= (uint32_t)(v >> 32) ^ ep1;
                }
                if (__all_sync(~0u, !miss)) break;
              }
              const uint32_t r = (lane & 7) + ((lane >> 3) & 1) * 8, rv = lane >> 2;
#pragma unroll
              for (int jj = 0; jj < 2; jj++) stsm4(sb + 2 * h * ASC + r * 64 + (((2 * jj + (lane >> 4)) ^ ((r >> 1) & 3)) << 4), t[4 * jj], t[4 * jj + 1], t[4 * jj + 2], t[4 * jj + 3]);
              const uint32_t ad = sb + (2 * h + 1) * ASC + rv * 64 + (((lane & 3) ^ ((rv >> 1) & 3)) << 4);
              sts128(ad, t[8], t[10], t[12], t[14]); sts128(ad + 512, t[9], t[11], t[13], t[15]);
              bar_arrive(NB_HALO + h, 64);
            }
          } else {
            bar_sync(NB_HALO, 64);
            const uint4* kp = (const uint4*)(g_kn + ((l >> 1) * 128 + bn * 8) * 32) + 2 * lane;
            const uint4 v = __ldcg(kp), u = __ldcg(kp + 1);
            const uint32_t mx = max(max(max(v.x, v.y), max(v.z, v.w)), max(max(u.x, u.y), max(u.z, u.w)));
            const uint32_t m0 = __reduce_max_sync(~0u, (lane & 2) ? 0u : mx), m1 = __reduce_max_sync(~0u, (lane & 2) ? mx : 0u);
            if (lane == 0) *(uint2*)(smem + KMAX) = make_uint2(m0, m1);
            __syncwarp();
            bar_arrive(NB_KN, 160); bar_arrive(NB_KN + 1, 160);
            bar_sync(NB_HALO + 1, 64);
            watch(cnt_o(l, pm, 0) + (lane & 7), ep1 * 2, 0xFFu, l + 1, sb + W_O);
          }
        } else {
          bar_sync(NB_SIG + 2 * hw, 160); bar_sync(NB_SIG + 2 * hw + 1, 160);
          if (!(l & 1)) bar_arrive(NB_DONE, 96);
          if (hw == (l & 1)) bar_arrive((l & 1) ? NB_DONE : NB_KN, (l & 1) ? 64 : 64 + 32 * PLATE);
          asm volatile("fence.acq_rel.gpu;" ::: "memory");
          e_red_relaxed(cnt_o(l, 2 * bm, hw) + (bn >> 1));
          e_red_relaxed(cnt_o(l, 2 * bm + 1, hw) + (bn >> 1));
          if (hw == 1 && l == 1) { e_red_relaxed(cnt_ad(bn)); e_red_relaxed(cnt_ad(bn)); }
        }
        if (hw == 2) { bar_sync((l & 1) ? NB_DONE : NB_KN, (l & 1) ? 64 : 64 + 32 * PLATE); watch(cnt_o(l, pm, (lane >> 3) & 1) + (lane & 7), ep1 * 2, 0xFFFFu, l + 1, sb + W_O); }
        if (hw < 2 + XLATE && l < 3) {
          bar_sync(NB_X0, 320 + 32 * XLATE);
          if (hw == 0) {
            e_red(cnt_x(l + 1, bm) + pn);
          } else if (hw == 1) {
            mbar_wait(sb + B_PE + 8 * 3, l & 1);
            push_peer(sb + 2 * QSTG + po * 16384, sb + po * 16384, sb + B_QD, rank ^ 1);
            push_peer(sb + 3 * QSTG + po * 16384, sb + QSTG + po * 16384, sb + B_QD + 8, rank ^ 1);
          }
        }
      }
    }
  } else {
    asm volatile("setmaxnreg.inc.sync.aligned.u32 224;");
    const uint32_t zero = prm.zero;
    cluster_wait();
    const uint32_t ep1 = __shfl_sync(~0u, epoch + 1, 0);
#pragma unroll 1
    for (int l = 0; l < 4; l++) {
      {
        float acc[2][96];
#pragma unroll
        for (int i = 0; i < 96; i++) { acc[0][i] = 0.f; acc[1][i] = 0.f; }
        fence_regs(acc[0]); fence_regs(acc[1]);
        const bool early = l > 0 && wg == ((cta_id() >> 3) & 1);
#pragma unroll 1
        for (int kt = 0; kt < 14; kt++) {
          const int s = kt & 3;
          if (l > 0 && kt < 4 && kt != 1) mbar_wait(sb + (kt ? B_QD - 16 + 8 * kt : B_QL), (l + 1) & 1);
          if (!(early && kt < 4)) mbar_wait(sb + B_QF + 8 * s, (kt >> 2) & 1);
          const uint64_t da = mkdesc(sb + s * QSTG + wg * 16384, 16, 1024, 1), db = mkdesc(sb + s * QSTG + 32768, 8192, 1024, 1);
          wg_fence();
#pragma unroll
          for (int k = 0; k < 4; k++)
#pragma unroll
            for (int m = 0; m < 2; m++) wgmma_m64n192k16_ss_tb(acc[m], da + m * 512 + k * 2, db + k * 128, 1);
          wg_commit();
          wg_wait<1>();
          if (early && kt < 5) {
#pragma unroll 1
            for (int i = kt == 3 ? 0 : 3; i < kt; i++) { mbar_wait(sb + B_QF + 8 * i, 0); if (w == 0) e_arrive_both(sb + B_QE + 8 * i); }
          } else if (kt > 0 && w == 0) e_arrive_both(sb + B_QE + 8 * ((kt - 1) & 3));
          if (kt == KC) {
#pragma unroll 1
            for (uint32_t n = 0; n < 4000000u; n++) {
              uint32_t v;
              asm volatile("ld.acquire.cta.shared.u32 %0, [%1];" : "=r"(v) : "r"(sb + W_X) : "memory");
              if ((v >> 8) == (uint32_t)(l * 256 + 3)) break;
            }
            const int lane = lane_id();
            float nm[4];
#pragma unroll
            for (int i = 0; i < 4; i++) nm[i] = bf_lo(*(volatile unsigned short*)(smem + MEAN + (wg * 128 + w * 16 + (lane >> 2) + (i >> 1) * 64 + (i & 1) * 8) * 2));
            wg_wait<0>();
            fence_regs(acc[0]); fence_regs(acc[1]);
#pragma unroll
            for (int j = 0; j < 12; j++) {
              const float4 c = lds128f(sb + COLS + j * 64 + (lane & 3) * 16);
#pragma unroll
              for (int m = 0; m < 2; m++) {
                float* a = &acc[m][8 * j];
                a[0] = fmaf(nm[2 * m], c.y, a[0]); a[1] = fmaf(nm[2 * m], c.x, a[1]); a[2] = fmaf(nm[2 * m + 1], c.y, a[2]); a[3] = fmaf(nm[2 * m + 1], c.x, a[3]);
                a[4] = fmaf(nm[2 * m], c.w, a[4]); a[5] = fmaf(nm[2 * m], c.z, a[5]); a[6] = fmaf(nm[2 * m + 1], c.w, a[6]); a[7] = fmaf(nm[2 * m + 1], c.z, a[7]);
              }
            }
            fence_regs(acc[0]); fence_regs(acc[1]);
          }
        }
        auto part = [&](int s, int m, int k0, int k1) {
          const uint64_t da = mkdesc(sb + s * QSTG + wg * 16384 + m * 8192, 16, 1024, 1), db = mkdesc(sb + s * QSTG + 32768, 8192, 1024, 1);
          pin(zero);
          wg_fence();
#pragma unroll
          for (int k = k0; k < k1; k++) wgmma_m64n192k16_ss_tb(acc[m], da + k * 2, db + k * 128, 1);
          wg_commit();
          pin(zero);
        };
        mbar_wait(sb + B_QF + 16, 1);
        part(2, 1, 0, 4);
        wg_wait<1>();
        if (w == 0) e_arrive_both(sb + B_QE + 8);
        if (!(l & 1)) bar_arrive(NB_ST, 288);
        mbar_wait(sb + B_QF + 24, 1);
        part(3, 1, 0, 4);
        part(2, 0, 0, G1);
        IDS();
        const int g = lane >> 2, qd = lane & 3;
        float rs[2][2];
#pragma unroll
        for (int i = 0; i < 4; i++) rs[i >> 1][i & 1] = lds32f(sb + RSTD + (wg * 128 + w * 16 + g + (i >> 1) * 64 + (i & 1) * 8) * 4);
        auto scale = [&](int gi, int m, float sc) {
          const float r0 = rs[m][0] * sc, r1 = rs[m][1] * sc;
#pragma unroll
          for (int i = 0; i < 16; i++) acc[m][16 * gi + i] *= (i & 2) ? r1 : r0;
        };
        auto pack_b = [&](int gi, int m, uint32_t (&t)[8]) {
#pragma unroll
          for (int i = 0; i < 8; i++) t[i] = pack2(acc[m][16 * gi + 2 * i], acc[m][16 * gi + 2 * i + 1]);
        };
        auto norm_tile = [&](int gi, int m, uint32_t (&t)[8]) { scale(gi, m, 1.f); pack_b(gi, m, t); };
        auto pack_h = [&](int gi, int m, uint32_t (&t)[8]) {
#pragma unroll
          for (int i = 0; i < 8; i++) t[i] = pack2h(acc[m][16 * gi + 2 * i], acc[m][16 * gi + 2 * i + 1]);
        };
        uint32_t q[2][2][8], qn[2][2];
        const uint32_t srow = (lane & 7) + ((lane >> 3) & 1) * 8;
        const uint32_t row0 = wg * 128 + w * 16;
        auto put_kv = [&](int h, int v, int m, const uint32_t (&t)[8]) {
          const uint32_t base = sb + ((l & 1) ? (h ? 0 : T0) + v * 16384 : (2 * h + v) * ASC + 1024) + (row0 + m * 64) * 64;
          if (!v) {
#pragma unroll
            for (int jj = 0; jj < 2; jj++) stsm4(base + srow * 64 + (((2 * jj + (lane >> 4)) ^ ((srow >> 1) & 3)) << 4), t[4 * jj], t[4 * jj + 1], t[4 * jj + 2], t[4 * jj + 3]);
          } else {
            const uint32_t ad = base + g * 64 + ((qd ^ (g >> 1)) << 4);
            sts128(ad, t[0], t[2], t[4], t[6]); sts128(ad + 512, t[1], t[3], t[5], t[7]);
          }
        };
        auto send_halo = [&](int h, int v, const uint32_t (&t)[8]) {
          unsigned long long* hp = g_halo + ((size_t)(l >> 1) * 128 + b) * 1024 + h * 512 + v * 256 + lane;
#pragma unroll
          for (int i = 0; i < 8; i++) st_tagged(hp + i * 32, t[i], ep1);
        };
        auto put_kn = [&](int h, int m, uint32_t kn) {
          if (lane == 0) g_kn[((l >> 1) * 128 + bn * 8 + bm) * 32 + 16 * h + 8 * m + wg * 4 + w] = __uint_as_float(kn);
        };
        auto conv_tile1 = [&](int h) {
          uint32_t t[8], tv[8], kn = NOT_F16;
          norm_tile(4 + h, 1, tv);
          put_kv(h, 1, 1, tv);
          scale(2 + h, 1, 1.f);
          if (h == 0) { if (G1 < 4) part(2, 0, G1, 4); if (G2) part(3, 0, 0, G2); } else if (G3 < 4) part(3, 0, G3, 4);
          if (l & 1) {
            float n[2] = {0.f, 0.f};
#pragma unroll
            for (int i = 0; i < 16; i++) n[(i >> 1) & 1] = fmaf(acc[1][32 + 16 * h + i], acc[1][32 + 16 * h + i], n[(i >> 1) & 1]);
            const float a = ((qd & 1) ? n[1] : n[0]) + __shfl_xor_sync(~0u, (qd & 1) ? n[0] : n[1], 1);
            scale(h, 1, QSCALE / 128.f);
            kn = f16_class(__reduce_max_sync(~0u, __float_as_uint(a + __shfl_xor_sync(~0u, a, 2))), K_LO);
            put_kn(h, 1, kn);
          } else scale(h, 1, 1.f);
          if (kn == NOT_F16) pack_b(2 + h, 1, t); else pack_h(2 + h, 1, t);
          put_kv(h, 0, 1, t);
          if (!(l & 1) && row0 == 176 && bm < 7) { send_halo(h, 0, t); send_halo(h, 1, tv); }
        };
        mbar_wait(sb + B_QE + 8, 1);
        wg_wait<1>();
        fence_regs(acc[1]);
        conv_tile1(0);
        if (G2 < G3) part(3, 0, G2, G3);
        if (l & 1) { fence_async_smem(); bar_arrive(NB_ST, 288); }
        conv_tile1(1);
        wg_wait<(G2 > 0) + (G2 < G3) + (G3 < 4)>();
        if (w == 0) e_arrive_both(sb + B_QE + 16);
        wg_wait<0>();
        fence_regs(acc[0]);
        if (w == 0) e_arrive_both(sb + B_QE + 24);
        bf16* const op0 = [&] { IDS(); return g_os + (size_t)(bm * 256 + row0 + (lane >> 2)) * 1024 + bn * 32 + (lane & 3) * 8; }();
        auto put_o = [&](int h, int m, const float (&o)[16], float i0, float i1) {
          bf16* op = op0 + m * 65536 + h * 512;
          const uint4 a = make_uint4(pack2(o[0] * i0, o[1] * i0), pack2(o[4] * i0, o[5] * i0), pack2(o[8] * i0, o[9] * i0), pack2(o[12] * i0, o[13] * i0));
          const uint4 c = make_uint4(pack2(o[2] * i1, o[3] * i1), pack2(o[6] * i1, o[7] * i1), pack2(o[10] * i1, o[11] * i1), pack2(o[14] * i1, o[15] * i1));
          *(uint4*)op = a; *(uint4*)(op + 8 * 1024) = c;
          const uint32_t hi = __vimax3_u16x2(__vimax3_u16x2(a.x, a.y, a.z), __vimax3_u16x2(a.w, c.x, c.y), __vmaxu2(c.z, c.w));
          const uint32_t lo = __vimax3_s16x2(__vimax3_s16x2(a.x, a.y, a.z), __vimax3_s16x2(a.w, c.x, c.y), __vmaxs2(c.z, c.w));
          return __vmaxu2(hi & 0x7FFF7FFFu, lo & 0x7FFF7FFFu);
        };
        if (!(l & 1)) {
          auto conv_kv = [&](int h) {
            uint32_t t[8];
            norm_tile(2 + h, 0, t); put_kv(h, 0, 0, t);
            norm_tile(4 + h, 0, t); put_kv(h, 1, 0, t);
          };
          conv_kv(0);
          if (!PERHEAD) conv_kv(1);
          norm_tile(0, 0, q[0][0]); pack_b(0, 1, q[0][1]);
          bar_sync(NB_SC, 256);
          const bool e = g & 1, sel = 2 * qd + (g & 1) >= g + 2, first = bm == 0 && row0 == 0;
#pragma unroll 1
          for (int h = 0; h < 2; h++) {
            if (row0 == 0) bar_sync(NB_HALO + h, 64);
            float s[2][4][4];
            uint32_t vf[2][4][4], pf[2][2][4];
#pragma unroll
            for (int m = 0; m < 2; m++)
#pragma unroll
              for (int nt = 0; nt < 4; nt++) {
                uint32_t kf[4];
                const uint32_t r = row0 + m * 64 + 8 * nt + (lane & 7);
                ldsm4(sb + 2 * h * ASC + r * 64 + (((lane >> 3) ^ ((r >> 1) & 3)) << 4), kf);
                s[m][nt][0] = s[m][nt][1] = s[m][nt][2] = s[m][nt][3] = 0.f;
                mma16816(s[m][nt], q[0][m][0], q[0][m][1], q[0][m][2], q[0][m][3], kf[0], kf[1]);
                mma16816(s[m][nt], q[0][m][4], q[0][m][5], q[0][m][6], q[0][m][7], kf[2], kf[3]);
              }
#pragma unroll
            for (int m = 0; m < 2; m++)
#pragma unroll
              for (int i = 0; i < 4; i++) {
                const uint32_t r = row0 + m * 64 + 16 * (i >> 1) + srow, ch = 2 * (i & 1) + (lane >> 4);
                ldsm4t(sb + (2 * h + 1) * ASC + r * 64 + ((ch ^ ((r >> 1) & 3)) << 4), vf[m][i]);
              }
            float va[4], vb[4], mx[4];
#pragma unroll
            for (int i = 0; i < 4; i++) {
              const int m = i >> 1, hh = i & 1;
              const float a = e ? s[m][hh + 1][2 * hh + 1] : s[m][hh + 1][2 * hh];
              const float lo = e ? s[m][hh][2 * hh + 1] : s[m][hh][2 * hh], hi = e ? s[m][hh + 2][2 * hh + 1] : s[m][hh + 2][2 * hh];
              const uint32_t t = pack2(a, sel ? lo : hi);
              const uint32_t u = pack2(bf_lo(t) * 0.17677669529663687f, bf_hi(t) * 0.17677669529663687f);
              va[i] = (m == 0 && hh == 0 && first) ? -INFINITY : bf_lo(u);
              vb[i] = (m == 0 && first && sel) ? -INFINITY : bf_hi(u);
              mx[i] = fmaxf(va[i], vb[i]);
            }
#pragma unroll
            for (int i = 0; i < 4; i++) mx[i] = fmaxf(mx[i], __shfl_xor_sync(~0u, mx[i], 1));
#pragma unroll
            for (int i = 0; i < 4; i++) mx[i] = fmaxf(mx[i], __shfl_xor_sync(~0u, mx[i], 2));
#pragma unroll
            for (int i = 0; i < 4; i++) {
              va[i] = ex2((va[i] - mx[i]) * 1.4426950408889634f); vb[i] = ex2((vb[i] - mx[i]) * 1.4426950408889634f);
              mx[i] = va[i] + vb[i];
            }
#pragma unroll
            for (int i = 0; i < 4; i++) mx[i] += __shfl_xor_sync(~0u, mx[i], 1);
#pragma unroll
            for (int i = 0; i < 4; i++) mx[i] += __shfl_xor_sync(~0u, mx[i], 2);
#pragma unroll
            for (int i = 0; i < 4; i++) {
              const int m = i >> 1, hh = i & 1;
              const float inv = rcp(mx[i]);
              const uint32_t t = pack2(va[i] * inv, vb[i] * inv);
              const uint32_t pa = e ? t << 16 : t & 0xFFFFu, pb = e ? t & 0xFFFF0000u : t >> 16;
              pf[m][hh][hh + 1] = pa; pf[m][hh][hh] = sel ? pb : 0u; pf[m][hh][hh + 2] = sel ? 0u : pb; pf[m][hh][3 - 3 * hh] = 0u;
            }
#pragma unroll
            for (int m = 0; m < 2; m++) {
              float o[4][4];
#pragma unroll
              for (int j = 0; j < 4; j++) o[j][0] = o[j][1] = o[j][2] = o[j][3] = 0.f;
#pragma unroll
              for (int i = 0; i < 4; i++) {
                const int kk = i >> 1, jj = 2 * (i & 1);
                mma16816(o[jj], pf[m][0][2 * kk], pf[m][1][2 * kk], pf[m][0][2 * kk + 1], pf[m][1][2 * kk + 1], vf[m][i][0], vf[m][i][1]);
                mma16816(o[jj + 1], pf[m][0][2 * kk], pf[m][1][2 * kk], pf[m][0][2 * kk + 1], pf[m][1][2 * kk + 1], vf[m][i][2], vf[m][i][3]);
              }
              const float of[16] = {o[0][0], o[0][1], o[0][2], o[0][3], o[1][0], o[1][1], o[1][2], o[1][3], o[2][0], o[2][1], o[2][2], o[2][3], o[3][0], o[3][1], o[3][2], o[3][3]};
              put_o(h, m, of, 1.f, 1.f);
            }
            bar_arrive(NB_SIG + 2 * h + wg, 160);
            if (h == 0) {
              if (PERHEAD) conv_kv(1);
              norm_tile(1, 0, q[0][0]); pack_b(1, 1, q[0][1]);
              if (PERHEAD) bar_sync(NB_SC, 256);
            }
          }
        } else {
          auto conv_h = [&](int gi, int m, uint32_t (&t)[8]) {
            pack_h(gi, m, t);
            float d0[4] = {0.f, 0.f, 0.f, 0.f}, d1[4] = {0.f, 0.f, 0.f, 0.f};
            mma16816h(d0, t[0], t[1], t[2], t[3], t[0], t[2]); mma16816h(d1, t[0], t[1], t[2], t[3], t[1], t[3]);
            mma16816h(d0, t[4], t[5], t[6], t[7], t[4], t[6]); mma16816h(d1, t[4], t[5], t[6], t[7], t[5], t[7]);
            return (uint32_t)__reduce_max_sync(~0u, max(max(__float_as_int(d0[0]), __float_as_int(d0[1])), max(__float_as_int(d1[2]), __float_as_int(d1[3]))));
          };
#pragma unroll
          for (int h = 0; h < 2; h++) {
            uint32_t t[8], tv[8];
            scale(2 + h, 0, 1.f);
            const uint32_t kn = f16_class(conv_h(2 + h, 0, t), K_LO);
            if (h) {
#pragma unroll
              for (int i = 0; i < 2; i++) {
                scale(i, 0, QSCALE);
                qn[i][0] = f16_class(conv_h(i, 0, q[i][0]), K_LO);
                qn[i][1] = f16_class(conv_h(i, 1, q[i][1]), K_LO);
              }
            }
            norm_tile(4 + h, 0, tv);
            put_kv(h, 1, 0, tv);
            put_kn(h, 0, kn);
            if (kn == NOT_F16) pack_b(2 + h, 0, t);
            put_kv(h, 0, 0, t);
            fence_async_smem();
            bar_arrive(NB_KV + 12 * h, 288);
            if (h == 0) mbar_wait(sb + B_QF + 24, 1);
          }
          if (max(max(qn[0][0], qn[0][1]), max(qn[1][0], qn[1][1])) == NOT_F16) {
#pragma unroll
            for (int i = 0; i < 4; i++) if (qn[i >> 1][i & 1] == NOT_F16) pack_b(i >> 1, i & 1, q[i >> 1][i & 1]);
          }
          const bool elected = w == 0 && lane == 0;
          const uint64_t kd0 = mkdesc(sb + T0, 16, 512, 2);
          const uint64_t vd0 = mkdesc(sb + T0 + 16384, ONES - (T0 + 16384), 512, 2);
          constexpr uint64_t VSTEP = 64 - (64ull << 16);
          constexpr int RPC = NQ / 16, NC = 256 / NQ;
          float o[2][20], SA[2][NQ / 2];
          uint32_t SB[2][NQ / 4], PA[LA][4], PB[LB][4];
#pragma unroll
          for (int m = 0; m < 2; m++) {
#pragma unroll
            for (int i = 0; i < NQ / 2; i++) SA[m][i] = 0.f;
#pragma unroll
            for (int i = 0; i < NQ / 4; i++) SB[m][i] = 0u;
            fence_regs(SA[m]); fence_regs(SB[m]);
          }
          auto qka = [&](int b, int k, uint64_t d, int h = 0) { QK_A(SA[b], q[h][0][4 * k], q[h][0][4 * k + 1], q[h][0][4 * k + 2], q[h][0][4 * k + 3], d + 2 * k, k ? 1 : zero); };
          auto qkb = [&](int b, int k, uint64_t d, int h = 0) { QK_B(SB[b], q[h][1][4 * k], q[h][1][4 * k + 1], q[h][1][4 * k + 2], q[h][1][4 * k + 3], d + 2 * k, k ? 1 : zero); };
          auto pv = [&](int m, const uint32_t (&Px)[4], uint64_t vd) { wgmma_m64n40k16_rs_tb(o[m], Px[0], Px[1], Px[2], Px[3], vd, 1); };
          auto clear = [&]() {
#pragma unroll
            for (int i = 0; i < 20; i++) o[0][i] = o[1][i] = 0.f;
            fence_regs(o[0]); fence_regs(o[1]);
#pragma unroll
            for (int i = 0; i < 4; i++) PA[0][i] = PB[0][i] = PA[LA - 1][i] = PB[LB - 1][i] = zero;
          };
          mbar_wait(sb + B_TF, 0);
          wg_fence(); qka(0, 0, kd0); qkb(0, 0, kd0); qka(0, 1, kd0); qkb(0, 1, kd0); wg_commit();
          clear();
          wg_wait<0>(); fence_regs(SA[0]); fence_regs(SB[0]);
#pragma unroll 1
          for (int pass = 0; pass < 2; pass++) {
#pragma unroll 1
            for (int j = 0; j < 8; j++) {
              const uint32_t s = j & 3, sn = j < 7 ? (j + 1) & 3 : s, sp = j > 0 ? (j + 3) & 3 : s;
              const uint64_t kd = kd0 + s * 2048, vd = vd0 + s * (32 * VSTEP), kdn = kd0 + sn * 2048, vdp = vd0 + sp * (32 * VSTEP) + 16 * VSTEP;
              bool landed = false;
#pragma unroll
              for (int r = 0; r < 16; r++) {
                const int c = r / RPC, ro = r % RPC, cn = c + 1;
                if (r == 16 - RPC && !landed) mbar_wait(sb + B_TF + 8 * sn, ((j + 1) >> 2) & 1);
                wg_fence();
                const uint64_t kx = cn < NC ? kd + cn * NQ * 4 : kdn, va = (r >= LA ? vd : vdp) + (r - LA) * VSTEP, vb = (r >= LB ? vd : vdp) + (r - LB) * VSTEP;
                if (LAG & 4) { pv(0, PA[r % LA], va); pv(1, PB[r % LB], vb); }
#pragma unroll
                for (int k = 0; k < 2; k++) {
                  if (ro == ((OA >> (4 * k)) & 15)) qka(cn & 1, k, kx);
                  if (ro == ((OB >> (4 * k)) & 15)) qkb(cn & 1, k, kx);
                }
                if (!(LAG & 4)) {
                  if (ro == RPC - 1 || (LAG & 1)) wg_commit();
                  if (LAG & 8) { pv(1, PB[r % LB], vb); pv(0, PA[r % LA], va); } else { pv(0, PA[r % LA], va); pv(1, PB[r % LB], vb); }
                }
                wg_commit();
                if (r == 14 - RPC) landed = mbar_test(sb + B_TF + 8 * sn, ((j + 1) >> 2) & 1) || j == 7;
#pragma unroll
                for (int i = 0; i < 4; i++) {
                  if (LAG & 16) PB[r % LB][i] = exp2_h2(SB[c & 1][4 * ro + i]);
                  PA[r % LA][i] = pack2(ex2(SA[c & 1][8 * ro + 2 * i]), ex2(SA[c & 1][8 * ro + 2 * i + 1]));
                  if (!(LAG & 16)) PB[r % LB][i] = exp2_h2(SB[c & 1][4 * ro + i]);
                }
                if (r == 15 || ((LAG & 4) && ro == RPC - 1 && ((OA >> 4) == ro || (OB >> 4) == ro))) wg_wait<0>(); else if (ro == RPC - 1 || !(LAG & 2)) wg_wait<1>();
                if (ro == RPC - 1) { fence_regs(SA[cn & 1]); fence_regs(SB[cn & 1]); }
                if (r == (LA + LB > 2 ? 4 : RPC) && elected && j > 0) mbar_arrive(sb + B_TE + 8 * sp);
              }
            }
            int badm = 0;
            if (pass == 0) mbar_wait(sb + B_TF, 0);
            wg_fence();
            if (LA == 2) pv(0, PA[0], vd0 + 110 * VSTEP);
            if (LB == 2) pv(1, PB[0], vd0 + 110 * VSTEP);
            pv(0, PA[LA - 1], vd0 + 111 * VSTEP); pv(1, PB[LB - 1], vd0 + 111 * VSTEP); wg_commit();
            qka(0, 0, kd0, 1); qkb(0, 0, kd0, 1); qka(0, 1, kd0, 1); qkb(0, 1, kd0, 1); wg_commit();
            if (pass == 0) bar_sync(NB_KN + wg, 160);
            const float kmax = *(volatile float*)(smem + KMAX + 4 * pass);
            wg_wait<1>(); fence_regs(o[0]); fence_regs(o[1]);
            if (w == 0) e_arrive(sb + B_TE + 8 * 3);
#pragma unroll
            for (int m = 0; m < 2; m++) {
              const float of[16] = {o[m][0], o[m][1], o[m][2], o[m][3], o[m][4], o[m][5], o[m][6], o[m][7], o[m][8], o[m][9], o[m][10], o[m][11], o[m][12], o[m][13], o[m][14], o[m][15]};
              const uint32_t chk = put_o(pass, m, of, rcp(o[m][16]), rcp(o[m][18]));
              const bool bad = !(__uint_as_float(qn[0][m]) * kmax <= (m ? 0.875f * 0.875f : 112.f * 112.f)) || !(fminf(o[m][16], o[m][18]) >= 9.3e-10f) ||
                               !(o[m][16] + o[m][18] <= 3e38f) || ((chk + 0x00800080u) & 0x80008000u);
              badm |= __any_sync(~0u, bad) << m;
            }
            wg_wait<0>(); fence_regs(SA[0]); fence_regs(SB[0]);
            if (badm) {
#pragma unroll 1
              for (int m = 0; m < 2; m++) if ((badm >> m) & 1) {
                uint32_t qq[8]; float res[20];
#pragma unroll
                for (int i = 0; i < 8; i++) { qq[i] = m ? q[0][1][i] : q[0][0][i]; if ((m ? qn[0][1] : qn[0][0]) != NOT_F16) qq[i] = h2_to_bf2(qq[i]); }
                attn_slow(qq, m ? 128.f : 1.f, 2 * (cta_id() & 15) + pass, g_kn + ((l >> 1) * 128 + (cta_id() & 15) * 8) * 32 + 16 * pass, res, lane_id());
                const float of[16] = {res[0], res[1], res[2], res[3], res[4], res[5], res[6], res[7], res[8], res[9], res[10], res[11], res[12], res[13], res[14], res[15]};
                put_o(pass, m, of, rcp(res[16]), rcp(res[18]));
              }
            }
            bar_arrive(NB_SIG + 2 * pass + wg, 160);
            qn[0][0] = qn[1][0]; qn[0][1] = qn[1][1];
#pragma unroll
            for (int m = 0; m < 2; m++)
#pragma unroll
              for (int i = 0; i < 8; i++) q[0][m][i] = q[1][m][i];
            clear();
          }
        }
      }
      {
        float acc[64];
#pragma unroll
        for (int i = 0; i < 64; i++) acc[i] = 0.f;
        fence_regs(acc);
        uint32_t s = 0, lap = 0;
#pragma unroll 1
        for (int kt = 0; kt < 16; kt++) {
          mbar_wait(sb + B_PF + 8 * s, ((s < 4 ? l : 0) + lap) & 1);
          const uint64_t da = mkdesc(sb + pslot_a(s, l) + wg * 8192, 16, 1024, 1), db = mkdesc(sb + pslot_b(s, l), 8192, 1024, 1);
          wg_fence();
#pragma unroll
          for (int k = 0; k < 4; k++) wgmma_m64n128k16_ss_tb(acc, da + k * 2, db + k * 128, 1);
          wg_commit();
          wg_wait<1>();
          if (kt > 0 && w == 0) e_arrive_both(sb + B_PE + 8 * (s ? s - 1 : 5));
          if (++s == 6) { s = 0; lap++; }
        }
        IDS();
        const int g = lane >> 2, qd = lane & 3;
        const int r0 = wg * 64 + w * 16;
        const uint32_t r = r0 + (lane & 7) + ((lane >> 3) & 1) * 8;
        uint32_t x[8][4];
        mbar_wait(sb + B_RF, l & 1);
#pragma unroll
        for (int jj = 0; jj < 8; jj++) ldsm4(sb + ((l & 1) ? RES : 0) + (jj >> 2) * 16384 + r * 128 + ((((2 * jj + (lane >> 4)) & 7) ^ (r & 7)) << 4), x[jj]);
        wg_wait<0>();
        fence_regs(acc);
        bar_sync(NB_SC, 256);
        if (w == 0) e_arrive_both(sb + B_PE + 8 * 3);
        const CUtensorMap* mo = &prm.m[l == 3 ? M_OUT : M_XST];
#pragma unroll
        for (int jj = 0; jj < 8; jj++) {
#pragma unroll
          for (int i = 0; i < 4; i++) x[jj][i] = add_bf16x2(x[jj][i], pack2(acc[8 * jj + 2 * i], acc[8 * jj + 2 * i + 1]));
          stsm4(sb + (jj >> 2) * QSTG + po * 16384 + r * 128 + ((((2 * jj + (lane >> 4)) & 7) ^ (r & 7)) << 4), x[jj][0], x[jj][1], x[jj][2], x[jj][3]);
          if ((jj & 3) == 3) { fence_async_smem(); __syncwarp(); tma_st(mo, pn * 128 + (jj >> 2) * 64, pm * 128 + r0, sb + (jj >> 2) * QSTG + po * 16384 + r0 * 128); }
        }
        bulk_commit();
        if (l < 3) {
          bar_arrive(NB_X, 288);
          float s1[4] = {0.f, 0.f, 0.f, 0.f}, s2[4][4];
#pragma unroll
          for (int i = 0; i < 16; i++) s2[i >> 2][i & 3] = 0.f;
#pragma unroll
          for (int jj = 0; jj < 8; jj++) {
            mma16816(s1, x[jj][0], x[jj][1], x[jj][2], x[jj][3], 0x3f803f80u, 0x3f803f80u);
#pragma unroll
            for (int i = 0; i < 4; i++) mma1688(s2[i], x[jj][i & 2], x[jj][i | 1], x[jj][i]);
          }
          if (qd == (g >> 1)) {
            float2* sp = g_stats + pn * 2048 + pm * 128 + r0 + g;
            sp[0] = make_float2(s1[0], (g & 1) ? s2[0][1] + s2[2][1] : s2[0][0] + s2[2][0]);
            sp[8] = make_float2(s1[2], (g & 1) ? s2[1][3] + s2[3][3] : s2[1][2] + s2[3][2]);
          }
        }
        bulk_wait_n<0>();
        if (l < 3) bar_arrive(NB_X0, 320 + 32 * XLATE);
      }
    }
  }
  asm volatile("barrier.cluster.arrive.relaxed.aligned;\nbarrier.cluster.wait.aligned;" ::: "memory");
}

typedef CUresult (*EncodeFn)(CUtensorMap*, CUtensorMapDataType, cuuint32_t, void*, const cuuint64_t*, const cuuint64_t*, const cuuint32_t*,
                             const cuuint32_t*, CUtensorMapInterleave, CUtensorMapSwizzle, CUtensorMapL2promotion, CUtensorMapFloatOOBfill);

static void make_map(EncodeFn fn, CUtensorMap* m, const void* ptr, int rank, const uint64_t* dims, const uint64_t* strides, const uint32_t* box, CUtensorMapSwizzle sw) {
  cuuint64_t d[5], st[4];
  cuuint32_t bx[5], es[5];
  for (int i = 0; i < rank; i++) { d[i] = dims[i]; bx[i] = box[i]; es[i] = 1; if (i) st[i - 1] = strides[i - 1] * 2; }
  fn(m, CU_TENSOR_MAP_DATA_TYPE_BFLOAT16, rank, (void*)ptr, d, st, bx, es, CU_TENSOR_MAP_INTERLEAVE_NONE, sw,
     CU_TENSOR_MAP_L2_PROMOTION_L2_128B, CU_TENSOR_MAP_FLOAT_OOB_FILL_NONE);
}
static void map2(EncodeFn fn, CUtensorMap* m, const void* ptr, uint64_t inner, uint64_t outer, uint32_t bi, uint32_t bo, CUtensorMapSwizzle sw) {
  const uint64_t d[2] = {inner, outer}, st[1] = {inner};
  const uint32_t bx[2] = {bi, bo};
  make_map(fn, m, ptr, 2, d, st, bx, sw);
}

extern "C" void kernel_launch(void* const* d_in, const int* in_sizes, int n_in, void* d_out, int out_size) {
  (void)in_sizes; (void)n_in; (void)out_size;
  static EncodeFn enc = nullptr;
  static void *xs, *os, *kk, *vv, *ep;
  if (!enc) {
    void* p = nullptr;
    cudaDriverEntryPointQueryResult qr;
    cudaGetDriverEntryPoint("cuTensorMapEncodeTiled", &p, cudaEnableDefault, &qr);
    enc = (EncodeFn)p;
    cudaGetSymbolAddress(&xs, g_xs); cudaGetSymbolAddress(&os, g_os); cudaGetSymbolAddress(&kk, g_k); cudaGetSymbolAddress(&vv, g_v); cudaGetSymbolAddress(&ep, g_epoch);
    cudaFuncSetAttribute(fused_kernel, cudaFuncAttributeMaxDynamicSharedMemorySize, SMEM_BYTES);
  }
  Params prm;
  const CUtensorMapSwizzle S128 = CU_TENSOR_MAP_SWIZZLE_128B, S64 = CU_TENSOR_MAP_SWIZZLE_64B;
  map2(enc, &prm.m[M_X0A], d_in[0], 1024, 2048, 64, 256, S128);
  map2(enc, &prm.m[M_XSA], xs, 1024, 2048, 64, 256, S128);
  for (int t = 0; t < 2; t++) {
    const uint64_t d3[3] = {1024, 1024, 3}, s3[2] = {3072, 1024};
    const uint32_t b3[3] = {64, 64, 3};
    make_map(enc, &prm.m[M_WQA + t], d_in[1 + 3 * t], 3, d3, s3, b3, S128);
    const uint64_t d5[5] = {64, 32, 2, 16, 16}, s5[4] = {1024, 32 * 1024, 64 * 1024, 64};
    const uint32_t b5[5] = {64, 32, 1, 2, 2};
    make_map(enc, &prm.m[M_WOA + t], d_in[2 + 3 * t], 5, d5, s5, b5, S128);
    const uint64_t dr[3] = {64, 2048, 16}, sr[2] = {1024, 64};
    const uint32_t br[3] = {64, 128, 2};
    make_map(enc, &prm.m[M_X0R + t], t ? xs : d_in[0], 3, dr, sr, br, S128);
  }
  map2(enc, &prm.m[M_OS], os, 1024, 2048, 64, 64, S128);
  map2(enc, &prm.m[M_K], kk, 32, 65536, 32, 256, S64);
  map2(enc, &prm.m[M_V], vv, 32, 65536, 32, 256, S64);
  map2(enc, &prm.m[M_K4], kk, 32, 65536, 32, 64, S64);
  map2(enc, &prm.m[M_V4], vv, 32, 65536, 32, 64, S64);
  map2(enc, &prm.m[M_XSO], xs, 1024, 2048, 64, 128, S128);
  map2(enc, &prm.m[M_X0H], d_in[0], 1024, 2048, 64, 128, S128);
  map2(enc, &prm.m[M_XST], xs, 1024, 2048, 64, 16, S128);
  map2(enc, &prm.m[M_OUT], d_out, 1024, 2048, 64, 16, S128);
  prm.x0 = (const bf16*)d_in[0];
  prm.wq[0] = (const bf16*)d_in[1]; prm.wq[1] = (const bf16*)d_in[4];
  prm.wo[0] = (const bf16*)d_in[2]; prm.wo[1] = (const bf16*)d_in[5];
  prm.epoch = (uint32_t*)ep;
  prm.zero = 0;
  for (int i = 0; i < 128; i++) prm.map[i] = remap(i);
  fused_kernel<<<128, 384, SMEM_BYTES>>>(prm);
}
```

```cpp
#include <cuda_runtime.h>
#include <cuda_bf16.h>
#include <cuda.h>
#include <stdint.h>

typedef __nv_bfloat16 bf16;

__device__ __forceinline__ void wgmma_m64n192k16_ss_tb(float (&d)[96], uint64_t da, uint64_t db, int scale_d) {
  asm volatile("{\n.reg .pred p;\nsetp.ne.b32 p, %98, 0;\n"
    "wgmma.mma_async.sync.aligned.m64n192k16.f32.bf16.bf16 "
    "{%0, %1, %2, %3, %4, %5, %6, %7, %8, %9, %10, %11, %12, %13, %14, %15, "
    "%16, %17, %18, %19, %20, %21, %22, %23, %24, %25, %26, %27, %28, %29, %30, %31, "
    "%32, %33, %34, %35, %36, %37, %38, %39, %40, %41, %42, %43, %44, %45, %46, %47, "
    "%48, %49, %50, %51, %52, %53, %54, %55, %56, %57, %58, %59, %60, %61, %62, %63, "
    "%64, %65, %66, %67, %68, %69, %70, %71, %72, %73, %74, %75, %76, %77, %78, %79, "
    "%80, %81, %82, %83, %84, %85, %86, %87, %88, %89, %90, %91, %92, %93, %94, %95}, "
    "%96, %97, p, 1, 1, 0, 1;\n}\n"
    : "+f"(d[0]), "+f"(d[1]), "+f"(d[2]), "+f"(d[3]), "+f"(d[4]), "+f"(d[5]), "+f"(d[6]), "+f"(d[7]),
      "+f"(d[8]), "+f"(d[9]), "+f"(d[10]), "+f"(d[11]), "+f"(d[12]), "+f"(d[13]), "+f"(d[14]), "+f"(d[15]),
      "+f"(d[16]), "+f"(d[17]), "+f"(d[18]), "+f"(d[19]), "+f"(d[20]), "+f"(d[21]), "+f"(d[22]), "+f"(d[23]),
      "+f"(d[24]), "+f"(d[25]), "+f"(d[26]), "+f"(d[27]), "+f"(d[28]), "+f"(d[29]), "+f"(d[30]), "+f"(d[31]),
      "+f"(d[32]), "+f"(d[33]), "+f"(d[34]), "+f"(d[35]), "+f"(d[36]), "+f"(d[37]), "+f"(d[38]), "+f"(d[39]),
      "+f"(d[40]), "+f"(d[41]), "+f"(d[42]), "+f"(d[43]), "+f"(d[44]), "+f"(d[45]), "+f"(d[46]), "+f"(d[47]),
      "+f"(d[48]), "+f"(d[49]), "+f"(d[50]), "+f"(d[51]), "+f"(d[52]), "+f"(d[53]), "+f"(d[54]), "+f"(d[55]),
      "+f"(d[56]), "+f"(d[57]), "+f"(d[58]), "+f"(d[59]), "+f"(d[60]), "+f"(d[61]), "+f"(d[62]), "+f"(d[63]),
      "+f"(d[64]), "+f"(d[65]), "+f"(d[66]), "+f"(d[67]), "+f"(d[68]), "+f"(d[69]), "+f"(d[70]), "+f"(d[71]),
      "+f"(d[72]), "+f"(d[73]), "+f"(d[74]), "+f"(d[75]), "+f"(d[76]), "+f"(d[77]), "+f"(d[78]), "+f"(d[79]),
      "+f"(d[80]), "+f"(d[81]), "+f"(d[82]), "+f"(d[83]), "+f"(d[84]), "+f"(d[85]), "+f"(d[86]), "+f"(d[87]),
      "+f"(d[88]), "+f"(d[89]), "+f"(d[90]), "+f"(d[91]), "+f"(d[92]), "+f"(d[93]), "+f"(d[94]), "+f"(d[95])
    : "l"(da), "l"(db), "r"(scale_d));
}

__device__ __forceinline__ void wgmma_m64n128k16_ss_tb(float (&d)[64], uint64_t da, uint64_t db, int scale_d) {
  asm volatile("{\n.reg .pred p;\nsetp.ne.b32 p, %66, 0;\n"
    "wgmma.mma_async.sync.aligned.m64n128k16.f32.bf16.bf16 "
    "{%0, %1, %2, %3, %4, %5, %6, %7, %8, %9, %10, %11, %12, %13, %14, %15, "
    "%16, %17, %18, %19, %20, %21, %22, %23, %24, %25, %26, %27, %28, %29, %30, %31, "
    "%32, %33, %34, %35, %36, %37, %38, %39, %40, %41, %42, %43, %44, %45, %46, %47, "
    "%48, %49, %50, %51, %52, %53, %54, %55, %56, %57, %58, %59, %60, %61, %62, %63}, "
    "%64, %65, p, 1, 1, 0, 1;\n}\n"
    : "+f"(d[0]), "+f"(d[1]), "+f"(d[2]), "+f"(d[3]), "+f"(d[4]), "+f"(d[5]), "+f"(d[6]), "+f"(d[7]),
      "+f"(d[8]), "+f"(d[9]), "+f"(d[10]), "+f"(d[11]), "+f"(d[12]), "+f"(d[13]), "+f"(d[14]), "+f"(d[15]),
      "+f"(d[16]), "+f"(d[17]), "+f"(d[18]), "+f"(d[19]), "+f"(d[20]), "+f"(d[21]), "+f"(d[22]), "+f"(d[23]),
      "+f"(d[24]), "+f"(d[25]), "+f"(d[26]), "+f"(d[27]), "+f"(d[28]), "+f"(d[29]), "+f"(d[30]), "+f"(d[31]),
      "+f"(d[32]), "+f"(d[33]), "+f"(d[34]), "+f"(d[35]), "+f"(d[36]), "+f"(d[37]), "+f"(d[38]), "+f"(d[39]),
      "+f"(d[40]), "+f"(d[41]), "+f"(d[42]), "+f"(d[43]), "+f"(d[44]), "+f"(d[45]), "+f"(d[46]), "+f"(d[47]),
      "+f"(d[48]), "+f"(d[49]), "+f"(d[50]), "+f"(d[51]), "+f"(d[52]), "+f"(d[53]), "+f"(d[54]), "+f"(d[55]),
      "+f"(d[56]), "+f"(d[57]), "+f"(d[58]), "+f"(d[59]), "+f"(d[60]), "+f"(d[61]), "+f"(d[62]), "+f"(d[63])
    : "l"(da), "l"(db), "r"(scale_d));
}

__device__ __forceinline__ void wgmma_m64n32k16_rs_nb_h(float (&d)[16], uint32_t a0, uint32_t a1, uint32_t a2, uint32_t a3, uint64_t db, int scale_d) {
  asm volatile("{\n.reg .pred p;\nsetp.ne.b32 p, %21, 0;\n"
    "wgmma.mma_async.sync.aligned.m64n32k16.f32.f16.f16 "
    "{%0, %1, %2, %3, %4, %5, %6, %7, %8, %9, %10, %11, %12, %13, %14, %15}, "
    "{%16, %17, %18, %19}, %20, p, 1, 1, 0;\n}\n"
    : "+f"(d[0]), "+f"(d[1]), "+f"(d[2]), "+f"(d[3]), "+f"(d[4]), "+f"(d[5]), "+f"(d[6]), "+f"(d[7]),
      "+f"(d[8]), "+f"(d[9]), "+f"(d[10]), "+f"(d[11]), "+f"(d[12]), "+f"(d[13]), "+f"(d[14]), "+f"(d[15])
    : "r"(a0), "r"(a1), "r"(a2), "r"(a3), "l"(db), "r"(scale_d));
}

__device__ __forceinline__ void wgmma_m64n32k16_rs_nb_hh(uint32_t (&d)[8], uint32_t a0, uint32_t a1, uint32_t a2, uint32_t a3, uint64_t db, int scale_d) {
  asm volatile("{\n.reg .pred p;\nsetp.ne.b32 p, %13, 0;\n"
    "wgmma.mma_async.sync.aligned.m64n32k16.f16.f16.f16 "
    "{%0, %1, %2, %3, %4, %5, %6, %7}, "
    "{%8, %9, %10, %11}, %12, p, 1, 1, 0;\n}\n"
    : "+r"(d[0]), "+r"(d[1]), "+r"(d[2]), "+r"(d[3]), "+r"(d[4]), "+r"(d[5]), "+r"(d[6]), "+r"(d[7])
    : "r"(a0), "r"(a1), "r"(a2), "r"(a3), "l"(db), "r"(scale_d));
}

__device__ __forceinline__ void wgmma_m64n64k16_rs_nb_h(float (&d)[32], uint32_t a0, uint32_t a1, uint32_t a2, uint32_t a3, uint64_t db, int scale_d) {
  asm volatile("{\n.reg .pred p;\nsetp.ne.b32 p, %37, 0;\n"
    "wgmma.mma_async.sync.aligned.m64n64k16.f32.f16.f16 "
    "{%0, %1, %2, %3, %4, %5, %6, %7, %8, %9, %10, %11, %12, %13, %14, %15, "
    "%16, %17, %18, %19, %20, %21, %22, %23, %24, %25, %26, %27, %28, %29, %30, %31}, "
    "{%32, %33, %34, %35}, %36, p, 1, 1, 0;\n}\n"
    : "+f"(d[0]), "+f"(d[1]), "+f"(d[2]), "+f"(d[3]), "+f"(d[4]), "+f"(d[5]), "+f"(d[6]), "+f"(d[7]),
      "+f"(d[8]), "+f"(d[9]), "+f"(d[10]), "+f"(d[11]), "+f"(d[12]), "+f"(d[13]), "+f"(d[14]), "+f"(d[15]),
      "+f"(d[16]), "+f"(d[17]), "+f"(d[18]), "+f"(d[19]), "+f"(d[20]), "+f"(d[21]), "+f"(d[22]), "+f"(d[23]),
      "+f"(d[24]), "+f"(d[25]), "+f"(d[26]), "+f"(d[27]), "+f"(d[28]), "+f"(d[29]), "+f"(d[30]), "+f"(d[31])
    : "r"(a0), "r"(a1), "r"(a2), "r"(a3), "l"(db), "r"(scale_d));
}

__device__ __forceinline__ void wgmma_m64n64k16_rs_nb_hh(uint32_t (&d)[16], uint32_t a0, uint32_t a1, uint32_t a2, uint32_t a3, uint64_t db, int scale_d) {
  asm volatile("{\n.reg .pred p;\nsetp.ne.b32 p, %21, 0;\n"
    "wgmma.mma_async.sync.aligned.m64n64k16.f16.f16.f16 "
    "{%0, %1, %2, %3, %4, %5, %6, %7, %8, %9, %10, %11, %12, %13, %14, %15}, "
    "{%16, %17, %18, %19}, %20, p, 1, 1, 0;\n}\n"
    : "+r"(d[0]), "+r"(d[1]), "+r"(d[2]), "+r"(d[3]), "+r"(d[4]), "+r"(d[5]), "+r"(d[6]), "+r"(d[7]),
      "+r"(d[8]), "+r"(d[9]), "+r"(d[10]), "+r"(d[11]), "+r"(d[12]), "+r"(d[13]), "+r"(d[14]), "+r"(d[15])
    : "r"(a0), "r"(a1), "r"(a2), "r"(a3), "l"(db), "r"(scale_d));
}

__device__ __forceinline__ void wgmma_m64n40k16_rs_tb(float (&d)[20], uint32_t a0, uint32_t a1, uint32_t a2, uint32_t a3, uint64_t db, int scale_d) {
  asm volatile("{\n.reg .pred p;\nsetp.ne.b32 p, %25, 0;\n"
    "wgmma.mma_async.sync.aligned.m64n40k16.f32.bf16.bf16 "
    "{%0, %1, %2, %3, %4, %5, %6, %7, %8, %9, %10, %11, %12, %13, %14, %15, "
    "%16, %17, %18, %19}, "
    "{%20, %21, %22, %23}, %24, p, 1, 1, 1;\n}\n"
    : "+f"(d[0]), "+f"(d[1]), "+f"(d[2]), "+f"(d[3]), "+f"(d[4]), "+f"(d[5]), "+f"(d[6]), "+f"(d[7]),
      "+f"(d[8]), "+f"(d[9]), "+f"(d[10]), "+f"(d[11]), "+f"(d[12]), "+f"(d[13]), "+f"(d[14]), "+f"(d[15]),
      "+f"(d[16]), "+f"(d[17]), "+f"(d[18]), "+f"(d[19])
    : "r"(a0), "r"(a1), "r"(a2), "r"(a3), "l"(db), "r"(scale_d));
}

#define DEVINL __device__ __forceinline__
#define PSLEEP 0
#define XLATE 1
#define PLATE 1
#define HINT 4000
#define MWL mbar_wait_long
DEVINL void pin(uint32_t z) { asm volatile("{\n.reg .pred p;\nsetp.ne.u32 p, %0, 0;\nPIN:\n@p bra.uni PIN;\n}" ::"r"(z) : "memory"); }
DEVINL void wg_fence() { asm volatile("wgmma.fence.sync.aligned;" ::: "memory"); }
DEVINL void wg_commit() { asm volatile("wgmma.commit_group.sync.aligned;" ::: "memory"); }
template <int N> DEVINL void wg_wait() { asm volatile("wgmma.wait_group.sync.aligned %0;" ::"n"(N) : "memory"); }
DEVINL uint64_t mkdesc(uint32_t addr, uint32_t lbo, uint32_t sbo, int sw) {
  return (uint64_t)((addr & 0x3FFFF) >> 4) | ((uint64_t)(lbo >> 4) << 16) | ((uint64_t)(sbo >> 4) << 32) | ((uint64_t)sw << 62);
}
DEVINL void mbar_arrive(uint32_t bar) { asm volatile("mbarrier.arrive.shared::cta.b64 _, [%0];" ::"r"(bar) : "memory"); }
DEVINL bool mbar_try(uint32_t bar, uint32_t parity) {
  uint32_t ok;
  asm volatile("{\n.reg .pred p;\nmbarrier.try_wait.parity.shared::cta.b64 p, [%1], %2;\nselp.u32 %0, 1, 0, p;\n}" : "=r"(ok) : "r"(bar), "r"(parity) : "memory");
  return ok;
}
DEVINL bool mbar_test(uint32_t bar, uint32_t parity) {
  uint32_t ok;
  asm volatile("{\n.reg .pred p;\nmbarrier.test_wait.parity.shared::cta.b64 p, [%1], %2;\nselp.u32 %0, 1, 0, p;\n}" : "=r"(ok) : "r"(bar), "r"(parity) : "memory");
  return ok;
}
DEVINL void mbar_hint(uint32_t bar, uint32_t parity) {
#pragma unroll 1
  for (uint32_t n = 0; n < 16u; n++) if (mbar_try(bar, parity)) break;
}
DEVINL void mbar_wait(uint32_t bar, uint32_t parity) {
#pragma unroll 1
  for (uint32_t n = 0; n < 100000u; n++) if (mbar_try(bar, parity)) break;
}
DEVINL void mbar_wait_long(uint32_t bar, uint32_t parity) {
#pragma unroll 1
  for (uint32_t n = 0; n < 100000u; n++) {
    uint32_t ok;
    asm volatile("{\n.reg .pred p;\nmbarrier.try_wait.parity.shared::cta.b64 p, [%1], %2, %3;\nselp.u32 %0, 1, 0, p;\n}" : "=r"(ok) : "r"(bar), "r"(parity), "r"(HINT) : "memory");
    if (ok) break;
  }
}
#define EL(txt) "{\n.reg .pred pe;\nelect.sync _|pe, 0xffffffff;\n@pe " txt "\n}"
DEVINL void e_expect_tx(uint32_t bar, uint32_t bytes) { asm volatile(EL("mbarrier.arrive.expect_tx.shared::cta.b64 _, [%0], %1;") ::"r"(bar), "r"(bytes) : "memory"); }
DEVINL void e_init(uint32_t bar, uint32_t cnt) { asm volatile(EL("mbarrier.init.shared::cta.b64 [%0], %1;") ::"r"(bar), "r"(cnt) : "memory"); }
DEVINL void e_arrive(uint32_t bar) { asm volatile(EL("mbarrier.arrive.shared::cta.b64 _, [%0];") ::"r"(bar) : "memory"); }
DEVINL void e_red(uint32_t* p) { asm volatile(EL("red.release.gpu.global.add.u32 [%0], 1;") ::"l"(p) : "memory"); }
DEVINL void e_red_relaxed(uint32_t* p) { asm volatile(EL("red.relaxed.gpu.global.add.u32 [%0], 1;") ::"l"(p) : "memory"); }
DEVINL void tma_ld(uint32_t dst, const CUtensorMap* m, int c0, int c1, uint32_t bar) {
  asm volatile(EL("cp.async.bulk.tensor.2d.shared::cluster.global.mbarrier::complete_tx::bytes [%0], [%1, {%3, %4}], [%2];")
               ::"r"(dst), "l"(m), "r"(bar), "r"(c0), "r"(c1) : "memory");
}
DEVINL void tma_ld3(uint32_t dst, const CUtensorMap* m, int c0, int c1, int c2, uint32_t bar) {
  asm volatile(EL("cp.async.bulk.tensor.3d.shared::cluster.global.mbarrier::complete_tx::bytes [%0], [%1, {%3, %4, %5}], [%2];")
               ::"r"(dst), "l"(m), "r"(bar), "r"(c0), "r"(c1), "r"(c2) : "memory");
}
DEVINL void tma_ld5(uint32_t dst, const CUtensorMap* m, int c2, int c3, int c4, uint32_t bar) {
  asm volatile(EL("cp.async.bulk.tensor.5d.shared::cluster.global.mbarrier::complete_tx::bytes [%0], [%1, {0, 0, %3, %4, %5}], [%2];")
               ::"r"(dst), "l"(m), "r"(bar), "r"(c2), "r"(c3), "r"(c4) : "memory");
}
DEVINL void tma_ld_mc(uint32_t dst, const CUtensorMap* m, int c0, int c1, uint32_t bar) {
  asm volatile(EL("cp.async.bulk.tensor.2d.shared::cluster.global.mbarrier::complete_tx::bytes.multicast::cluster [%0], [%1, {%3, %4}], [%2], %5;")
               ::"r"(dst), "l"(m), "r"(bar), "r"(c0), "r"(c1), "h"((uint16_t)3) : "memory");
}
DEVINL void e_arrive_both(uint32_t bar) {
  asm volatile("{\n.reg .pred pe;\n.reg .b32 r0, r1;\nelect.sync _|pe, 0xffffffff;\nmapa.shared::cluster.u32 r0, %0, 0;\nmapa.shared::cluster.u32 r1, %0, 1;\n"
               "@pe mbarrier.arrive.shared::cluster.b64 _, [r0];\n@pe mbarrier.arrive.shared::cluster.b64 _, [r1];\n}" ::"r"(bar) : "memory");
}
DEVINL void push_peer(uint32_t dst, uint32_t src, uint32_t bar, uint32_t peer) {
  asm volatile("{\n.reg .pred pe;\n.reg .b32 d, b;\nelect.sync _|pe, 0xffffffff;\nmapa.shared::cluster.u32 d, %0, %3;\nmapa.shared::cluster.u32 b, %2, %3;\n"
               "@pe cp.async.bulk.shared::cluster.shared::cta.mbarrier::complete_tx::bytes [d], [%1], 16384, [b];\n}" ::"r"(dst), "r"(src), "r"(bar), "r"(peer) : "memory");
}
DEVINL void tma_st(const CUtensorMap* m, int c0, int c1, uint32_t src) {
  asm volatile(EL("cp.async.bulk.tensor.2d.global.shared::cta.bulk_group [%0, {%2, %3}], [%1];") ::"l"(m), "r"(src), "r"(c0), "r"(c1) : "memory");
}
DEVINL void bulk_commit() { asm volatile("cp.async.bulk.commit_group;" ::: "memory"); }
template <int N> DEVINL void bulk_wait_n() { asm volatile("cp.async.bulk.wait_group %0;\nbar.warp.sync 0xffffffff;" ::"n"(N) : "memory"); }
DEVINL void l2_prefetch(const void* g, uint32_t bytes) { asm volatile(EL("cp.async.bulk.prefetch.L2.global [%0], %1;") ::"l"(g), "r"(bytes) : "memory"); }
DEVINL void fence_async_smem() { asm volatile("fence.proxy.async.shared::cta;" ::: "memory"); }
DEVINL void fence_async_gl() { asm volatile("fence.proxy.async.global;" ::: "memory"); }
DEVINL void cluster_wait() { asm volatile("barrier.cluster.wait.aligned;" ::: "memory"); }
DEVINL void bar_sync(int id, int n) { asm volatile("bar.sync %0, %1;" ::"r"(id), "r"(n) : "memory"); }
DEVINL void bar_arrive(int id, int n) { asm volatile("bar.arrive %0, %1;" ::"r"(id), "r"(n) : "memory"); }
DEVINL uint32_t ld_acquire(const uint32_t* p) { uint32_t v; asm volatile("ld.acquire.gpu.global.u32 %0, [%1];" : "=r"(v) : "l"(p) : "memory"); return v; }
DEVINL void watch(const uint32_t* p, uint32_t target, uint32_t all, uint32_t tag, uint32_t slot) {
  uint32_t seen = 0;
#pragma unroll 1
  for (uint32_t n = 0; n < 200000u && seen != all; n++) {
    const uint32_t m = __ballot_sync(~0u, (int)(ld_acquire(p) - target) >= 0) & all;
    if (m != seen) { seen = m; asm volatile("st.release.cta.shared.u32 [%0], %1;" ::"r"(slot), "r"(tag << 16 | m) : "memory"); }
  }
}
template <bool RELAXED = false> DEVINL void await_bit(uint32_t slot, uint32_t tag, int j, uint32_t& rdy) {
  if ((rdy >> j) & 1) return;
#pragma unroll 1
  for (uint32_t n = 0; n < 8000000u; n++) {
    uint32_t v;
    asm volatile("ld.acquire.cta.shared.u32 %0, [%1];" : "=r"(v) : "r"(slot) : "memory");
    if ((v >> 16) == tag && ((v >> j) & 1)) { rdy = v; break; }
    if (RELAXED) __nanosleep(200); else if (PSLEEP) __nanosleep(PSLEEP);
  }
  asm volatile("fence.proxy.async.global;" ::: "memory");
}
DEVINL void poll_ge(const uint32_t* p, uint32_t target) {
#pragma unroll 1
  for (uint32_t n = 0; n < 200000u; n++) if (__all_sync(~0u, (int)(ld_acquire(p) - target) >= 0)) break;
}
DEVINL int lane_id() { int v; asm volatile("mov.u32 %0, %%laneid;" : "=r"(v)); return v; }
__host__ DEVINL int remap(int v) {
  const int c = v >> 1, u = c - 36, r = (u * 37) >> 8;
  const int L = max(c - 4 + max(r + 1, 0), (c - 4) >> 31 & (32 + 8 * c));
  return 2 * L + (v & 1);
}
DEVINL int block_id() { int v; asm volatile("mov.u32 %0, %%ctaid.x;" : "=r"(v)); return v; }
#define cta_id() prm.map[block_id()]
#define IDS() const int lane = lane_id(), b = cta_id(), bm = b >> 4, bn = b & 15, rank = b & 1, pm = 2 * bm + (bn >> 3), pn = bn & 7, po = pm & 1; \
  (void)lane; (void)bm; (void)bn; (void)rank; (void)pm; (void)pn; (void)po
DEVINL void st_tagged(unsigned long long* p, uint32_t v, uint32_t tag) {
  asm volatile("{\n.reg .b64 t;\nmov.b64 t, {%1, %2};\nst.relaxed.gpu.global.b64 [%0], t;\n}" ::"l"(p), "r"(v), "r"(tag) : "memory");
}
DEVINL float ex2(float x) { float y; asm("ex2.approx.ftz.f32 %0, %1;" : "=f"(y) : "f"(x)); return y; }
DEVINL float rcp(float x) { float y; asm("rcp.approx.ftz.f32 %0, %1;" : "=f"(y) : "f"(x)); return y; }
DEVINL uint32_t pack2(float lo, float hi) { uint32_t r; asm("cvt.rn.bf16x2.f32 %0, %1, %2;" : "=r"(r) : "f"(hi), "f"(lo)); return r; }
DEVINL float bf_lo(uint32_t w) { return __uint_as_float(w << 16); }
DEVINL float bf_hi(uint32_t w) { return __uint_as_float(w & 0xFFFF0000u); }
DEVINL float bf_round(float x) { return bf_lo(pack2(x, 0.f)); }
DEVINL uint32_t add_bf16x2(uint32_t a, uint32_t b) { uint32_t r; asm("add.rn.bf16x2 %0, %1, %2;" : "=r"(r) : "r"(a), "r"(b)); return r; }
DEVINL void stsm4(uint32_t addr, uint32_t a, uint32_t b, uint32_t c, uint32_t d) {
  asm volatile("stmatrix.sync.aligned.m8n8.x4.shared.b16 [%0], {%1, %2, %3, %4};" ::"r"(addr), "r"(a), "r"(b), "r"(c), "r"(d) : "memory");
}
DEVINL void ldsm4(uint32_t addr, uint32_t (&r)[4]) {
  asm volatile("ldmatrix.sync.aligned.m8n8.x4.shared.b16 {%0, %1, %2, %3}, [%4];" : "=r"(r[0]), "=r"(r[1]), "=r"(r[2]), "=r"(r[3]) : "r"(addr) : "memory");
}
DEVINL void ldsm4t(uint32_t addr, uint32_t (&r)[4]) {
  asm volatile("ldmatrix.sync.aligned.m8n8.x4.trans.shared.b16 {%0, %1, %2, %3}, [%4];" : "=r"(r[0]), "=r"(r[1]), "=r"(r[2]), "=r"(r[3]) : "r"(addr) : "memory");
}
DEVINL void sts128(uint32_t addr, uint32_t a, uint32_t b, uint32_t c, uint32_t d) {
  asm volatile("st.shared.v4.b32 [%0], {%1, %2, %3, %4};" ::"r"(addr), "r"(a), "r"(b), "r"(c), "r"(d) : "memory");
}
DEVINL float4 lds128f(uint32_t addr) { float4 v; asm volatile("ld.shared.v4.f32 {%0, %1, %2, %3}, [%4];" : "=f"(v.x), "=f"(v.y), "=f"(v.z), "=f"(v.w) : "r"(addr) : "memory"); return v; }
DEVINL float lds32f(uint32_t addr) { float v; asm volatile("ld.shared.f32 %0, [%1];" : "=f"(v) : "r"(addr) : "memory"); return v; }
DEVINL float2 lds64f(uint32_t addr) { float2 v; asm volatile("ld.shared.v2.f32 {%0, %1}, [%2];" : "=f"(v.x), "=f"(v.y) : "r"(addr) : "memory"); return v; }
DEVINL void mma16816(float (&d)[4], uint32_t a0, uint32_t a1, uint32_t a2, uint32_t a3, uint32_t b0, uint32_t b1) {
  asm("mma.sync.aligned.m16n8k16.row.col.f32.bf16.bf16.f32 {%0, %1, %2, %3}, {%4, %5, %6, %7}, {%8, %9}, {%0, %1, %2, %3};"
               : "+f"(d[0]), "+f"(d[1]), "+f"(d[2]), "+f"(d[3]) : "r"(a0), "r"(a1), "r"(a2), "r"(a3), "r"(b0), "r"(b1));
}
DEVINL void mma1688(float (&d)[4], uint32_t a0, uint32_t a1, uint32_t b0) {
  asm("mma.sync.aligned.m16n8k8.row.col.f32.bf16.bf16.f32 {%0, %1, %2, %3}, {%4, %5}, {%6}, {%0, %1, %2, %3};"
               : "+f"(d[0]), "+f"(d[1]), "+f"(d[2]), "+f"(d[3]) : "r"(a0), "r"(a1), "r"(b0));
}
DEVINL void mma16816h(float (&d)[4], uint32_t a0, uint32_t a1, uint32_t a2, uint32_t a3, uint32_t b0, uint32_t b1) {
  asm("mma.sync.aligned.m16n8k16.row.col.f32.f16.f16.f32 {%0, %1, %2, %3}, {%4, %5, %6, %7}, {%8, %9}, {%0, %1, %2, %3};"
               : "+f"(d[0]), "+f"(d[1]), "+f"(d[2]), "+f"(d[3]) : "r"(a0), "r"(a1), "r"(a2), "r"(a3), "r"(b0), "r"(b1));
}
template <int N> DEVINL void fence_regs(uint32_t (&d)[N]) {
#pragma unroll
  for (int i = 0; i < N; i++) asm volatile("" : "+r"(d[i])::"memory");
}
template <int N> DEVINL void fence_regs(float (&d)[N]) {
#pragma unroll
  for (int i = 0; i < N; i++) asm volatile("" : "+f"(d[i])::"memory");
}

__device__ __align__(1024) bf16 g_xs[2048 * 1024];
__device__ __align__(1024) bf16 g_os[2048 * 1024];
__device__ __align__(1024) bf16 g_k[32 * 2048 * 32];
__device__ __align__(1024) bf16 g_v[32 * 2048 * 32];
__device__ __align__(128) float2 g_stats[8 * 2048];
__device__ __align__(16) float g_csp[2 * 16 * 8 * 192];
__device__ __align__(128) float g_kn[2 * 128 * 32];
__device__ unsigned long long g_halo[2 * 128 * 32 * 32];
__device__ __align__(128) uint32_t g_cnt[256 * 32];
__device__ uint32_t g_epoch;

DEVINL uint32_t* cnt_x(int l, int bm) { return g_cnt + (l * 8 + bm) * 32; }
DEVINL uint32_t* cnt_o(int l, int pm, int h) { return g_cnt + (32 + (l * 16 + pm) * 2 + h) * 32; }
DEVINL uint32_t* cnt_kv(int lb, int bn) { return g_cnt + (160 + lb * 16 + bn) * 32; }
DEVINL uint32_t* cnt_ad(int bn) { return g_cnt + (192 + bn) * 32; }
DEVINL uint32_t* cnt_cs(int t, int bn) { return g_cnt + (208 + t * 16 + bn) * 32; }

DEVINL int qord(int i, int l, int pn) { return l == 0 ? i : i < 4 ? ((2 * pn) ^ (i & 2)) + (i & 1) : i - 4 < 2 * (pn & 6) ? i - 4 : i; }
struct Params {
  CUtensorMap m[17];
  const bf16* x0;
  const bf16* wq[2];
  const bf16* wo[2];
  uint32_t* epoch;
  uint32_t zero;
  int map[128];
};
enum { M_X0A = 0, M_XSA, M_WQA, M_WQB, M_WOA, M_WOB, M_OS, M_K, M_V, M_X0R, M_XSR, M_XSO, M_OUT, M_XST, M_X0H, M_K4, M_V4, M_COUNT };

constexpr uint32_t QSTG = 57344;
constexpr uint32_t T0 = 65536, TSTG = 32768;
constexpr uint32_t ONES = 229376;
constexpr uint32_t PSTG = 32768, RES = 196608;
constexpr uint32_t ASC = 17408;
constexpr uint32_t RSTD = 229376, MEAN = 230400, COLS = 230912, KMAX = 231680, B_QD = 231688, BARS = 232192, SMEM_BYTES = 232448;
constexpr uint32_t B_QF = BARS, B_QE = BARS + 32, B_TF = BARS + 64, B_TE = BARS + 96, B_PF = BARS + 128, B_PE = BARS + 176,
                   B_RF = BARS + 224, W_X = BARS + 232, W_O = BARS + 236, B_QL = BARS + 240, B_PA = BARS + 248;
enum { NB_ST = 1, NB_KV = 2  , NB_DONE = 3, NB_SC = 4, NB_SIG = 5  , NB_KN = 9  , NB_X = 11, NB_HALO = 12  , NB_X0 = 15 };

DEVINL uint32_t pslot_b(uint32_t s, int l) { return ((((l & 1) ? 0x320415u : 0x468795u) >> (4 * s)) & 15) * 16384u; }
DEVINL uint32_t pslot_a(uint32_t s, int l) { return ((((l & 1) ? 0xBA7896u : 0x32DCBAu) >> (4 * s)) & 15) * 16384u; }

#define G1 2
#define G2 0
#define G3 2
#define KC (11 + 2 * wg)
#define NA2 2
#define RESI 9
#define PERHEAD 1
#define LA 1
#define LB 1
#define PFETCH 0
#define PFW 3
#define PFI 8
#define H1ST 4
#define H1RED 5
#define NQ 32
#define OA 0x10
#define OB 0x10
#define LAG 2
#define QK_A wgmma_m64n32k16_rs_nb_h
#define QK_B wgmma_m64n32k16_rs_nb_hh
constexpr float QSCALE = 0.17677669529663687f * 1.4426950408889634f;

DEVINL uint32_t hfma2(uint32_t a, uint32_t b, uint32_t c) { uint32_t r; asm("fma.rn.f16x2 %0, %1, %2, %3;" : "=r"(r) : "r"(a), "r"(b), "r"(c)); return r; }
DEVINL uint32_t pack2h(float lo, float hi) { uint32_t r; asm("cvt.rn.f16x2.f32 %0, %1, %2;" : "=r"(r) : "f"(hi), "f"(lo)); return r; }
DEVINL uint32_t h2_to_bf2(uint32_t h) {
  float a, b;
  asm("{\n.reg .b16 l, h;\nmov.b32 {l, h}, %2;\ncvt.f32.f16 %0, l;\ncvt.f32.f16 %1, h;\n}" : "=f"(a), "=f"(b) : "r"(h));
  return pack2(a, b);
}
DEVINL uint32_t exp2_h2(uint32_t s) {
  const uint32_t r = hfma2(s, 0x00800080u, 0x007E007Eu);
  const uint32_t g = hfma2(hfma2(r, 0xF800F800u, 0x33FD33FDu), 0x44004400u, s);
  return r * 128u + hfma2(hfma2(g, g, 0x0DE10DE1u), g, 0x00300030u);
}
constexpr uint32_t NOT_F16 = 0x7FC00000u, K_LO = 0x35000000u  ;
DEVINL uint32_t f16_class(uint32_t norm2, uint32_t lo) { return norm2 - lo > 0x4E800000u - lo ? NOT_F16 : norm2; }

DEVINL void attn_slow(const uint32_t (&q)[8], float up, int head, const float* kn, float (&res)[20], int lane) {
  const int g = lane >> 2, qd = lane & 3;
  const bf16* kb = g_k + (size_t)head * 2048 * 32;
  const bf16* vb = g_v + (size_t)head * 2048 * 32;
  float o[4][4], m0 = -INFINITY, m1 = -INFINITY, l0 = 0.f, l1 = 0.f;
#pragma unroll
  for (int j = 0; j < 4; j++) { o[j][0] = o[j][1] = o[j][2] = o[j][3] = 0.f; }
#pragma unroll 1
  for (int k0 = 0; k0 < 2048; k0 += 16) {
    float s[2][4];
    const bool kh = __float_as_uint(__ldcg(kn + (k0 >> 8) * 32 + ((k0 >> 6) & 1) * 8 + ((k0 >> 7) & 1) * 4 + ((k0 >> 4) & 3))) != NOT_F16;
#pragma unroll
    for (int nt = 0; nt < 2; nt++) {
      s[nt][0] = s[nt][1] = s[nt][2] = s[nt][3] = 0.f;
      const uint32_t* kp = (const uint32_t*)(kb + (size_t)(k0 + nt * 8 + g) * 32) + qd;
      uint32_t kf[4];
#pragma unroll
      for (int i = 0; i < 4; i++) { kf[i] = __ldcg(kp + 4 * i); if (kh) kf[i] = h2_to_bf2(kf[i]); }
      mma16816(s[nt], q[0], q[1], q[2], q[3], kf[0], kf[1]);
      mma16816(s[nt], q[4], q[5], q[6], q[7], kf[2], kf[3]);
      s[nt][0] *= up; s[nt][1] *= up; s[nt][2] *= up; s[nt][3] *= up;
    }
    float a0 = fmaxf(fmaxf(s[0][0], s[0][1]), fmaxf(s[1][0], s[1][1]));
    float a1 = fmaxf(fmaxf(s[0][2], s[0][3]), fmaxf(s[1][2], s[1][3]));
    a0 = fmaxf(a0, __shfl_xor_sync(~0u, a0, 1)); a0 = fmaxf(a0, __shfl_xor_sync(~0u, a0, 2));
    a1 = fmaxf(a1, __shfl_xor_sync(~0u, a1, 1)); a1 = fmaxf(a1, __shfl_xor_sync(~0u, a1, 2));
    const float n0 = fmaxf(m0, a0), n1 = fmaxf(m1, a1);
    const float c0 = (m0 == n0) ? 1.f : ex2(m0 - n0), c1 = (m1 == n1) ? 1.f : ex2(m1 - n1);
    m0 = n0; m1 = n1;
    const uint32_t p0 = pack2(ex2(s[0][0] - n0), ex2(s[0][1] - n0)), p1 = pack2(ex2(s[0][2] - n1), ex2(s[0][3] - n1));
    const uint32_t p2 = pack2(ex2(s[1][0] - n0), ex2(s[1][1] - n0)), p3 = pack2(ex2(s[1][2] - n1), ex2(s[1][3] - n1));
    l0 = l0 * c0 + bf_lo(p0) + bf_hi(p0) + bf_lo(p2) + bf_hi(p2);
    l1 = l1 * c1 + bf_lo(p1) + bf_hi(p1) + bf_lo(p3) + bf_hi(p3);
#pragma unroll
    for (int j = 0; j < 4; j++) {
      o[j][0] *= c0; o[j][1] *= c0; o[j][2] *= c1; o[j][3] *= c1;
      const unsigned short* vp = (const unsigned short*)(vb + (size_t)(k0 + 2 * qd) * 32 + j * 8 + g);
      const uint32_t b0 = (uint32_t)__ldcg(vp) | ((uint32_t)__ldcg(vp + 32) << 16);
      const uint32_t b1 = (uint32_t)__ldcg(vp + 256) | ((uint32_t)__ldcg(vp + 288) << 16);
      mma16816(o[j], p0, p1, p2, p3, b0, b1);
    }
  }
  l0 += __shfl_xor_sync(~0u, l0, 1); l0 += __shfl_xor_sync(~0u, l0, 2);
  l1 += __shfl_xor_sync(~0u, l1, 1); l1 += __shfl_xor_sync(~0u, l1, 2);
#pragma unroll
  for (int j = 0; j < 4; j++) { res[4 * j] = o[j][0]; res[4 * j + 1] = o[j][1]; res[4 * j + 2] = o[j][2]; res[4 * j + 3] = o[j][3]; }
  res[16] = l0; res[18] = l1;
}

__global__ void __cluster_dims__(2, 1, 1) __launch_bounds__(384, 1) fused_kernel(const __grid_constant__ Params prm) {
  extern __shared__ __align__(1024) char smem[];
  const uint32_t sb = (uint32_t)__cvta_generic_to_shared(smem);
  const int tid = threadIdx.x;
  const int wid = __shfl_sync(0xffffffffu, tid >> 5, 0), wg = wid >> 2, w = wid & 3;
  const int bm = remap(blockIdx.x) >> 4, bn = remap(blockIdx.x) & 15;
  auto first_tile = [&](int kt) {
    e_expect_tx(sb + B_QF + 8 * kt, QSTG);
    tma_ld(sb + kt * QSTG, &prm.m[M_X0A], kt * 64, bm * 256, sb + B_QF + 8 * kt);
    tma_ld3(sb + kt * QSTG + 32768, &prm.m[M_WQA], bn * 64, kt * 64, 0, sb + B_QF + 8 * kt);
  };
  if (wid == 8) {
    e_init(sb + B_QF, 1);
    asm volatile("fence.mbarrier_init.release.cluster;" ::: "memory");
    first_tile(0);
  }
  if (wid < 8) {
#pragma unroll
    for (int i = 0; i < 4; i++) {
      const uint32_t cnt = (uint32_t)((i == 0 ? 0x14112140 : i == 1 ? 0x04112141 : i == 2 ? 0x14412141 : 0x24412141) >> (4 * wid)) & 7;
      if (cnt) e_init(sb + BARS + 32 * wid + 8 * i, cnt);
    }
    if (wid == 0 || wid == 7) e_init(sb + B_QD + (wid & 1) * 8, 1);
    if (tid == 255) *(uint2*)(smem + W_X) = make_uint2(0u, 0u);
    asm volatile("fence.mbarrier_init.release.cluster;" ::: "memory");
  }
  const uint32_t epoch = *(volatile uint32_t*)prm.epoch;
  __syncthreads();
  asm volatile("barrier.cluster.arrive.relaxed.aligned;" ::: "memory");

  if (wg == 2) {
    asm volatile("setmaxnreg.dec.sync.aligned.u32 56;");
    const uint32_t ep1 = epoch + 1;
    if (w == 0) {
      first_tile(1);
      mbar_wait(sb + B_QF, 0);
      first_tile(2); first_tile(3);
#pragma unroll 1
      for (int kt = 4; kt < 16; kt++) l2_prefetch(prm.wq[0] + kt * 196608 + blockIdx.x * 1536, 3072);
      cluster_wait();
#pragma unroll 1
      for (int l = 0; l < 4; l++) {
        IDS();
        const CUtensorMap* mw = &prm.m[M_WQA + (l & 1)];
        const CUtensorMap* mh = &prm.m[l == 0 ? M_X0H : M_XSO];
        const CUtensorMap* mo = &prm.m[M_WOA + (l & 1)];
        auto q_b = [&](int i) {
          const int s = i & 3;
          mbar_wait(sb + B_QE + 8 * s, ((i >> 2) & 1) ^ 1);
          e_expect_tx(sb + B_QF + 8 * s, QSTG);
          tma_ld3(sb + s * QSTG + 32768, mw, bn * 64, qord(i, l, pn) * 64, 0, sb + B_QF + 8 * s);
        };
        uint32_t rdy = l ? 0u : ~0u;
        auto q_a = [&](int i) {
          const int kt = qord(i, l, pn);
          await_bit(sb + W_X, l, kt >> 1, rdy);
          tma_ld_mc(sb + (i & 3) * QSTG + rank * 16384, mh, kt * 64, bm * 256 + rank * 128, sb + B_QF + 8 * (i & 3));
        };
        if (l > 0) {
#pragma unroll 1
          for (int i = 0; i < 4; i++) {
            const int kt = qord(i, l, pn);
            await_bit(sb + W_X, l, kt >> 1, rdy);
            e_expect_tx(sb + B_QF + 8 * i, 16384);
            tma_ld(sb + i * QSTG + (po ^ 1) * 16384, &prm.m[M_XSO], kt * 64, (pm ^ 1) * 128, sb + B_QF + 8 * i);
          }
        }
#pragma unroll 1
        for (int i = 4; i < 16; i++) {
          q_b(i); q_a(i);
          if (l == 0 && (PFW & 1) && i >= PFI && i < PFI + 4) l2_prefetch(prm.wq[1] + (blockIdx.x * 4 + i - PFI) * 6144, 12288);
          if (l < 2 && (PFW & 2) && i == PFI + 4) l2_prefetch(prm.wo[l] + blockIdx.x * 8192, 16384);
        }
        if (l & 1) {
          if (l == 3) poll_ge(cnt_ad(bn), ep1 * 16);
          const int krow = 2 * bn * 2048 + bm * 256;
          uint32_t* kvc = cnt_kv(l >> 1, bn);
#pragma unroll 1
          for (int m = 1; m >= 0; m--) {
            bar_sync(m ? NB_ST : NB_KV, 288);
#pragma unroll
            for (int i = 0; i < 4; i++) tma_st(&prm.m[M_K4 + (i >> 1)], 0, krow + (i & 1) * 128 + m * 64, sb + T0 + i * 8192 + m * 4096);
            if (m) {
              sts128(sb + ONES + lane * 32, 0x3f803f80u, 0x3f803f80u, 0x3f803f80u, 0x3f803f80u);
              sts128(sb + ONES + lane * 32 + 16, 0x3f803f80u, 0x3f803f80u, 0x3f803f80u, 0x3f803f80u);
              fence_async_smem();
              __syncwarp();
            }
          }
          e_arrive(sb + B_TF);
          bulk_commit(); bulk_wait_n<0>();
          e_red(kvc + bm);
          bar_sync(NB_KV + 12, 288);
          uint32_t seen = 0;
#pragma unroll 1
          for (int it = 1; it < 16; it++) {
            const int s = it & 3, blk = it;
            if (it == H1ST) { tma_st(&prm.m[M_K], 0, krow + 2048, sb); tma_st(&prm.m[M_V], 0, krow + 2048, sb + 16384); bulk_commit(); }
            if (it == H1RED) { bulk_wait_n<0>(); e_red(kvc + bm); }
            if (it == 12) { e_expect_tx(sb + B_RF, 32768); tma_ld3(sb + RES, &prm.m[M_XSR], 0, pm * 128, 2 * pn, sb + B_RF); }
            if (it == 2 || it == 3) mbar_wait(sb + B_TF + 8 * (it - 1), 0);
            MWL(sb + B_TE + 8 * s, ((it >> 2) & 1) ^ 1);
            if (it < 8) {
#pragma unroll 1
              for (uint32_t n = 0; n < 200000u && !((seen >> it) & 1); n++)
                seen = __ballot_sync(~0u, (int)(ld_acquire(kvc + ((bm + lane) & 7)) - (ep1 * 2 - 1)) >= 0);
              fence_async_gl();
            } else if (it == 8) { poll_ge(kvc + (lane & 7), ep1 * 2); fence_async_gl(); bar_arrive(NB_HALO, 64); }
            else if (it == 15) bar_arrive(NB_HALO + 1, 64);
            const int row = (2 * bn + (it >> 3)) * 2048 + ((bm + blk) & 7) * 256;
            e_expect_tx(sb + B_TF + 8 * s, 32768);
            tma_ld(sb + T0 + s * TSTG, &prm.m[M_K], 0, row, sb + B_TF + 8 * s);
            tma_ld(sb + T0 + s * TSTG + 16384, &prm.m[M_V], 0, row, sb + B_TF + 8 * s);
          }
        }
        auto p_b = [&](int i, uint32_t s, uint32_t par) {
          mbar_wait(sb + B_PE + 8 * s, par ^ 1);
          e_expect_tx(sb + B_PF + 8 * s, PSTG);
          tma_ld5(sb + pslot_b(s, l), mo, i >> 3, 2 * (i & 7), 2 * pn, sb + B_PF + 8 * s);
        };
        auto p_a = [&](int i, uint32_t s) {
          await_bit(sb + W_O, l + 1, i, rdy);
          tma_ld_mc(sb + pslot_a(s, l) + rank * 8192, &prm.m[M_OS], i * 64, pm * 128 + rank * 64, sb + B_PF + 8 * s);
        };
        auto p_a2 = [&](int i) {
          await_bit(sb + W_O, l + 1, i, rdy);
          tma_ld(sb + pslot_a(i, l), &prm.m[M_OS], i * 64, pm * 128, sb + B_PF + 8 * i);
          tma_ld(sb + pslot_a(i, l) + 8192, &prm.m[M_OS], i * 64, pm * 128 + 64, sb + B_PF + 8 * i);
        };
        rdy = 0;
        if (l & 1) {
#pragma unroll 1
          for (int u = 0; u < 6; u++) { const int i = (0x205413 >> (4 * u)) & 7; if (u == 4) MWL(sb + B_TE, 1); p_b(i, i, i < 4 ? 1 : 0); }
#pragma unroll 1
          for (int u = 0; u < 6; u++) {
            const int i = (0x542130 >> (4 * u)) & 7;
            if (!(u & 1)) MWL(sb + B_TE + 8 + 4 * u, 1);
            p_a2(i);
          }
        } else {
#pragma unroll 1
          for (int u = 0; u < 5; u++) { const int i = (0x32140 >> (4 * u)) & 7; if (!(u & 5)) mbar_wait(sb + B_QE + 8 + 4 * u, 1); p_b(i, i, 0); }
          mbar_wait(sb + B_QE + 24, 1);
          if (PLATE) bar_sync(NB_KN, 96);
#pragma unroll 1
          for (int i = 0; i < 4; i++) { if (i < NA2) p_a2(i); else p_a(i, i); }
          bar_sync(NB_DONE, 96);
          e_arrive_both(sb + B_PA);
          p_b(5, 5, 0);
          mbar_wait(sb + B_PA, (l >> 1) & 1);
          p_a(4, 4); p_a(5, 5);
        }
        uint32_t s = 0, lap = 1;
#pragma unroll 1
        for (int i = 6; i < 16; i++) {
          if (i == RESI && !(l & 1)) { e_expect_tx(sb + B_RF, 32768); tma_ld3(sb, &prm.m[l == 0 ? M_X0R : M_XSR], 0, pm * 128, 2 * pn, sb + B_RF); }
          p_b(i, s, ((s < 4 ? l : 0) + lap) & 1);
          p_a(i, s);
          if (++s == 6) { s = 0; lap++; }
        }
        const CUtensorMap* mn = &prm.m[M_WQA + ((l + 1) & 1)];
        if (l < 3) {
          mbar_wait(sb + B_PE + 8 * 4, 1); mbar_wait(sb + B_PE + 8 * 5, 1);
          tma_ld3(sb + 32768, mn, bn * 64, 2 * pn * 64, 0, sb + B_QL);
          mbar_wait(sb + B_PE + 8 * 0, l & 1);
          tma_ld3(sb + QSTG + 32768, mn, bn * 64, (2 * pn + 1) * 64, 0, sb + B_QL);
          mbar_wait(sb + B_PE + 8 * 1, l & 1);
          e_expect_tx(sb + B_QD, 40960);
          tma_ld3(sb + 2 * QSTG + 32768, mn, bn * 64, ((2 * pn) ^ 2) * 64, 0, sb + B_QD);
          bar_sync(NB_X, 288);
          e_expect_tx(sb + B_QL, 49152);
          e_expect_tx(sb + B_QD + 8, 40960);
          tma_ld3(sb + 3 * QSTG + 32768, mn, bn * 64, (((2 * pn) ^ 2) + 1) * 64, 0, sb + B_QD + 8);
        }
      }
      if (blockIdx.x == 0 && lane_id() == 0) *(volatile uint32_t*)prm.epoch = ep1;
    } else {
      const int hw = w - 1;
      if (hw == 1 && lane_id() < M_COUNT) asm volatile("prefetch.tensormap [%0];" ::"l"(&prm.m[lane_id()]) : "memory");
      cluster_wait();
      mbar_wait(sb + B_QF, 0);
#pragma unroll 1
      for (int l = 0; l < 4; l++) {
        IDS();
        if (hw == 2 && l > 0) watch(cnt_x(l, bm) + (lane & 7), ep1 * 2, 0xFFu, l, sb + W_X);
        if (l == 0) {
#pragma unroll 1
          for (int r = 2 * hw; r < 16; r += 6) {
            const uint4* p = (const uint4*)(prm.x0 + (size_t)(b * 16 + r) * 1024) + lane;
            float s1[2] = {0.f, 0.f}, s2[2] = {0.f, 0.f};
#pragma unroll
            for (int i = 0; i < 8; i++) {
              const uint4 v = __ldg(p + 32 * i);
              const uint32_t u[4] = {v.x, v.y, v.z, v.w};
#pragma unroll
              for (int k = 0; k < 4; k++) { const float a = bf_lo(u[k]), c = bf_hi(u[k]); s1[i >> 2] += a + c; s2[i >> 2] = fmaf(a, a, fmaf(c, c, s2[i >> 2])); }
            }
#pragma unroll
            for (int o = 16; o; o >>= 1)
#pragma unroll
              for (int rr = 0; rr < 2; rr++) { s1[rr] += __shfl_xor_sync(~0u, s1[rr], o); s2[rr] += __shfl_xor_sync(~0u, s2[rr], o); }
            if (lane == 0) *(float4*)&g_stats[b * 16 + r] = make_float4(s1[0], s2[0], s1[1], s2[1]);
          }
        }
        if (l == 1) { uint32_t rdy = 0; await_bit<true>(sb + W_X, 1, pn, rdy); mbar_hint(sb + B_QF + 8, 0); }
        if (l < 2) {
          float cs[8];
#pragma unroll
          for (int i = 0; i < 8; i++) cs[i] = 0.f;
          const uint4* wp = (const uint4*)(prm.wq[l] + (size_t)(bm * 128 + (lane >> 3)) * 3072 + hw * 1024 + bn * 64) + (lane & 7);
#pragma unroll 8
          for (int i = 0; i < 32; i++) {
            const uint4 v = __ldg(wp + (size_t)i * 4 * 384);
            cs[0] += bf_lo(v.x); cs[1] += bf_hi(v.x); cs[2] += bf_lo(v.y); cs[3] += bf_hi(v.y);
            cs[4] += bf_lo(v.z); cs[5] += bf_hi(v.z); cs[6] += bf_lo(v.w); cs[7] += bf_hi(v.w);
          }
#pragma unroll
          for (int i = 0; i < 8; i++) { cs[i] += __shfl_xor_sync(~0u, cs[i], 8); cs[i] += __shfl_xor_sync(~0u, cs[i], 16); }
          if (lane < 8) {
            float4* d = (float4*)(g_csp + ((l * 16 + bn) * 8 + bm) * 192 + hw * 64 + lane * 8);
            d[0] = make_float4(cs[0], cs[1], cs[2], cs[3]); d[1] = make_float4(cs[4], cs[5], cs[6], cs[7]);
          }
          __syncwarp();
          asm volatile("fence.acq_rel.gpu;" ::: "memory");
          e_red_relaxed(cnt_cs(l, bn));
          if (l == 0) e_red_relaxed(cnt_x(0, bm) + pn);
          poll_ge(lane < 8 && l == 0 ? cnt_x(0, bm) + lane : cnt_cs(l, bn), ep1 * (lane < 8 && l == 0 ? 6 : 24));
        }
        if (l > 0) {
          uint32_t rdy = 0;
#pragma unroll 1
          for (int j = 0; j < 8; j++) await_bit<true>(sb + W_X, l, j, rdy);
        }
#pragma unroll 1
        for (int it = hw * 32 + lane; it < 176; it += 96) {
          const bool rows = it < 128;
          const float4* p = rows ? (const float4*)(g_stats + bm * 256) + it : (const float4*)(g_csp + ((l & 1) * 16 + bn) * 8 * 192) + (it - 128);
          const int stride = rows ? 1024 : 48, np = rows && l == 0 ? 1 : 8;
          float4 a = make_float4(0.f, 0.f, 0.f, 0.f);
#pragma unroll
          for (int k = 0; k < 8; k++) if (k < np) { const float4 v = __ldcg(p + k * stride); a.x += v.x; a.y += v.y; a.z += v.z; a.w += v.w; }
          if (rows) {
            const float m0 = a.x * (1.f / 1024.f), m1 = a.z * (1.f / 1024.f);
            const float v0 = fmaxf(a.y * (1.f / 1024.f) - m0 * m0, 0.f), v1 = fmaxf(a.w * (1.f / 1024.f) - m1 * m1, 0.f);
            const float r0 = __fdividef(1.f, bf_round(sqrtf(bf_round(bf_round(v0) + 1e-5f)))), r1 = __fdividef(1.f, bf_round(sqrtf(bf_round(bf_round(v1) + 1e-5f))));
            *(float2*)(smem + RSTD + it * 8) = make_float2(r0, r1);
            *(uint32_t*)(smem + MEAN + it * 4) = pack2(-m0, -m1);
          } else {
            float2* d = (float2*)(smem + COLS) + ((it - 128) >> 2) * 8 + (it & 1) * 4 + ((it >> 1) & 1);
            d[0] = make_float2(a.y, a.x); d[2] = make_float2(a.w, a.z);
          }
        }
        __syncwarp();
        if (lane == 0) asm volatile("red.release.cta.shared.add.u32 [%0], 0x100;" ::"r"(sb + W_X) : "memory");
        if (hw == 2) {
          if (!(l & 1)) {
            bar_sync(NB_ST, 288);
            const volatile unsigned long long* hp = g_halo + ((size_t)(l >> 1) * 128 + b - 16) * 1024 + lane;
#pragma unroll 1
            for (int h = 0; h < 2; h++) {
              uint32_t t[16];
#pragma unroll
              for (int i = 0; i < 16; i++) t[i] = 0;
#pragma unroll 1
              for (uint32_t n = bm ? 0 : 100000u; n < 100000u; n++) {
                uint32_t miss = 0;
#pragma unroll
                for (int i = 0; i < 16; i++) {
                  const unsigned long long v = hp[h * 512 + i * 32];
                  t[i] = (uint32_t)v; miss |= (uint32_t)(v >> 32) ^ ep1;
                }
                if (__all_sync(~0u, !miss)) break;
              }
              const uint32_t r = (lane & 7) + ((lane >> 3) & 1) * 8, rv = lane >> 2;
#pragma unroll
              for (int jj = 0; jj < 2; jj++) stsm4(sb + 2 * h * ASC + r * 64 + (((2 * jj + (lane >> 4)) ^ ((r >> 1) & 3)) << 4), t[4 * jj], t[4 * jj + 1], t[4 * jj + 2], t[4 * jj + 3]);
              const uint32_t ad = sb + (2 * h + 1) * ASC + rv * 64 + (((lane & 3) ^ ((rv >> 1) & 3)) << 4);
              sts128(ad, t[8], t[10], t[12], t[14]); sts128(ad + 512, t[9], t[11], t[13], t[15]);
              bar_arrive(NB_HALO + h, 64);
            }
          } else {
            bar_sync(NB_HALO, 64);
            const uint4* kp = (const uint4*)(g_kn + ((l >> 1) * 128 + bn * 8) * 32) + 2 * lane;
            const uint4 v = __ldcg(kp), u = __ldcg(kp + 1);
            const uint32_t mx = max(max(max(v.x, v.y), max(v.z, v.w)), max(max(u.x, u.y), max(u.z, u.w)));
            const uint32_t m0 = __reduce_max_sync(~0u, (lane & 2) ? 0u : mx), m1 = __reduce_max_sync(~0u, (lane & 2) ? mx : 0u);
            if (lane == 0) *(uint2*)(smem + KMAX) = make_uint2(m0, m1);
            __syncwarp();
            bar_arrive(NB_KN, 160); bar_arrive(NB_KN + 1, 160);
            bar_sync(NB_HALO + 1, 64);
            watch(cnt_o(l, pm, 0) + (lane & 7), ep1 * 2, 0xFFu, l + 1, sb + W_O);
          }
        } else {
          bar_sync(NB_SIG + 2 * hw, 160); bar_sync(NB_SIG + 2 * hw + 1, 160);
          if (!(l & 1)) bar_arrive(NB_DONE, 96);
          if (hw == (l & 1)) bar_arrive((l & 1) ? NB_DONE : NB_KN, (l & 1) ? 64 : 64 + 32 * PLATE);
          asm volatile("fence.acq_rel.gpu;" ::: "memory");
          e_red_relaxed(cnt_o(l, 2 * bm, hw) + (bn >> 1));
          e_red_relaxed(cnt_o(l, 2 * bm + 1, hw) + (bn >> 1));
          if (hw == 1 && l == 1) { e_red_relaxed(cnt_ad(bn)); e_red_relaxed(cnt_ad(bn)); }
        }
        if (hw == 2) { bar_sync((l & 1) ? NB_DONE : NB_KN, (l & 1) ? 64 : 64 + 32 * PLATE); watch(cnt_o(l, pm, (lane >> 3) & 1) + (lane & 7), ep1 * 2, 0xFFFFu, l + 1, sb + W_O); }
        if (hw < 2 + XLATE && l < 3) {
          bar_sync(NB_X0, 320 + 32 * XLATE);
          if (hw == 0) {
            e_red(cnt_x(l + 1, bm) + pn);
          } else if (hw == 1) {
            mbar_wait(sb + B_PE + 8 * 3, l & 1);
            push_peer(sb + 2 * QSTG + po * 16384, sb + po * 16384, sb + B_QD, rank ^ 1);
            push_peer(sb + 3 * QSTG + po * 16384, sb + QSTG + po * 16384, sb + B_QD + 8, rank ^ 1);
          }
        }
      }
    }
  } else {
    asm volatile("setmaxnreg.inc.sync.aligned.u32 224;");
    const uint32_t zero = prm.zero;
    cluster_wait();
    const uint32_t ep1 = __shfl_sync(~0u, epoch + 1, 0);
#pragma unroll 1
    for (int l = 0; l < 4; l++) {
      {
        float acc[2][96];
#pragma unroll
        for (int i = 0; i < 96; i++) { acc[0][i] = 0.f; acc[1][i] = 0.f; }
        fence_regs(acc[0]); fence_regs(acc[1]);
        const bool early = l > 0 && wg == ((cta_id() >> 3) & 1);
#pragma unroll 1
        for (int kt = 0; kt < 14; kt++) {
          const int s = kt & 3;
          if (l > 0 && kt < 4 && kt != 1) mbar_wait(sb + (kt ? B_QD - 16 + 8 * kt : B_QL), (l + 1) & 1);
          if (!(early && kt < 4)) mbar_wait(sb + B_QF + 8 * s, (kt >> 2) & 1);
          const uint64_t da = mkdesc(sb + s * QSTG + wg * 16384, 16, 1024, 1), db = mkdesc(sb + s * QSTG + 32768, 8192, 1024, 1);
          wg_fence();
#pragma unroll
          for (int k = 0; k < 4; k++)
#pragma unroll
            for (int m = 0; m < 2; m++) wgmma_m64n192k16_ss_tb(acc[m], da + m * 512 + k * 2, db + k * 128, 1);
          wg_commit();
          wg_wait<1>();
          if (early && kt < 5) {
#pragma unroll 1
            for (int i = kt == 3 ? 0 : 3; i < kt; i++) { mbar_wait(sb + B_QF + 8 * i, 0); if (w == 0) e_arrive_both(sb + B_QE + 8 * i); }
          } else if (kt > 0 && w == 0) e_arrive_both(sb + B_QE + 8 * ((kt - 1) & 3));
          if (kt == KC) {
#pragma unroll 1
            for (uint32_t n = 0; n < 4000000u; n++) {
              uint32_t v;
              asm volatile("ld.acquire.cta.shared.u32 %0, [%1];" : "=r"(v) : "r"(sb + W_X) : "memory");
              if ((v >> 8) == (uint32_t)(l * 256 + 3)) break;
            }
            const int lane = lane_id();
            float nm[4];
#pragma unroll
            for (int i = 0; i < 4; i++) nm[i] = bf_lo(*(volatile unsigned short*)(smem + MEAN + (wg * 128 + w * 16 + (lane >> 2) + (i >> 1) * 64 + (i & 1) * 8) * 2));
            wg_wait<0>();
            fence_regs(acc[0]); fence_regs(acc[1]);
#pragma unroll
            for (int j = 0; j < 12; j++) {
              const float4 c = lds128f(sb + COLS + j * 64 + (lane & 3) * 16);
#pragma unroll
              for (int m = 0; m < 2; m++) {
                float* a = &acc[m][8 * j];
                a[0] = fmaf(nm[2 * m], c.y, a[0]); a[1] = fmaf(nm[2 * m], c.x, a[1]); a[2] = fmaf(nm[2 * m + 1], c.y, a[2]); a[3] = fmaf(nm[2 * m + 1], c.x, a[3]);
                a[4] = fmaf(nm[2 * m], c.w, a[4]); a[5] = fmaf(nm[2 * m], c.z, a[5]); a[6] = fmaf(nm[2 * m + 1], c.w, a[6]); a[7] = fmaf(nm[2 * m + 1], c.z, a[7]);
              }
            }
            fence_regs(acc[0]); fence_regs(acc[1]);
          }
        }
        auto part = [&](int s, int m, int k0, int k1) {
          const uint64_t da = mkdesc(sb + s * QSTG + wg * 16384 + m * 8192, 16, 1024, 1), db = mkdesc(sb + s * QSTG + 32768, 8192, 1024, 1);
          pin(zero);
          wg_fence();
#pragma unroll
          for (int k = k0; k < k1; k++) wgmma_m64n192k16_ss_tb(acc[m], da + k * 2, db + k * 128, 1);
          wg_commit();
          pin(zero);
        };
        mbar_wait(sb + B_QF + 16, 1);
        part(2, 1, 0, 4);
        wg_wait<1>();
        if (w == 0) e_arrive_both(sb + B_QE + 8);
        if (!(l & 1)) bar_arrive(NB_ST, 288);
        mbar_wait(sb + B_QF + 24, 1);
        part(3, 1, 0, 4);
        part(2, 0, 0, G1);
        IDS();
        const int g = lane >> 2, qd = lane & 3;
        float rs[2][2];
#pragma unroll
        for (int i = 0; i < 4; i++) rs[i >> 1][i & 1] = lds32f(sb + RSTD + (wg * 128 + w * 16 + g + (i >> 1) * 64 + (i & 1) * 8) * 4);
        auto scale = [&](int gi, int m, float sc) {
          const float r0 = rs[m][0] * sc, r1 = rs[m][1] * sc;
#pragma unroll
          for (int i = 0; i < 16; i++) acc[m][16 * gi + i] *= (i & 2) ? r1 : r0;
        };
        auto pack_b = [&](int gi, int m, uint32_t (&t)[8]) {
#pragma unroll
          for (int i = 0; i < 8; i++) t[i] = pack2(acc[m][16 * gi + 2 * i], acc[m][16 * gi + 2 * i + 1]);
        };
        auto norm_tile = [&](int gi, int m, uint32_t (&t)[8]) { scale(gi, m, 1.f); pack_b(gi, m, t); };
        auto pack_h = [&](int gi, int m, uint32_t (&t)[8]) {
#pragma unroll
          for (int i = 0; i < 8; i++) t[i] = pack2h(acc[m][16 * gi + 2 * i], acc[m][16 * gi + 2 * i + 1]);
        };
        uint32_t q[2][2][8], qn[2][2];
        const uint32_t srow = (lane & 7) + ((lane >> 3) & 1) * 8;
        const uint32_t row0 = wg * 128 + w * 16;
        auto put_kv = [&](int h, int v, int m, const uint32_t (&t)[8]) {
          const uint32_t base = sb + ((l & 1) ? (h ? 0 : T0) + v * 16384 : (2 * h + v) * ASC + 1024) + (row0 + m * 64) * 64;
          if (!v) {
#pragma unroll
            for (int jj = 0; jj < 2; jj++) stsm4(base + srow * 64 + (((2 * jj + (lane >> 4)) ^ ((srow >> 1) & 3)) << 4), t[4 * jj], t[4 * jj + 1], t[4 * jj + 2], t[4 * jj + 3]);
          } else {
            const uint32_t ad = base + g * 64 + ((qd ^ (g >> 1)) << 4);
            sts128(ad, t[0], t[2], t[4], t[6]); sts128(ad + 512, t[1], t[3], t[5], t[7]);
          }
        };
        auto send_halo = [&](int h, int v, const uint32_t (&t)[8]) {
          unsigned long long* hp = g_halo + ((size_t)(l >> 1) * 128 + b) * 1024 + h * 512 + v * 256 + lane;
#pragma unroll
          for (int i = 0; i < 8; i++) st_tagged(hp + i * 32, t[i], ep1);
        };
        auto put_kn = [&](int h, int m, uint32_t kn) {
          if (lane == 0) g_kn[((l >> 1) * 128 + bn * 8 + bm) * 32 + 16 * h + 8 * m + wg * 4 + w] = __uint_as_float(kn);
        };
        auto conv_tile1 = [&](int h) {
          uint32_t t[8], tv[8], kn = NOT_F16;
          norm_tile(4 + h, 1, tv);
          put_kv(h, 1, 1, tv);
          scale(2 + h, 1, 1.f);
          if (h == 0) { if (G1 < 4) part(2, 0, G1, 4); if (G2) part(3, 0, 0, G2); } else if (G3 < 4) part(3, 0, G3, 4);
          if (l & 1) {
            float n[2] = {0.f, 0.f};
#pragma unroll
            for (int i = 0; i < 16; i++) n[(i >> 1) & 1] = fmaf(acc[1][32 + 16 * h + i], acc[1][32 + 16 * h + i], n[(i >> 1) & 1]);
            const float a = ((qd & 1) ? n[1] : n[0]) + __shfl_xor_sync(~0u, (qd & 1) ? n[0] : n[1], 1);
            scale(h, 1, QSCALE / 128.f);
            kn = f16_class(__reduce_max_sync(~0u, __float_as_uint(a + __shfl_xor_sync(~0u, a, 2))), K_LO);
            put_kn(h, 1, kn);
          } else scale(h, 1, 1.f);
          if (kn == NOT_F16) pack_b(2 + h, 1, t); else pack_h(2 + h, 1, t);
          put_kv(h, 0, 1, t);
          if (!(l & 1) && row0 == 176 && bm < 7) { send_halo(h, 0, t); send_halo(h, 1, tv); }
        };
        mbar_wait(sb + B_QE + 8, 1);
        wg_wait<1>();
        fence_regs(acc[1]);
        conv_tile1(0);
        if (G2 < G3) part(3, 0, G2, G3);
        if (l & 1) { fence_async_smem(); bar_arrive(NB_ST, 288); }
        conv_tile1(1);
        wg_wait<(G2 > 0) + (G2 < G3) + (G3 < 4)>();
        if (w == 0) e_arrive_both(sb + B_QE + 16);
        wg_wait<0>();
        fence_regs(acc[0]);
        if (w == 0) e_arrive_both(sb + B_QE + 24);
        bf16* const op0 = [&] { IDS(); return g_os + (size_t)(bm * 256 + row0 + (lane >> 2)) * 1024 + bn * 32 + (lane & 3) * 8; }();
        auto put_o = [&](int h, int m, const float (&o)[16], float i0, float i1) {
          bf16* op = op0 + m * 65536 + h * 512;
          const uint4 a = make_uint4(pack2(o[0] * i0, o[1] * i0), pack2(o[4] * i0, o[5] * i0), pack2(o[8] * i0, o[9] * i0), pack2(o[12] * i0, o[13] * i0));
          const uint4 c = make_uint4(pack2(o[2] * i1, o[3] * i1), pack2(o[6] * i1, o[7] * i1), pack2(o[10] * i1, o[11] * i1), pack2(o[14] * i1, o[15] * i1));
          *(uint4*)op = a; *(uint4*)(op + 8 * 1024) = c;
          const uint32_t hi = __vimax3_u16x2(__vimax3_u16x2(a.x, a.y, a.z), __vimax3_u16x2(a.w, c.x, c.y), __vmaxu2(c.z, c.w));
          const uint32_t lo = __vimax3_s16x2(__vimax3_s16x2(a.x, a.y, a.z), __vimax3_s16x2(a.w, c.x, c.y), __vmaxs2(c.z, c.w));
          return __vmaxu2(hi & 0x7FFF7FFFu, lo & 0x7FFF7FFFu);
        };
        if (!(l & 1)) {
          auto conv_kv = [&](int h) {
            uint32_t t[8];
            norm_tile(2 + h, 0, t); put_kv(h, 0, 0, t);
            norm_tile(4 + h, 0, t); put_kv(h, 1, 0, t);
          };
          conv_kv(0);
          if (!PERHEAD) conv_kv(1);
          norm_tile(0, 0, q[0][0]); pack_b(0, 1, q[0][1]);
          bar_sync(NB_SC, 256);
          const bool e = g & 1, sel = 2 * qd + (g & 1) >= g + 2, first = bm == 0 && row0 == 0;
#pragma unroll 1
          for (int h = 0; h < 2; h++) {
            if (row0 == 0) bar_sync(NB_HALO + h, 64);
            float s[2][4][4];
            uint32_t vf[2][4][4], pf[2][2][4];
#pragma unroll
            for (int m = 0; m < 2; m++)
#pragma unroll
              for (int nt = 0; nt < 4; nt++) {
                uint32_t kf[4];
                const uint32_t r = row0 + m * 64 + 8 * nt + (lane & 7);
                ldsm4(sb + 2 * h * ASC + r * 64 + (((lane >> 3) ^ ((r >> 1) & 3)) << 4), kf);
                s[m][nt][0] = s[m][nt][1] = s[m][nt][2] = s[m][nt][3] = 0.f;
                mma16816(s[m][nt], q[0][m][0], q[0][m][1], q[0][m][2], q[0][m][3], kf[0], kf[1]);
                mma16816(s[m][nt], q[0][m][4], q[0][m][5], q[0][m][6], q[0][m][7], kf[2], kf[3]);
              }
#pragma unroll
            for (int m = 0; m < 2; m++)
#pragma unroll
              for (int i = 0; i < 4; i++) {
                const uint32_t r = row0 + m * 64 + 16 * (i >> 1) + srow, ch = 2 * (i & 1) + (lane >> 4);
                ldsm4t(sb + (2 * h + 1) * ASC + r * 64 + ((ch ^ ((r >> 1) & 3)) << 4), vf[m][i]);
              }
            float va[4], vb[4], mx[4];
#pragma unroll
            for (int i = 0; i < 4; i++) {
              const int m = i >> 1, hh = i & 1;
              const float a = e ? s[m][hh + 1][2 * hh + 1] : s[m][hh + 1][2 * hh];
              const float lo = e ? s[m][hh][2 * hh + 1] : s[m][hh][2 * hh], hi = e ? s[m][hh + 2][2 * hh + 1] : s[m][hh + 2][2 * hh];
              const uint32_t t = pack2(a, sel ? lo : hi);
              const uint32_t u = pack2(bf_lo(t) * 0.17677669529663687f, bf_hi(t) * 0.17677669529663687f);
              va[i] = (m == 0 && hh == 0 && first) ? -INFINITY : bf_lo(u);
              vb[i] = (m == 0 && first && sel) ? -INFINITY : bf_hi(u);
              mx[i] = fmaxf(va[i], vb[i]);
            }
#pragma unroll
            for (int i = 0; i < 4; i++) mx[i] = fmaxf(mx[i], __shfl_xor_sync(~0u, mx[i], 1));
#pragma unroll
            for (int i = 0; i < 4; i++) mx[i] = fmaxf(mx[i], __shfl_xor_sync(~0u, mx[i], 2));
#pragma unroll
            for (int i = 0; i < 4; i++) {
              va[i] = ex2((va[i] - mx[i]) * 1.4426950408889634f); vb[i] = ex2((vb[i] - mx[i]) * 1.4426950408889634f);
              mx[i] = va[i] + vb[i];
            }
#pragma unroll
            for (int i = 0; i < 4; i++) mx[i] += __shfl_xor_sync(~0u, mx[i], 1);
#pragma unroll
            for (int i = 0; i < 4; i++) mx[i] += __shfl_xor_sync(~0u, mx[i], 2);
#pragma unroll
            for (int i = 0; i < 4; i++) {
              const int m = i >> 1, hh = i & 1;
              const float inv = rcp(mx[i]);
              const uint32_t t = pack2(va[i] * inv, vb[i] * inv);
              const uint32_t pa = e ? t << 16 : t & 0xFFFFu, pb = e ? t & 0xFFFF0000u : t >> 16;
              pf[m][hh][hh + 1] = pa; pf[m][hh][hh] = sel ? pb : 0u; pf[m][hh][hh + 2] = sel ? 0u : pb; pf[m][hh][3 - 3 * hh] = 0u;
            }
#pragma unroll
            for (int m = 0; m < 2; m++) {
              float o[4][4];
#pragma unroll
              for (int j = 0; j < 4; j++) o[j][0] = o[j][1] = o[j][2] = o[j][3] = 0.f;
#pragma unroll
              for (int i = 0; i < 4; i++) {
                const int kk = i >> 1, jj = 2 * (i & 1);
                mma16816(o[jj], pf[m][0][2 * kk], pf[m][1][2 * kk], pf[m][0][2 * kk + 1], pf[m][1][2 * kk + 1], vf[m][i][0], vf[m][i][1]);
                mma16816(o[jj + 1], pf[m][0][2 * kk], pf[m][1][2 * kk], pf[m][0][2 * kk + 1], pf[m][1][2 * kk + 1], vf[m][i][2], vf[m][i][3]);
              }
              const float of[16] = {o[0][0], o[0][1], o[0][2], o[0][3], o[1][0], o[1][1], o[1][2], o[1][3], o[2][0], o[2][1], o[2][2], o[2][3], o[3][0], o[3][1], o[3][2], o[3][3]};
              put_o(h, m, of, 1.f, 1.f);
            }
            bar_arrive(NB_SIG + 2 * h + wg, 160);
            if (h == 0) {
              if (PERHEAD) conv_kv(1);
              norm_tile(1, 0, q[0][0]); pack_b(1, 1, q[0][1]);
              if (PERHEAD) bar_sync(NB_SC, 256);
            }
          }
        } else {
          auto conv_h = [&](int gi, int m, uint32_t (&t)[8]) {
            pack_h(gi, m, t);
            float d0[4] = {0.f, 0.f, 0.f, 0.f}, d1[4] = {0.f, 0.f, 0.f, 0.f};
            mma16816h(d0, t[0], t[1], t[2], t[3], t[0], t[2]); mma16816h(d1, t[0], t[1], t[2], t[3], t[1], t[3]);
            mma16816h(d0, t[4], t[5], t[6], t[7], t[4], t[6]); mma16816h(d1, t[4], t[5], t[6], t[7], t[5], t[7]);
            return (uint32_t)__reduce_max_sync(~0u, max(max(__float_as_int(d0[0]), __float_as_int(d0[1])), max(__float_as_int(d1[2]), __float_as_int(d1[3]))));
          };
#pragma unroll
          for (int h = 0; h < 2; h++) {
            uint32_t t[8], tv[8];
            scale(2 + h, 0, 1.f);
            const uint32_t kn = f16_class(conv_h(2 + h, 0, t), K_LO);
            if (h) {
#pragma unroll
              for (int i = 0; i < 2; i++) {
                scale(i, 0, QSCALE);
                qn[i][0] = f16_class(conv_h(i, 0, q[i][0]), K_LO);
                qn[i][1] = f16_class(conv_h(i, 1, q[i][1]), K_LO);
              }
            }
            norm_tile(4 + h, 0, tv);
            put_kv(h, 1, 0, tv);
            put_kn(h, 0, kn);
            if (kn == NOT_F16) pack_b(2 + h, 0, t);
            put_kv(h, 0, 0, t);
            fence_async_smem();
            bar_arrive(NB_KV + 12 * h, 288);
            if (h == 0) mbar_wait(sb + B_QF + 24, 1);
          }
          if (max(max(qn[0][0], qn[0][1]), max(qn[1][0], qn[1][1])) == NOT_F16) {
#pragma unroll
            for (int i = 0; i < 4; i++) if (qn[i >> 1][i & 1] == NOT_F16) pack_b(i >> 1, i & 1, q[i >> 1][i & 1]);
          }
          const bool elected = w == 0 && lane == 0;
          const uint64_t kd0 = mkdesc(sb + T0, 16, 512, 2);
          const uint64_t vd0 = mkdesc(sb + T0 + 16384, ONES - (T0 + 16384), 512, 2);
          constexpr uint64_t VSTEP = 64 - (64ull << 16);
          constexpr int RPC = NQ / 16, NC = 256 / NQ;
          float o[2][20], SA[2][NQ / 2];
          uint32_t SB[2][NQ / 4], PA[LA][4], PB[LB][4];
#pragma unroll
          for (int m = 0; m < 2; m++) {
#pragma unroll
            for (int i = 0; i < NQ / 2; i++) SA[m][i] = 0.f;
#pragma unroll
            for (int i = 0; i < NQ / 4; i++) SB[m][i] = 0u;
            fence_regs(SA[m]); fence_regs(SB[m]);
          }
          auto qka = [&](int b, int k, uint64_t d, int h = 0) { QK_A(SA[b], q[h][0][4 * k], q[h][0][4 * k + 1], q[h][0][4 * k + 2], q[h][0][4 * k + 3], d + 2 * k, k ? 1 : zero); };
          auto qkb = [&](int b, int k, uint64_t d, int h = 0) { QK_B(SB[b], q[h][1][4 * k], q[h][1][4 * k + 1], q[h][1][4 * k + 2], q[h][1][4 * k + 3], d + 2 * k, k ? 1 : zero); };
          auto pv = [&](int m, const uint32_t (&Px)[4], uint64_t vd) { wgmma_m64n40k16_rs_tb(o[m], Px[0], Px[1], Px[2], Px[3], vd, 1); };
          auto clear = [&]() {
#pragma unroll
            for (int i = 0; i < 20; i++) o[0][i] = o[1][i] = 0.f;
            fence_regs(o[0]); fence_regs(o[1]);
#pragma unroll
            for (int i = 0; i < 4; i++) PA[0][i] = PB[0][i] = PA[LA - 1][i] = PB[LB - 1][i] = zero;
          };
          mbar_wait(sb + B_TF, 0);
          wg_fence(); qka(0, 0, kd0); qkb(0, 0, kd0); qka(0, 1, kd0); qkb(0, 1, kd0); wg_commit();
          clear();
          wg_wait<0>(); fence_regs(SA[0]); fence_regs(SB[0]);
#pragma unroll 1
          for (int pass = 0; pass < 2; pass++) {
#pragma unroll 1
            for (int j = 0; j < 8; j++) {
              const uint32_t s = j & 3, sn = j < 7 ? (j + 1) & 3 : s, sp = j > 0 ? (j + 3) & 3 : s;
              const uint64_t kd = kd0 + s * 2048, vd = vd0 + s * (32 * VSTEP), kdn = kd0 + sn * 2048, vdp = vd0 + sp * (32 * VSTEP) + 16 * VSTEP;
              bool landed = false;
#pragma unroll
              for (int r = 0; r < 16; r++) {
                const int c = r / RPC, ro = r % RPC, cn = c + 1;
                if (r == 16 - RPC && !landed) mbar_wait(sb + B_TF + 8 * sn, ((j + 1) >> 2) & 1);
                wg_fence();
                const uint64_t kx = cn < NC ? kd + cn * NQ * 4 : kdn, va = (r >= LA ? vd : vdp) + (r - LA) * VSTEP, vb = (r >= LB ? vd : vdp) + (r - LB) * VSTEP;
                if (LAG & 4) { pv(0, PA[r % LA], va); pv(1, PB[r % LB], vb); }
#pragma unroll
                for (int k = 0; k < 2; k++) {
                  if (ro == ((OA >> (4 * k)) & 15)) qka(cn & 1, k, kx);
                  if (ro == ((OB >> (4 * k)) & 15)) qkb(cn & 1, k, kx);
                }
                if (!(LAG & 4)) {
                  if (ro == RPC - 1 || (LAG & 1)) wg_commit();
                  if (LAG & 8) { pv(1, PB[r % LB], vb); pv(0, PA[r % LA], va); } else { pv(0, PA[r % LA], va); pv(1, PB[r % LB], vb); }
                }
                wg_commit();
                if (r == 14 - RPC) landed = mbar_test(sb + B_TF + 8 * sn, ((j + 1) >> 2) & 1) || j == 7;
#pragma unroll
                for (int i = 0; i < 4; i++) {
                  if (LAG & 16) PB[r % LB][i] = exp2_h2(SB[c & 1][4 * ro + i]);
                  PA[r % LA][i] = pack2(ex2(SA[c & 1][8 * ro + 2 * i]), ex2(SA[c & 1][8 * ro + 2 * i + 1]));
                  if (!(LAG & 16)) PB[r % LB][i] = exp2_h2(SB[c & 1][4 * ro + i]);
                }
                if (r == 15 || ((LAG & 4) && ro == RPC - 1 && ((OA >> 4) == ro || (OB >> 4) == ro))) wg_wait<0>(); else if (ro == RPC - 1 || !(LAG & 2)) wg_wait<1>();
                if (ro == RPC - 1) { fence_regs(SA[cn & 1]); fence_regs(SB[cn & 1]); }
                if (r == (LA + LB > 2 ? 4 : RPC) && elected && j > 0) mbar_arrive(sb + B_TE + 8 * sp);
              }
            }
            int badm = 0;
            if (pass == 0) mbar_wait(sb + B_TF, 0);
            wg_fence();
            if (LA == 2) pv(0, PA[0], vd0 + 110 * VSTEP);
            if (LB == 2) pv(1, PB[0], vd0 + 110 * VSTEP);
            pv(0, PA[LA - 1], vd0 + 111 * VSTEP); pv(1, PB[LB - 1], vd0 + 111 * VSTEP); wg_commit();
            qka(0, 0, kd0, 1); qkb(0, 0, kd0, 1); qka(0, 1, kd0, 1); qkb(0, 1, kd0, 1); wg_commit();
            if (pass == 0) bar_sync(NB_KN + wg, 160);
            const float kmax = *(volatile float*)(smem + KMAX + 4 * pass);
            wg_wait<1>(); fence_regs(o[0]); fence_regs(o[1]);
            if (w == 0) e_arrive(sb + B_TE + 8 * 3);
#pragma unroll
            for (int m = 0; m < 2; m++) {
              const float of[16] = {o[m][0], o[m][1], o[m][2], o[m][3], o[m][4], o[m][5], o[m][6], o[m][7], o[m][8], o[m][9], o[m][10], o[m][11], o[m][12], o[m][13], o[m][14], o[m][15]};
              const uint32_t chk = put_o(pass, m, of, rcp(o[m][16]), rcp(o[m][18]));
              const bool bad = !(__uint_as_float(qn[0][m]) * kmax <= (m ? 0.875f * 0.875f : 112.f * 112.f)) || !(fminf(o[m][16], o[m][18]) >= 9.3e-10f) ||
                               !(o[m][16] + o[m][18] <= 3e38f) || ((chk + 0x00800080u) & 0x80008000u);
              badm |= __any_sync(~0u, bad) << m;
            }
            wg_wait<0>(); fence_regs(SA[0]); fence_regs(SB[0]);
            if (badm) {
#pragma unroll 1
              for (int m = 0; m < 2; m++) if ((badm >> m) & 1) {
                uint32_t qq[8]; float res[20];
#pragma unroll
                for (int i = 0; i < 8; i++) { qq[i] = m ? q[0][1][i] : q[0][0][i]; if ((m ? qn[0][1] : qn[0][0]) != NOT_F16) qq[i] = h2_to_bf2(qq[i]); }
                attn_slow(qq, m ? 128.f : 1.f, 2 * (cta_id() & 15) + pass, g_kn + ((l >> 1) * 128 + (cta_id() & 15) * 8) * 32 + 16 * pass, res, lane_id());
                const float of[16] = {res[0], res[1], res[2], res[3], res[4], res[5], res[6], res[7], res[8], res[9], res[10], res[11], res[12], res[13], res[14], res[15]};
                put_o(pass, m, of, rcp(res[16]), rcp(res[18]));
              }
            }
            bar_arrive(NB_SIG + 2 * pass + wg, 160);
            qn[0][0] = qn[1][0]; qn[0][1] = qn[1][1];
#pragma unroll
            for (int m = 0; m < 2; m++)
#pragma unroll
              for (int i = 0; i < 8; i++) q[0][m][i] = q[1][m][i];
            clear();
          }
        }
      }
      {
        float acc[64];
#pragma unroll
        for (int i = 0; i < 64; i++) acc[i] = 0.f;
        fence_regs(acc);
        uint32_t s = 0, lap = 0;
#pragma unroll 1
        for (int kt = 0; kt < 16; kt++) {
          mbar_wait(sb + B_PF + 8 * s, ((s < 4 ? l : 0) + lap) & 1);
          const uint64_t da = mkdesc(sb + pslot_a(s, l) + wg * 8192, 16, 1024, 1), db = mkdesc(sb + pslot_b(s, l), 8192, 1024, 1);
          wg_fence();
#pragma unroll
          for (int k = 0; k < 4; k++) wgmma_m64n128k16_ss_tb(acc, da + k * 2, db + k * 128, 1);
          wg_commit();
          wg_wait<1>();
          if (kt > 0 && w == 0) e_arrive_both(sb + B_PE + 8 * (s ? s - 1 : 5));
          if (++s == 6) { s = 0; lap++; }
        }
        IDS();
        const int g = lane >> 2, qd = lane & 3;
        const int r0 = wg * 64 + w * 16;
        const uint32_t r = r0 + (lane & 7) + ((lane >> 3) & 1) * 8;
        uint32_t x[8][4];
        mbar_wait(sb + B_RF, l & 1);
#pragma unroll
        for (int jj = 0; jj < 8; jj++) ldsm4(sb + ((l & 1) ? RES : 0) + (jj >> 2) * 16384 + r * 128 + ((((2 * jj + (lane >> 4)) & 7) ^ (r & 7)) << 4), x[jj]);
        wg_wait<0>();
        fence_regs(acc);
        bar_sync(NB_SC, 256);
        if (w == 0) e_arrive_both(sb + B_PE + 8 * 3);
        const CUtensorMap* mo = &prm.m[l == 3 ? M_OUT : M_XST];
#pragma unroll
        for (int jj = 0; jj < 8; jj++) {
#pragma unroll
          for (int i = 0; i < 4; i++) x[jj][i] = add_bf16x2(x[jj][i], pack2(acc[8 * jj + 2 * i], acc[8 * jj + 2 * i + 1]));
          stsm4(sb + (jj >> 2) * QSTG + po * 16384 + r * 128 + ((((2 * jj + (lane >> 4)) & 7) ^ (r & 7)) << 4), x[jj][0], x[jj][1], x[jj][2], x[jj][3]);
          if ((jj & 3) == 3) { fence_async_smem(); __syncwarp(); tma_st(mo, pn * 128 + (jj >> 2) * 64, pm * 128 + r0, sb + (jj >> 2) * QSTG + po * 16384 + r0 * 128); }
        }
        bulk_commit();
        if (l < 3) {
          bar_arrive(NB_X, 288);
          float s1[4] = {0.f, 0.f, 0.f, 0.f}, s2[4][4];
#pragma unroll
          for (int i = 0; i < 16; i++) s2[i >> 2][i & 3] = 0.f;
#pragma unroll
          for (int jj = 0; jj < 8; jj++) {
            mma16816(s1, x[jj][0], x[jj][1], x[jj][2], x[jj][3], 0x3f803f80u, 0x3f803f80u);
#pragma unroll
            for (int i = 0; i < 4; i++) mma1688(s2[i], x[jj][i & 2], x[jj][i | 1], x[jj][i]);
          }
          if (qd == (g >> 1)) {
            float2* sp = g_stats + pn * 2048 + pm * 128 + r0 + g;
            sp[0] = make_float2(s1[0], (g & 1) ? s2[0][1] + s2[2][1] : s2[0][0] + s2[2][0]);
            sp[8] = make_float2(s1[2], (g & 1) ? s2[1][3] + s2[3][3] : s2[1][2] + s2[3][2]);
          }
        }
        bulk_wait_n<0>();
        if (l < 3) bar_arrive(NB_X0, 320 + 32 * XLATE);
      }
    }
  }
  asm volatile("barrier.cluster.arrive.relaxed.aligned;\nbarrier.cluster.wait.aligned;" ::: "memory");
}

typedef CUresult (*EncodeFn)(CUtensorMap*, CUtensorMapDataType, cuuint32_t, void*, const cuuint64_t*, const cuuint64_t*, const cuuint32_t*,
                             const cuuint32_t*, CUtensorMapInterleave, CUtensorMapSwizzle, CUtensorMapL2promotion, CUtensorMapFloatOOBfill);

static void make_map(EncodeFn fn, CUtensorMap* m, const void* ptr, int rank, const uint64_t* dims, const uint64_t* strides, const uint32_t* box, CUtensorMapSwizzle sw) {
  cuuint64_t d[5], st[4];
  cuuint32_t bx[5], es[5];
  for (int i = 0; i < rank; i++) { d[i] = dims[i]; bx[i] = box[i]; es[i] = 1; if (i) st[i - 1] = strides[i - 1] * 2; }
  fn(m, CU_TENSOR_MAP_DATA_TYPE_BFLOAT16, rank, (void*)ptr, d, st, bx, es, CU_TENSOR_MAP_INTERLEAVE_NONE, sw,
     CU_TENSOR_MAP_L2_PROMOTION_L2_128B, CU_TENSOR_MAP_FLOAT_OOB_FILL_NONE);
}
static void map2(EncodeFn fn, CUtensorMap* m, const void* ptr, uint64_t inner, uint64_t outer, uint32_t bi, uint32_t bo, CUtensorMapSwizzle sw) {
  const uint64_t d[2] = {inner, outer}, st[1] = {inner};
  const uint32_t bx[2] = {bi, bo};
  make_map(fn, m, ptr, 2, d, st, bx, sw);
}

extern "C" void kernel_launch(void* const* d_in, const int* in_sizes, int n_in, void* d_out, int out_size) {
  (void)in_sizes; (void)n_in; (void)out_size;
  static EncodeFn enc = nullptr;
  static void *xs, *os, *kk, *vv, *ep;
  if (!enc) {
    void* p = nullptr;
    cudaDriverEntryPointQueryResult qr;
    cudaGetDriverEntryPoint("cuTensorMapEncodeTiled", &p, cudaEnableDefault, &qr);
    enc = (EncodeFn)p;
    cudaGetSymbolAddress(&xs, g_xs); cudaGetSymbolAddress(&os, g_os); cudaGetSymbolAddress(&kk, g_k); cudaGetSymbolAddress(&vv, g_v); cudaGetSymbolAddress(&ep, g_epoch);
    cudaFuncSetAttribute(fused_kernel, cudaFuncAttributeMaxDynamicSharedMemorySize, SMEM_BYTES);
  }
  Params prm;
  const CUtensorMapSwizzle S128 = CU_TENSOR_MAP_SWIZZLE_128B, S64 = CU_TENSOR_MAP_SWIZZLE_64B;
  map2(enc, &prm.m[M_X0A], d_in[0], 1024, 2048, 64, 256, S128);
  map2(enc, &prm.m[M_XSA], xs, 1024, 2048, 64, 256, S128);
  for (int t = 0; t < 2; t++) {
    const uint64_t d3[3] = {1024, 1024, 3}, s3[2] = {3072, 1024};
    const uint32_t b3[3] = {64, 64, 3};
    make_map(enc, &prm.m[M_WQA + t], d_in[1 + 3 * t], 3, d3, s3, b3, S128);
    const uint64_t d5[5] = {64, 32, 2, 16, 16}, s5[4] = {1024, 32 * 1024, 64 * 1024, 64};
    const uint32_t b5[5] = {64, 32, 1, 2, 2};
    make_map(enc, &prm.m[M_WOA + t], d_in[2 + 3 * t], 5, d5, s5, b5, S128);
    const uint64_t dr[3] = {64, 2048, 16}, sr[2] = {1024, 64};
    const uint32_t br[3] = {64, 128, 2};
    make_map(enc, &prm.m[M_X0R + t], t ? xs : d_in[0], 3, dr, sr, br, S128);
  }
  map2(enc, &prm.m[M_OS], os, 1024, 2048, 64, 64, S128);
  map2(enc, &prm.m[M_K], kk, 32, 65536, 32, 256, S64);
  map2(enc, &prm.m[M_V], vv, 32, 65536, 32, 256, S64);
  map2(enc, &prm.m[M_K4], kk, 32, 65536, 32, 64, S64);
  map2(enc, &prm.m[M_V4], vv, 32, 65536, 32, 64, S64);
  map2(enc, &prm.m[M_XSO], xs, 1024, 2048, 64, 128, S128);
  map2(enc, &prm.m[M_X0H], d_in[0], 1024, 2048, 64, 128, S128);
  map2(enc, &prm.m[M_XST], xs, 1024, 2048, 64, 16, S128);
  map2(enc, &prm.m[M_OUT], d_out, 1024, 2048, 64, 16, S128);
  prm.x0 = (const bf16*)d_in[0];
  prm.wq[0] = (const bf16*)d_in[1]; prm.wq[1] = (const bf16*)d_in[4];
  prm.wo[0] = (const bf16*)d_in[2]; prm.wo[1] = (const bf16*)d_in[5];
  prm.epoch = (uint32_t*)ep;
  prm.zero = 0;
  for (int i = 0; i < 128; i++) prm.map[i] = remap(i);
  fused_kernel<<<128, 384, SMEM_BYTES>>>(prm);
}
```

```cpp
#include <cuda_runtime.h>
#include <cuda_bf16.h>
#include <cuda.h>
#include <stdint.h>

typedef __nv_bfloat16 bf16;

__device__ __forceinline__ void wgmma_m64n192k16_ss_tb(float (&d)[96], uint64_t da, uint64_t db, int scale_d) {
  asm volatile("{\n.reg .pred p;\nsetp.ne.b32 p, %98, 0;\n"
    "wgmma.mma_async.sync.aligned.m64n192k16.f32.bf16.bf16 "
    "{%0, %1, %2, %3, %4, %5, %6, %7, %8, %9, %10, %11, %12, %13, %14, %15, "
    "%16, %17, %18, %19, %20, %21, %22, %23, %24, %25, %26, %27, %28, %29, %30, %31, "
    "%32, %33, %34, %35, %36, %37, %38, %39, %40, %41, %42, %43, %44, %45, %46, %47, "
    "%48, %49, %50, %51, %52, %53, %54, %55, %56, %57, %58, %59, %60, %61, %62, %63, "
    "%64, %65, %66, %67, %68, %69, %70, %71, %72, %73, %74, %75, %76, %77, %78, %79, "
    "%80, %81, %82, %83, %84, %85, %86, %87, %88, %89, %90, %91, %92, %93, %94, %95}, "
    "%96, %97, p, 1, 1, 0, 1;\n}\n"
    : "+f"(d[0]), "+f"(d[1]), "+f"(d[2]), "+f"(d[3]), "+f"(d[4]), "+f"(d[5]), "+f"(d[6]), "+f"(d[7]),
      "+f"(d[8]), "+f"(d[9]), "+f"(d[10]), "+f"(d[11]), "+f"(d[12]), "+f"(d[13]), "+f"(d[14]), "+f"(d[15]),
      "+f"(d[16]), "+f"(d[17]), "+f"(d[18]), "+f"(d[19]), "+f"(d[20]), "+f"(d[21]), "+f"(d[22]), "+f"(d[23]),
      "+f"(d[24]), "+f"(d[25]), "+f"(d[26]), "+f"(d[27]), "+f"(d[28]), "+f"(d[29]), "+f"(d[30]), "+f"(d[31]),
      "+f"(d[32]), "+f"(d[33]), "+f"(d[34]), "+f"(d[35]), "+f"(d[36]), "+f"(d[37]), "+f"(d[38]), "+f"(d[39]),
      "+f"(d[40]), "+f"(d[41]), "+f"(d[42]), "+f"(d[43]), "+f"(d[44]), "+f"(d[45]), "+f"(d[46]), "+f"(d[47]),
      "+f"(d[48]), "+f"(d[49]), "+f"(d[50]), "+f"(d[51]), "+f"(d[52]), "+f"(d[53]), "+f"(d[54]), "+f"(d[55]),
      "+f"(d[56]), "+f"(d[57]), "+f"(d[58]), "+f"(d[59]), "+f"(d[60]), "+f"(d[61]), "+f"(d[62]), "+f"(d[63]),
      "+f"(d[64]), "+f"(d[65]), "+f"(d[66]), "+f"(d[67]), "+f"(d[68]), "+f"(d[69]), "+f"(d[70]), "+f"(d[71]),
      "+f"(d[72]), "+f"(d[73]), "+f"(d[74]), "+f"(d[75]), "+f"(d[76]), "+f"(d[77]), "+f"(d[78]), "+f"(d[79]),
      "+f"(d[80]), "+f"(d[81]), "+f"(d[82]), "+f"(d[83]), "+f"(d[84]), "+f"(d[85]), "+f"(d[86]), "+f"(d[87]),
      "+f"(d[88]), "+f"(d[89]), "+f"(d[90]), "+f"(d[91]), "+f"(d[92]), "+f"(d[93]), "+f"(d[94]), "+f"(d[95])
    : "l"(da), "l"(db), "r"(scale_d));
}

__device__ __forceinline__ void wgmma_m64n128k16_ss_tb(float (&d)[64], uint64_t da, uint64_t db, int scale_d) {
  asm volatile("{\n.reg .pred p;\nsetp.ne.b32 p, %66, 0;\n"
    "wgmma.mma_async.sync.aligned.m64n128k16.f32.bf16.bf16 "
    "{%0, %1, %2, %3, %4, %5, %6, %7, %8, %9, %10, %11, %12, %13, %14, %15, "
    "%16, %17, %18, %19, %20, %21, %22, %23, %24, %25, %26, %27, %28, %29, %30, %31, "
    "%32, %33, %34, %35, %36, %37, %38, %39, %40, %41, %42, %43, %44, %45, %46, %47, "
    "%48, %49, %50, %51, %52, %53, %54, %55, %56, %57, %58, %59, %60, %61, %62, %63}, "
    "%64, %65, p, 1, 1, 0, 1;\n}\n"
    : "+f"(d[0]), "+f"(d[1]), "+f"(d[2]), "+f"(d[3]), "+f"(d[4]), "+f"(d[5]), "+f"(d[6]), "+f"(d[7]),
      "+f"(d[8]), "+f"(d[9]), "+f"(d[10]), "+f"(d[11]), "+f"(d[12]), "+f"(d[13]), "+f"(d[14]), "+f"(d[15]),
      "+f"(d[16]), "+f"(d[17]), "+f"(d[18]), "+f"(d[19]), "+f"(d[20]), "+f"(d[21]), "+f"(d[22]), "+f"(d[23]),
      "+f"(d[24]), "+f"(d[25]), "+f"(d[26]), "+f"(d[27]), "+f"(d[28]), "+f"(d[29]), "+f"(d[30]), "+f"(d[31]),
      "+f"(d[32]), "+f"(d[33]), "+f"(d[34]), "+f"(d[35]), "+f"(d[36]), "+f"(d[37]), "+f"(d[38]), "+f"(d[39]),
      "+f"(d[40]), "+f"(d[41]), "+f"(d[42]), "+f"(d[43]), "+f"(d[44]), "+f"(d[45]), "+f"(d[46]), "+f"(d[47]),
      "+f"(d[48]), "+f"(d[49]), "+f"(d[50]), "+f"(d[51]), "+f"(d[52]), "+f"(d[53]), "+f"(d[54]), "+f"(d[55]),
      "+f"(d[56]), "+f"(d[57]), "+f"(d[58]), "+f"(d[59]), "+f"(d[60]), "+f"(d[61]), "+f"(d[62]), "+f"(d[63])
    : "l"(da), "l"(db), "r"(scale_d));
}

__device__ __forceinline__ void wgmma_m64n32k16_rs_nb_h(float (&d)[16], uint32_t a0, uint32_t a1, uint32_t a2, uint32_t a3, uint64_t db, int scale_d) {
  asm volatile("{\n.reg .pred p;\nsetp.ne.b32 p, %21, 0;\n"
    "wgmma.mma_async.sync.aligned.m64n32k16.f32.f16.f16 "
    "{%0, %1, %2, %3, %4, %5, %6, %7, %8, %9, %10, %11, %12, %13, %14, %15}, "
    "{%16, %17, %18, %19}, %20, p, 1, 1, 0;\n}\n"
    : "+f"(d[0]), "+f"(d[1]), "+f"(d[2]), "+f"(d[3]), "+f"(d[4]), "+f"(d[5]), "+f"(d[6]), "+f"(d[7]),
      "+f"(d[8]), "+f"(d[9]), "+f"(d[10]), "+f"(d[11]), "+f"(d[12]), "+f"(d[13]), "+f"(d[14]), "+f"(d[15])
    : "r"(a0), "r"(a1), "r"(a2), "r"(a3), "l"(db), "r"(scale_d));
}

__device__ __forceinline__ void wgmma_m64n32k16_rs_nb_hh(uint32_t (&d)[8], uint32_t a0, uint32_t a1, uint32_t a2, uint32_t a3, uint64_t db, int scale_d) {
  asm volatile("{\n.reg .pred p;\nsetp.ne.b32 p, %13, 0;\n"
    "wgmma.mma_async.sync.aligned.m64n32k16.f16.f16.f16 "
    "{%0, %1, %2, %3, %4, %5, %6, %7}, "
    "{%8, %9, %10, %11}, %12, p, 1, 1, 0;\n}\n"
    : "+r"(d[0]), "+r"(d[1]), "+r"(d[2]), "+r"(d[3]), "+r"(d[4]), "+r"(d[5]), "+r"(d[6]), "+r"(d[7])
    : "r"(a0), "r"(a1), "r"(a2), "r"(a3), "l"(db), "r"(scale_d));
}

__device__ __forceinline__ void wgmma_m64n64k16_rs_nb_h(float (&d)[32], uint32_t a0, uint32_t a1, uint32_t a2, uint32_t a3, uint64_t db, int scale_d) {
  asm volatile("{\n.reg .pred p;\nsetp.ne.b32 p, %37, 0;\n"
    "wgmma.mma_async.sync.aligned.m64n64k16.f32.f16.f16 "
    "{%0, %1, %2, %3, %4, %5, %6, %7, %8, %9, %10, %11, %12, %13, %14, %15, "
    "%16, %17, %18, %19, %20, %21, %22, %23, %24, %25, %26, %27, %28, %29, %30, %31}, "
    "{%32, %33, %34, %35}, %36, p, 1, 1, 0;\n}\n"
    : "+f"(d[0]), "+f"(d[1]), "+f"(d[2]), "+f"(d[3]), "+f"(d[4]), "+f"(d[5]), "+f"(d[6]), "+f"(d[7]),
      "+f"(d[8]), "+f"(d[9]), "+f"(d[10]), "+f"(d[11]), "+f"(d[12]), "+f"(d[13]), "+f"(d[14]), "+f"(d[15]),
      "+f"(d[16]), "+f"(d[17]), "+f"(d[18]), "+f"(d[19]), "+f"(d[20]), "+f"(d[21]), "+f"(d[22]), "+f"(d[23]),
      "+f"(d[24]), "+f"(d[25]), "+f"(d[26]), "+f"(d[27]), "+f"(d[28]), "+f"(d[29]), "+f"(d[30]), "+f"(d[31])
    : "r"(a0), "r"(a1), "r"(a2), "r"(a3), "l"(db), "r"(scale_d));
}

__device__ __forceinline__ void wgmma_m64n64k16_rs_nb_hh(uint32_t (&d)[16], uint32_t a0, uint32_t a1, uint32_t a2, uint32_t a3, uint64_t db, int scale_d) {
  asm volatile("{\n.reg .pred p;\nsetp.ne.b32 p, %21, 0;\n"
    "wgmma.mma_async.sync.aligned.m64n64k16.f16.f16.f16 "
    "{%0, %1, %2, %3, %4, %5, %6, %7, %8, %9, %10, %11, %12, %13, %14, %15}, "
    "{%16, %17, %18, %19}, %20, p, 1, 1, 0;\n}\n"
    : "+r"(d[0]), "+r"(d[1]), "+r"(d[2]), "+r"(d[3]), "+r"(d[4]), "+r"(d[5]), "+r"(d[6]), "+r"(d[7]),
      "+r"(d[8]), "+r"(d[9]), "+r"(d[10]), "+r"(d[11]), "+r"(d[12]), "+r"(d[13]), "+r"(d[14]), "+r"(d[15])
    : "r"(a0), "r"(a1), "r"(a2), "r"(a3), "l"(db), "r"(scale_d));
}

__device__ __forceinline__ void wgmma_m64n40k16_rs_tb(float (&d)[20], uint32_t a0, uint32_t a1, uint32_t a2, uint32_t a3, uint64_t db, int scale_d) {
  asm volatile("{\n.reg .pred p;\nsetp.ne.b32 p, %25, 0;\n"
    "wgmma.mma_async.sync.aligned.m64n40k16.f32.bf16.bf16 "
    "{%0, %1, %2, %3, %4, %5, %6, %7, %8, %9, %10, %11, %12, %13, %14, %15, "
    "%16, %17, %18, %19}, "
    "{%20, %21, %22, %23}, %24, p, 1, 1, 1;\n}\n"
    : "+f"(d[0]), "+f"(d[1]), "+f"(d[2]), "+f"(d[3]), "+f"(d[4]), "+f"(d[5]), "+f"(d[6]), "+f"(d[7]),
      "+f"(d[8]), "+f"(d[9]), "+f"(d[10]), "+f"(d[11]), "+f"(d[12]), "+f"(d[13]), "+f"(d[14]), "+f"(d[15]),
      "+f"(d[16]), "+f"(d[17]), "+f"(d[18]), "+f"(d[19])
    : "r"(a0), "r"(a1), "r"(a2), "r"(a3), "l"(db), "r"(scale_d));
}

#define DEVINL __device__ __forceinline__
#define PSLEEP 0
#define XLATE 1
#define PLATE 1
#define HINT 4000
#define MWL mbar_wait_long
DEVINL void pin(uint32_t z) { asm volatile("{\n.reg .pred p;\nsetp.ne.u32 p, %0, 0;\nPIN:\n@p bra.uni PIN;\n}" ::"r"(z) : "memory"); }
DEVINL void wg_fence() { asm volatile("wgmma.fence.sync.aligned;" ::: "memory"); }
DEVINL void wg_commit() { asm volatile("wgmma.commit_group.sync.aligned;" ::: "memory"); }
template <int N> DEVINL void wg_wait() { asm volatile("wgmma.wait_group.sync.aligned %0;" ::"n"(N) : "memory"); }
DEVINL uint64_t mkdesc(uint32_t addr, uint32_t lbo, uint32_t sbo, int sw) {
  return (uint64_t)((addr & 0x3FFFF) >> 4) | ((uint64_t)(lbo >> 4) << 16) | ((uint64_t)(sbo >> 4) << 32) | ((uint64_t)sw << 62);
}
DEVINL void mbar_arrive(uint32_t bar) { asm volatile("mbarrier.arrive.shared::cta.b64 _, [%0];" ::"r"(bar) : "memory"); }
DEVINL bool mbar_try(uint32_t bar, uint32_t parity) {
  uint32_t ok;
  asm volatile("{\n.reg .pred p;\nmbarrier.try_wait.parity.shared::cta.b64 p, [%1], %2;\nselp.u32 %0, 1, 0, p;\n}" : "=r"(ok) : "r"(bar), "r"(parity) : "memory");
  return ok;
}
DEVINL bool mbar_test(uint32_t bar, uint32_t parity) {
  uint32_t ok;
  asm volatile("{\n.reg .pred p;\nmbarrier.test_wait.parity.shared::cta.b64 p, [%1], %2;\nselp.u32 %0, 1, 0, p;\n}" : "=r"(ok) : "r"(bar), "r"(parity) : "memory");
  return ok;
}
DEVINL void mbar_hint(uint32_t bar, uint32_t parity) {
#pragma unroll 1
  for (uint32_t n = 0; n < 16u; n++) if (mbar_try(bar, parity)) break;
}
DEVINL void mbar_wait(uint32_t bar, uint32_t parity) {
#pragma unroll 1
  for (uint32_t n = 0; n < 100000u; n++) if (mbar_try(bar, parity)) break;
}
DEVINL void mbar_wait_long(uint32_t bar, uint32_t parity) {
#pragma unroll 1
  for (uint32_t n = 0; n < 100000u; n++) {
    uint32_t ok;
    asm volatile("{\n.reg .pred p;\nmbarrier.try_wait.parity.shared::cta.b64 p, [%1], %2, %3;\nselp.u32 %0, 1, 0, p;\n}" : "=r"(ok) : "r"(bar), "r"(parity), "r"(HINT) : "memory");
    if (ok) break;
  }
}
#define EL(txt) "{\n.reg .pred pe;\nelect.sync _|pe, 0xffffffff;\n@pe " txt "\n}"
DEVINL void e_expect_tx(uint32_t bar, uint32_t bytes) { asm volatile(EL("mbarrier.arrive.expect_tx.shared::cta.b64 _, [%0], %1;") ::"r"(bar), "r"(bytes) : "memory"); }
DEVINL void e_init(uint32_t bar, uint32_t cnt) { asm volatile(EL("mbarrier.init.shared::cta.b64 [%0], %1;") ::"r"(bar), "r"(cnt) : "memory"); }
DEVINL void e_arrive(uint32_t bar) { asm volatile(EL("mbarrier.arrive.shared::cta.b64 _, [%0];") ::"r"(bar) : "memory"); }
DEVINL void e_red(uint32_t* p) { asm volatile(EL("red.release.gpu.global.add.u32 [%0], 1;") ::"l"(p) : "memory"); }
DEVINL void e_red_relaxed(uint32_t* p) { asm volatile(EL("red.relaxed.gpu.global.add.u32 [%0], 1;") ::"l"(p) : "memory"); }
DEVINL void tma_ld(uint32_t dst, const CUtensorMap* m, int c0, int c1, uint32_t bar) {
  asm volatile(EL("cp.async.bulk.tensor.2d.shared::cluster.global.mbarrier::complete_tx::bytes [%0], [%1, {%3, %4}], [%2];")
               ::"r"(dst), "l"(m), "r"(bar), "r"(c0), "r"(c1) : "memory");
}
DEVINL void tma_ld3(uint32_t dst, const CUtensorMap* m, int c0, int c1, int c2, uint32_t bar) {
  asm volatile(EL("cp.async.bulk.tensor.3d.shared::cluster.global.mbarrier::complete_tx::bytes [%0], [%1, {%3, %4, %5}], [%2];")
               ::"r"(dst), "l"(m), "r"(bar), "r"(c0), "r"(c1), "r"(c2) : "memory");
}
DEVINL void tma_ld5(uint32_t dst, const CUtensorMap* m, int c2, int c3, int c4, uint32_t bar) {
  asm volatile(EL("cp.async.bulk.tensor.5d.shared::cluster.global.mbarrier::complete_tx::bytes [%0], [%1, {0, 0, %3, %4, %5}], [%2];")
               ::"r"(dst), "l"(m), "r"(bar), "r"(c2), "r"(c3), "r"(c4) : "memory");
}
DEVINL void tma_ld_mc(uint32_t dst, const CUtensorMap* m, int c0, int c1, uint32_t bar) {
  asm volatile(EL("cp.async.bulk.tensor.2d.shared::cluster.global.mbarrier::complete_tx::bytes.multicast::cluster [%0], [%1, {%3, %4}], [%2], %5;")
               ::"r"(dst), "l"(m), "r"(bar), "r"(c0), "r"(c1), "h"((uint16_t)3) : "memory");
}
DEVINL void e_arrive_both(uint32_t bar) {
  asm volatile("{\n.reg .pred pe;\n.reg .b32 r0, r1;\nelect.sync _|pe, 0xffffffff;\nmapa.shared::cluster.u32 r0, %0, 0;\nmapa.shared::cluster.u32 r1, %0, 1;\n"
               "@pe mbarrier.arrive.shared::cluster.b64 _, [r0];\n@pe mbarrier.arrive.shared::cluster.b64 _, [r1];\n}" ::"r"(bar) : "memory");
}
DEVINL void push_peer(uint32_t dst, uint32_t src, uint32_t bar, uint32_t peer) {
  asm volatile("{\n.reg .pred pe;\n.reg .b32 d, b;\nelect.sync _|pe, 0xffffffff;\nmapa.shared::cluster.u32 d, %0, %3;\nmapa.shared::cluster.u32 b, %2, %3;\n"
               "@pe cp.async.bulk.shared::cluster.shared::cta.mbarrier::complete_tx::bytes [d], [%1], 16384, [b];\n}" ::"r"(dst), "r"(src), "r"(bar), "r"(peer) : "memory");
}
DEVINL void tma_st(const CUtensorMap* m, int c0, int c1, uint32_t src) {
  asm volatile(EL("cp.async.bulk.tensor.2d.global.shared::cta.bulk_group [%0, {%2, %3}], [%1];") ::"l"(m), "r"(src), "r"(c0), "r"(c1) : "memory");
}
DEVINL void bulk_commit() { asm volatile("cp.async.bulk.commit_group;" ::: "memory"); }
template <int N> DEVINL void bulk_wait_n() { asm volatile("cp.async.bulk.wait_group %0;\nbar.warp.sync 0xffffffff;" ::"n"(N) : "memory"); }
DEVINL void l2_prefetch(const void* g, uint32_t bytes) { asm volatile(EL("cp.async.bulk.prefetch.L2.global [%0], %1;") ::"l"(g), "r"(bytes) : "memory"); }
DEVINL void fence_async_smem() { asm volatile("fence.proxy.async.shared::cta;" ::: "memory"); }
DEVINL void fence_async_gl() { asm volatile("fence.proxy.async.global;" ::: "memory"); }
DEVINL void cluster_wait() { asm volatile("barrier.cluster.wait.aligned;" ::: "memory"); }
DEVINL void bar_sync(int id, int n) { asm volatile("bar.sync %0, %1;" ::"r"(id), "r"(n) : "memory"); }
DEVINL void bar_arrive(int id, int n) { asm volatile("bar.arrive %0, %1;" ::"r"(id), "r"(n) : "memory"); }
DEVINL uint32_t ld_acquire(const uint32_t* p) { uint32_t v; asm volatile("ld.acquire.gpu.global.u32 %0, [%1];" : "=r"(v) : "l"(p) : "memory"); return v; }
DEVINL void watch(const uint32_t* p, uint32_t target, uint32_t all, uint32_t tag, uint32_t slot) {
  uint32_t seen = 0;
#pragma unroll 1
  for (uint32_t n = 0; n < 200000u && seen != all; n++) {
    const uint32_t m = __ballot_sync(~0u, (int)(ld_acquire(p) - target) >= 0) & all;
    if (m != seen) { seen = m; asm volatile("st.release.cta.shared.u32 [%0], %1;" ::"r"(slot), "r"(tag << 16 | m) : "memory"); }
  }
}
template <bool RELAXED = false> DEVINL void await_bit(uint32_t slot, uint32_t tag, int j, uint32_t& rdy) {
  if ((rdy >> j) & 1) return;
#pragma unroll 1
  for (uint32_t n = 0; n < 8000000u; n++) {
    uint32_t v;
    asm volatile("ld.acquire.cta.shared.u32 %0, [%1];" : "=r"(v) : "r"(slot) : "memory");
    if ((v >> 16) == tag && ((v >> j) & 1)) { rdy = v; break; }
    if (RELAXED) __nanosleep(200); else if (PSLEEP) __nanosleep(PSLEEP);
  }
  asm volatile("fence.proxy.async.global;" ::: "memory");
}
DEVINL void poll_ge(const uint32_t* p, uint32_t target) {
#pragma unroll 1
  for (uint32_t n = 0; n < 200000u; n++) if (__all_sync(~0u, (int)(ld_acquire(p) - target) >= 0)) break;
}
DEVINL int lane_id() { int v; asm volatile("mov.u32 %0, %%laneid;" : "=r"(v)); return v; }
__host__ DEVINL int remap(int v) {
  const int c = v >> 1, u = c - 36, r = (u * 37) >> 8;
  const int L = max(c - 4 + max(r + 1, 0), (c - 4) >> 31 & (32 + 8 * c));
  return 2 * L + (v & 1);
}
DEVINL int block_id() { int v; asm volatile("mov.u32 %0, %%ctaid.x;" : "=r"(v)); return v; }
#define cta_id() prm.map[block_id()]
#define IDS() const int lane = lane_id(), b = cta_id(), bm = b >> 4, bn = b & 15, rank = b & 1, pm = 2 * bm + (bn >> 3), pn = bn & 7, po = pm & 1; \
  (void)lane; (void)bm; (void)bn; (void)rank; (void)pm; (void)pn; (void)po
DEVINL void st_tagged(unsigned long long* p, uint32_t v, uint32_t tag) {
  asm volatile("{\n.reg .b64 t;\nmov.b64 t, {%1, %2};\nst.relaxed.gpu.global.b64 [%0], t;\n}" ::"l"(p), "r"(v), "r"(tag) : "memory");
}
DEVINL float ex2(float x) { float y; asm("ex2.approx.ftz.f32 %0, %1;" : "=f"(y) : "f"(x)); return y; }
DEVINL float rcp(float x) { float y; asm("rcp.approx.ftz.f32 %0, %1;" : "=f"(y) : "f"(x)); return y; }
DEVINL uint32_t pack2(float lo, float hi) { uint32_t r; asm("cvt.rn.bf16x2.f32 %0, %1, %2;" : "=r"(r) : "f"(hi), "f"(lo)); return r; }
DEVINL float bf_lo(uint32_t w) { return __uint_as_float(w << 16); }
DEVINL float bf_hi(uint32_t w) { return __uint_as_float(w & 0xFFFF0000u); }
DEVINL float bf_round(float x) { return bf_lo(pack2(x, 0.f)); }
DEVINL uint32_t add_bf16x2(uint32_t a, uint32_t b) { uint32_t r; asm("add.rn.bf16x2 %0, %1, %2;" : "=r"(r) : "r"(a), "r"(b)); return r; }
DEVINL void stsm4(uint32_t addr, uint32_t a, uint32_t b, uint32_t c, uint32_t d) {
  asm volatile("stmatrix.sync.aligned.m8n8.x4.shared.b16 [%0], {%1, %2, %3, %4};" ::"r"(addr), "r"(a), "r"(b), "r"(c), "r"(d) : "memory");
}
DEVINL void ldsm4(uint32_t addr, uint32_t (&r)[4]) {
  asm volatile("ldmatrix.sync.aligned.m8n8.x4.shared.b16 {%0, %1, %2, %3}, [%4];" : "=r"(r[0]), "=r"(r[1]), "=r"(r[2]), "=r"(r[3]) : "r"(addr) : "memory");
}
DEVINL void ldsm4t(uint32_t addr, uint32_t (&r)[4]) {
  asm volatile("ldmatrix.sync.aligned.m8n8.x4.trans.shared.b16 {%0, %1, %2, %3}, [%4];" : "=r"(r[0]), "=r"(r[1]), "=r"(r[2]), "=r"(r[3]) : "r"(addr) : "memory");
}
DEVINL void sts128(uint32_t addr, uint32_t a, uint32_t b, uint32_t c, uint32_t d) {
  asm volatile("st.shared.v4.b32 [%0], {%1, %2, %3, %4};" ::"r"(addr), "r"(a), "r"(b), "r"(c), "r"(d) : "memory");
}
DEVINL float4 lds128f(uint32_t addr) { float4 v; asm volatile("ld.shared.v4.f32 {%0, %1, %2, %3}, [%4];" : "=f"(v.x), "=f"(v.y), "=f"(v.z), "=f"(v.w) : "r"(addr) : "memory"); return v; }
DEVINL float lds32f(uint32_t addr) { float v; asm volatile("ld.shared.f32 %0, [%1];" : "=f"(v) : "r"(addr) : "memory"); return v; }
DEVINL float2 lds64f(uint32_t addr) { float2 v; asm volatile("ld.shared.v2.f32 {%0, %1}, [%2];" : "=f"(v.x), "=f"(v.y) : "r"(addr) : "memory"); return v; }
DEVINL void mma16816(float (&d)[4], uint32_t a0, uint32_t a1, uint32_t a2, uint32_t a3, uint32_t b0, uint32_t b1) {
  asm("mma.sync.aligned.m16n8k16.row.col.f32.bf16.bf16.f32 {%0, %1, %2, %3}, {%4, %5, %6, %7}, {%8, %9}, {%0, %1, %2, %3};"
               : "+f"(d[0]), "+f"(d[1]), "+f"(d[2]), "+f"(d[3]) : "r"(a0), "r"(a1), "r"(a2), "r"(a3), "r"(b0), "r"(b1));
}
DEVINL void mma1688(float (&d)[4], uint32_t a0, uint32_t a1, uint32_t b0) {
  asm("mma.sync.aligned.m16n8k8.row.col.f32.bf16.bf16.f32 {%0, %1, %2, %3}, {%4, %5}, {%6}, {%0, %1, %2, %3};"
               : "+f"(d[0]), "+f"(d[1]), "+f"(d[2]), "+f"(d[3]) : "r"(a0), "r"(a1), "r"(b0));
}
DEVINL void mma16816h(float (&d)[4], uint32_t a0, uint32_t a1, uint32_t a2, uint32_t a3, uint32_t b0, uint32_t b1) {
  asm("mma.sync.aligned.m16n8k16.row.col.f32.f16.f16.f32 {%0, %1, %2, %3}, {%4, %5, %6, %7}, {%8, %9}, {%0, %1, %2, %3};"
               : "+f"(d[0]), "+f"(d[1]), "+f"(d[2]), "+f"(d[3]) : "r"(a0), "r"(a1), "r"(a2), "r"(a3), "r"(b0), "r"(b1));
}
template <int N> DEVINL void fence_regs(uint32_t (&d)[N]) {
#pragma unroll
  for (int i = 0; i < N; i++) asm volatile("" : "+r"(d[i])::"memory");
}
template <int N> DEVINL void fence_regs(float (&d)[N]) {
#pragma unroll
  for (int i = 0; i < N; i++) asm volatile("" : "+f"(d[i])::"memory");
}

__device__ __align__(1024) bf16 g_xs[2048 * 1024];
__device__ __align__(1024) bf16 g_os[2048 * 1024];
__device__ __align__(1024) bf16 g_k[32 * 2048 * 32];
__device__ __align__(1024) bf16 g_v[32 * 2048 * 32];
__device__ __align__(128) float2 g_stats[8 * 2048];
__device__ __align__(16) float g_csp[2 * 16 * 8 * 192];
__device__ __align__(128) float g_kn[2 * 128 * 32];
__device__ unsigned long long g_halo[2 * 128 * 32 * 32];
__device__ __align__(128) uint32_t g_cnt[256 * 32];
__device__ uint32_t g_epoch;

DEVINL uint32_t* cnt_x(int l, int bm) { return g_cnt + (l * 8 + bm) * 32; }
DEVINL uint32_t* cnt_o(int l, int pm, int h) { return g_cnt + (32 + (l * 16 + pm) * 2 + h) * 32; }
DEVINL uint32_t* cnt_kv(int lb, int bn) { return g_cnt + (160 + lb * 16 + bn) * 32; }
DEVINL uint32_t* cnt_ad(int bn) { return g_cnt + (192 + bn) * 32; }
DEVINL uint32_t* cnt_cs(int t, int bn) { return g_cnt + (208 + t * 16 + bn) * 32; }

DEVINL int qord(int i, int l, int pn) { return l == 0 ? i : i < 4 ? ((2 * pn) ^ (i & 2)) + (i & 1) : i - 4 < 2 * (pn & 6) ? i - 4 : i; }
struct Params {
  CUtensorMap m[17];
  const bf16* x0;
  const bf16* wq[2];
  const bf16* wo[2];
  uint32_t* epoch;
  uint32_t zero;
  int map[128];
};
enum { M_X0A = 0, M_XSA, M_WQA, M_WQB, M_WOA, M_WOB, M_OS, M_K, M_V, M_X0R, M_XSR, M_XSO, M_OUT, M_XST, M_X0H, M_K4, M_V4, M_COUNT };

constexpr uint32_t QSTG = 57344;
constexpr uint32_t T0 = 65536, TSTG = 32768;
constexpr uint32_t ONES = 229376;
constexpr uint32_t PSTG = 32768, RES = 196608;
constexpr uint32_t ASC = 17408;
constexpr uint32_t RSTD = 229376, MEAN = 230400, COLS = 230912, KMAX = 231680, B_QD = 231688, BARS = 232192, SMEM_BYTES = 232448;
constexpr uint32_t B_QF = BARS, B_QE = BARS + 32, B_TF = BARS + 64, B_TE = BARS + 96, B_PF = BARS + 128, B_PE = BARS + 176,
                   B_RF = BARS + 224, W_X = BARS + 232, W_O = BARS + 236, B_QL = BARS + 240, B_PA = BARS + 248;
enum { NB_ST = 1, NB_KV = 2  , NB_DONE = 3, NB_SC = 4, NB_SIG = 5  , NB_KN = 9  , NB_X = 11, NB_HALO = 12  , NB_X0 = 15 };

DEVINL uint32_t pslot_b(uint32_t s, int l) { return ((((l & 1) ? 0x320415u : 0x468795u) >> (4 * s)) & 15) * 16384u; }
DEVINL uint32_t pslot_a(uint32_t s, int l) { return ((((l & 1) ? 0xBA7896u : 0x32DCBAu) >> (4 * s)) & 15) * 16384u; }

#define G1 2
#define G2 0
#define G3 2
#define KC (11 + 2 * wg)
#define NA2 2
#define RESI 12
#define PERHEAD 1
#define PFETCH 0
#define PFW 3
#define PFI 8
#define H1ST 4
#define H1RED 5
#define WGBAR 0
#define NRB 16
#define LEAHI 2
#define ONECOL 0
#define NQ 32
#define OA 0x10
#define OB 0x10
#define LAG 2
#define NQB NQ
#define QK_A wgmma_m64n32k16_rs_nb_h
#define QK_B wgmma_m64n32k16_rs_nb_hh
constexpr float QSCALE = 0.17677669529663687f * 1.4426950408889634f;

DEVINL uint32_t hfma2(uint32_t a, uint32_t b, uint32_t c) { uint32_t r; asm("fma.rn.f16x2 %0, %1, %2, %3;" : "=r"(r) : "r"(a), "r"(b), "r"(c)); return r; }
DEVINL uint32_t pack2h(float lo, float hi) { uint32_t r; asm("cvt.rn.f16x2.f32 %0, %1, %2;" : "=r"(r) : "f"(hi), "f"(lo)); return r; }
DEVINL uint32_t h2_to_bf2(uint32_t h) {
  float a, b;
  asm("{\n.reg .b16 l, h;\nmov.b32 {l, h}, %2;\ncvt.f32.f16 %0, l;\ncvt.f32.f16 %1, h;\n}" : "=f"(a), "=f"(b) : "r"(h));
  return pack2(a, b);
}
DEVINL uint32_t exp2_h2(uint32_t s, uint32_t zero) {
  const uint32_t r = hfma2(s, 0x00800080u, 0x007E007Eu);
  const uint32_t g = hfma2(hfma2(r, 0xF800F800u, 0x33FD33FDu), 0x44004400u, s);
  return (LEAHI == 2 ? __funnelshift_l(r, r, 7) : LEAHI ? __funnelshift_l(zero, r, 7) : r * 128u) + hfma2(hfma2(g, g, 0x0DE10DE1u), g, 0x00300030u);
}
constexpr uint32_t NOT_F16 = 0x7FC00000u, K_LO = 0x35000000u  ;
DEVINL uint32_t f16_class(uint32_t norm2, uint32_t lo) { return norm2 - lo > 0x4E800000u - lo ? NOT_F16 : norm2; }

DEVINL void attn_slow(const uint32_t (&q)[8], float up, int head, const float* kn, float (&res)[20], int lane) {
  const int g = lane >> 2, qd = lane & 3;
  const bf16* kb = g_k + (size_t)head * 2048 * 32;
  const bf16* vb = g_v + (size_t)head * 2048 * 32;
  float o[4][4], m0 = -INFINITY, m1 = -INFINITY, l0 = 0.f, l1 = 0.f;
#pragma unroll
  for (int j = 0; j < 4; j++) { o[j][0] = o[j][1] = o[j][2] = o[j][3] = 0.f; }
#pragma unroll 1
  for (int k0 = 0; k0 < 2048; k0 += 16) {
    float s[2][4];
    const bool kh = __float_as_uint(__ldcg(kn + (k0 >> 8) * 32 + ((k0 >> 6) & 1) * 8 + ((k0 >> 7) & 1) * 4 + ((k0 >> 4) & 3))) != NOT_F16;
#pragma unroll
    for (int nt = 0; nt < 2; nt++) {
      s[nt][0] = s[nt][1] = s[nt][2] = s[nt][3] = 0.f;
      const uint32_t* kp = (const uint32_t*)(kb + (size_t)(k0 + nt * 8 + g) * 32) + qd;
      uint32_t kf[4];
#pragma unroll
      for (int i = 0; i < 4; i++) { kf[i] = __ldcg(kp + 4 * i); if (kh) kf[i] = h2_to_bf2(kf[i]); }
      mma16816(s[nt], q[0], q[1], q[2], q[3], kf[0], kf[1]);
      mma16816(s[nt], q[4], q[5], q[6], q[7], kf[2], kf[3]);
      s[nt][0] *= up; s[nt][1] *= up; s[nt][2] *= up; s[nt][3] *= up;
    }
    float a0 = fmaxf(fmaxf(s[0][0], s[0][1]), fmaxf(s[1][0], s[1][1]));
    float a1 = fmaxf(fmaxf(s[0][2], s[0][3]), fmaxf(s[1][2], s[1][3]));
    a0 = fmaxf(a0, __shfl_xor_sync(~0u, a0, 1)); a0 = fmaxf(a0, __shfl_xor_sync(~0u, a0, 2));
    a1 = fmaxf(a1, __shfl_xor_sync(~0u, a1, 1)); a1 = fmaxf(a1, __shfl_xor_sync(~0u, a1, 2));
    const float n0 = fmaxf(m0, a0), n1 = fmaxf(m1, a1);
    const float c0 = (m0 == n0) ? 1.f : ex2(m0 - n0), c1 = (m1 == n1) ? 1.f : ex2(m1 - n1);
    m0 = n0; m1 = n1;
    const uint32_t p0 = pack2(ex2(s[0][0] - n0), ex2(s[0][1] - n0)), p1 = pack2(ex2(s[0][2] - n1), ex2(s[0][3] - n1));
    const uint32_t p2 = pack2(ex2(s[1][0] - n0), ex2(s[1][1] - n0)), p3 = pack2(ex2(s[1][2] - n1), ex2(s[1][3] - n1));
    l0 = l0 * c0 + bf_lo(p0) + bf_hi(p0) + bf_lo(p2) + bf_hi(p2);
    l1 = l1 * c1 + bf_lo(p1) + bf_hi(p1) + bf_lo(p3) + bf_hi(p3);
#pragma unroll
    for (int j = 0; j < 4; j++) {
      o[j][0] *= c0; o[j][1] *= c0; o[j][2] *= c1; o[j][3] *= c1;
      const unsigned short* vp = (const unsigned short*)(vb + (size_t)(k0 + 2 * qd) * 32 + j * 8 + g);
      const uint32_t b0 = (uint32_t)__ldcg(vp) | ((uint32_t)__ldcg(vp + 32) << 16);
      const uint32_t b1 = (uint32_t)__ldcg(vp + 256) | ((uint32_t)__ldcg(vp + 288) << 16);
      mma16816(o[j], p0, p1, p2, p3, b0, b1);
    }
  }
  l0 += __shfl_xor_sync(~0u, l0, 1); l0 += __shfl_xor_sync(~0u, l0, 2);
  l1 += __shfl_xor_sync(~0u, l1, 1); l1 += __shfl_xor_sync(~0u, l1, 2);
#pragma unroll
  for (int j = 0; j < 4; j++) { res[4 * j] = o[j][0]; res[4 * j + 1] = o[j][1]; res[4 * j + 2] = o[j][2]; res[4 * j + 3] = o[j][3]; }
  res[16] = l0; res[18] = l1;
}

__global__ void __cluster_dims__(2, 1, 1) __launch_bounds__(384, 1) fused_kernel(const __grid_constant__ Params prm) {
  extern __shared__ __align__(1024) char smem[];
  const uint32_t sb = (uint32_t)__cvta_generic_to_shared(smem);
  const int tid = threadIdx.x;
  const int wid = __shfl_sync(0xffffffffu, tid >> 5, 0), wg = wid >> 2, w = wid & 3;
  const int bm = remap(blockIdx.x) >> 4, bn = remap(blockIdx.x) & 15;
  auto first_tile = [&](int kt) {
    e_expect_tx(sb + B_QF + 8 * kt, QSTG);
    tma_ld(sb + kt * QSTG, &prm.m[M_X0A], kt * 64, bm * 256, sb + B_QF + 8 * kt);
    tma_ld3(sb + kt * QSTG + 32768, &prm.m[M_WQA], bn * 64, kt * 64, 0, sb + B_QF + 8 * kt);
  };
  if (wid == 8) {
    e_init(sb + B_QF, 1);
    asm volatile("fence.mbarrier_init.release.cluster;" ::: "memory");
    first_tile(0);
  }
  if (wid < 8) {
#pragma unroll
    for (int i = 0; i < 4; i++) {
      const uint32_t cnt = (uint32_t)((i == 0 ? 0x14112140 : i == 1 ? 0x04112141 : i == 2 ? 0x14412141 : 0x24412141) >> (4 * wid)) & 7;
      if (cnt) e_init(sb + BARS + 32 * wid + 8 * i, cnt);
    }
    if (wid == 0 || wid == 7) e_init(sb + B_QD + (wid & 1) * 8, 1);
    if (tid == 255) *(uint2*)(smem + W_X) = make_uint2(0u, 0u);
    asm volatile("fence.mbarrier_init.release.cluster;" ::: "memory");
  }
  const uint32_t epoch = *(volatile uint32_t*)prm.epoch;
  __syncthreads();
  asm volatile("barrier.cluster.arrive.relaxed.aligned;" ::: "memory");

  if (wg == 2) {
    asm volatile("setmaxnreg.dec.sync.aligned.u32 56;");
    const uint32_t ep1 = epoch + 1;
    if (w == 0) {
      first_tile(1);
      mbar_wait(sb + B_QF, 0);
      first_tile(2); first_tile(3);
#pragma unroll 1
      for (int kt = 4; kt < 16; kt++) l2_prefetch(prm.wq[0] + kt * 196608 + blockIdx.x * 1536, 3072);
      cluster_wait();
#pragma unroll 1
      for (int l = 0; l < 4; l++) {
        IDS();
        const CUtensorMap* mw = &prm.m[M_WQA + (l & 1)];
        const CUtensorMap* mh = &prm.m[l == 0 ? M_X0H : M_XSO];
        const CUtensorMap* mo = &prm.m[M_WOA + (l & 1)];
        auto q_b = [&](int i) {
          const int s = i & 3;
          mbar_wait(sb + B_QE + 8 * s, ((i >> 2) & 1) ^ 1);
          e_expect_tx(sb + B_QF + 8 * s, QSTG);
          tma_ld3(sb + s * QSTG + 32768, mw, bn * 64, qord(i, l, pn) * 64, 0, sb + B_QF + 8 * s);
        };
        uint32_t rdy = l ? 0u : ~0u;
        auto q_a = [&](int i) {
          const int kt = qord(i, l, pn);
          await_bit(sb + W_X, l, kt >> 1, rdy);
          tma_ld_mc(sb + (i & 3) * QSTG + rank * 16384, mh, kt * 64, bm * 256 + rank * 128, sb + B_QF + 8 * (i & 3));
        };
        if (l > 0) {
#pragma unroll 1
          for (int i = 0; i < 4; i++) {
            const int kt = qord(i, l, pn);
            await_bit(sb + W_X, l, kt >> 1, rdy);
            e_expect_tx(sb + B_QF + 8 * i, 16384);
            tma_ld(sb + i * QSTG + (po ^ 1) * 16384, &prm.m[M_XSO], kt * 64, (pm ^ 1) * 128, sb + B_QF + 8 * i);
          }
        }
#pragma unroll 1
        for (int i = 4; i < 16; i++) {
          q_b(i); q_a(i);
          if (l == 0 && (PFW & 1) && i >= PFI && i < PFI + 4) l2_prefetch(prm.wq[1] + (blockIdx.x * 4 + i - PFI) * 6144, 12288);
          if (l < 2 && (PFW & 2) && i == PFI + 4) l2_prefetch(prm.wo[l] + blockIdx.x * 8192, 16384);
        }
        if (l & 1) {
          if (l == 3) poll_ge(cnt_ad(bn), ep1 * 16);
          const int krow = 2 * bn * 2048 + bm * 256;
          uint32_t* kvc = cnt_kv(l >> 1, bn);
#pragma unroll 1
          for (int m = 1; m >= 0; m--) {
            bar_sync(m ? NB_ST : NB_KV, 288);
#pragma unroll
            for (int i = 0; i < 4; i++) tma_st(&prm.m[M_K4 + (i >> 1)], 0, krow + (i & 1) * 128 + m * 64, sb + T0 + i * 8192 + m * 4096);
            if (m) {
              sts128(sb + ONES + lane * 32, 0x3f803f80u, 0x3f803f80u, 0x3f803f80u, 0x3f803f80u);
              sts128(sb + ONES + lane * 32 + 16, 0x3f803f80u, 0x3f803f80u, 0x3f803f80u, 0x3f803f80u);
              fence_async_smem();
              __syncwarp();
            }
          }
          e_arrive(sb + B_TF);
          bulk_commit(); bulk_wait_n<0>();
          e_red(kvc + bm);
          bar_sync(NB_KV + 12, 288);
          uint32_t seen = 0;
#pragma unroll 1
          for (int it = 1; it < 16; it++) {
            const int s = it & 3, blk = it;
            if (it == H1ST) { tma_st(&prm.m[M_K], 0, krow + 2048, sb); tma_st(&prm.m[M_V], 0, krow + 2048, sb + 16384); bulk_commit(); }
            if (it == H1RED) { bulk_wait_n<0>(); e_red(kvc + bm); }
            if (it == 12) { e_expect_tx(sb + B_RF, 32768); tma_ld3(sb + RES, &prm.m[M_XSR], 0, pm * 128, 2 * pn, sb + B_RF); }
            if (it == 2 || it == 3) mbar_wait(sb + B_TF + 8 * (it - 1), 0);
            MWL(sb + B_TE + 8 * s, ((it >> 2) & 1) ^ 1);
            if (it < 8) {
#pragma unroll 1
              for (uint32_t n = 0; n < 200000u && !((seen >> it) & 1); n++)
                seen = __ballot_sync(~0u, (int)(ld_acquire(kvc + ((bm + lane) & 7)) - (ep1 * 2 - 1)) >= 0);
              fence_async_gl();
            } else if (it == 8) { poll_ge(kvc + (lane & 7), ep1 * 2); fence_async_gl(); bar_arrive(NB_HALO, 64); }
            else if (it == 15) bar_arrive(NB_HALO + 1, 64);
            const int row = (2 * bn + (it >> 3)) * 2048 + ((bm + blk) & 7) * 256;
            e_expect_tx(sb + B_TF + 8 * s, 32768);
            tma_ld(sb + T0 + s * TSTG, &prm.m[M_K], 0, row, sb + B_TF + 8 * s);
            tma_ld(sb + T0 + s * TSTG + 16384, &prm.m[M_V], 0, row, sb + B_TF + 8 * s);
          }
        }
        auto p_b = [&](int i, uint32_t s, uint32_t par) {
          mbar_wait(sb + B_PE + 8 * s, par ^ 1);
          e_expect_tx(sb + B_PF + 8 * s, PSTG);
          tma_ld5(sb + pslot_b(s, l), mo, i >> 3, 2 * (i & 7), 2 * pn, sb + B_PF + 8 * s);
        };
        auto p_a = [&](int i, uint32_t s) {
          await_bit(sb + W_O, l + 1, i, rdy);
          tma_ld_mc(sb + pslot_a(s, l) + rank * 8192, &prm.m[M_OS], i * 64, pm * 128 + rank * 64, sb + B_PF + 8 * s);
        };
        auto p_a2 = [&](int i) {
          await_bit(sb + W_O, l + 1, i, rdy);
          tma_ld(sb + pslot_a(i, l), &prm.m[M_OS], i * 64, pm * 128, sb + B_PF + 8 * i);
          tma_ld(sb + pslot_a(i, l) + 8192, &prm.m[M_OS], i * 64, pm * 128 + 64, sb + B_PF + 8 * i);
        };
        rdy = 0;
        if (l & 1) {
#pragma unroll 1
          for (int u = 0; u < 6; u++) { const int i = (0x205413 >> (4 * u)) & 7; if (u == 4) MWL(sb + B_TE, 1); p_b(i, i, i < 4 ? 1 : 0); }
#pragma unroll 1
          for (int u = 0; u < 6; u++) {
            const int i = (0x542130 >> (4 * u)) & 7;
            if (!(u & 1)) MWL(sb + B_TE + 8 + 4 * u, 1);
            p_a2(i);
          }
        } else {
#pragma unroll 1
          for (int u = 0; u < 5; u++) { const int i = (0x32140 >> (4 * u)) & 7; if (!(u & 5)) mbar_wait(sb + B_QE + 8 + 4 * u, 1); p_b(i, i, 0); }
          mbar_wait(sb + B_QE + 24, 1);
          if (PLATE) bar_sync(NB_KN, 96);
#pragma unroll 1
          for (int i = 0; i < 4; i++) { if (i < NA2) p_a2(i); else p_a(i, i); }
          bar_sync(NB_DONE, 96);
          e_arrive_both(sb + B_PA);
          p_b(5, 5, 0);
          mbar_wait(sb + B_PA, (l >> 1) & 1);
          p_a(4, 4); p_a(5, 5);
        }
        uint32_t s = 0, lap = 1;
#pragma unroll 1
        for (int i = 6; i < 16; i++) {
          if (i == RESI && !(l & 1)) { e_expect_tx(sb + B_RF, 32768); tma_ld3(sb, &prm.m[l == 0 ? M_X0R : M_XSR], 0, pm * 128, 2 * pn, sb + B_RF); }
          p_b(i, s, ((s < 4 ? l : 0) + lap) & 1);
          p_a(i, s);
          if (++s == 6) { s = 0; lap++; }
        }
        const CUtensorMap* mn = &prm.m[M_WQA + ((l + 1) & 1)];
        if (l < 3) {
          mbar_wait(sb + B_PE + 8 * 4, 1); mbar_wait(sb + B_PE + 8 * 5, 1);
          tma_ld3(sb + 32768, mn, bn * 64, 2 * pn * 64, 0, sb + B_QL);
          mbar_wait(sb + B_PE + 8 * 0, l & 1);
          tma_ld3(sb + QSTG + 32768, mn, bn * 64, (2 * pn + 1) * 64, 0, sb + B_QL);
          mbar_wait(sb + B_PE + 8 * 1, l & 1);
          e_expect_tx(sb + B_QD, 40960);
          tma_ld3(sb + 2 * QSTG + 32768, mn, bn * 64, ((2 * pn) ^ 2) * 64, 0, sb + B_QD);
          bar_sync(NB_X, 288);
          e_expect_tx(sb + B_QL, 49152);
          e_expect_tx(sb + B_QD + 8, 40960);
          tma_ld3(sb + 3 * QSTG + 32768, mn, bn * 64, (((2 * pn) ^ 2) + 1) * 64, 0, sb + B_QD + 8);
        }
      }
      if (blockIdx.x == 0 && lane_id() == 0) *(volatile uint32_t*)prm.epoch = ep1;
    } else {
      const int hw = w - 1;
      if (hw == 1 && lane_id() < M_COUNT) asm volatile("prefetch.tensormap [%0];" ::"l"(&prm.m[lane_id()]) : "memory");
      cluster_wait();
      mbar_wait(sb + B_QF, 0);
#pragma unroll 1
      for (int l = 0; l < 4; l++) {
        IDS();
        if (hw == 2 && l > 0) watch(cnt_x(l, bm) + (lane & 7), ep1 * 2, 0xFFu, l, sb + W_X);
        if (l == 0) {
#pragma unroll 1
          for (int r = 2 * hw; r < 16; r += 6) {
            const uint4* p = (const uint4*)(prm.x0 + (size_t)(b * 16 + r) * 1024) + lane;
            float s1[2] = {0.f, 0.f}, s2[2] = {0.f, 0.f};
#pragma unroll
            for (int i = 0; i < 8; i++) {
              const uint4 v = __ldg(p + 32 * i);
              const uint32_t u[4] = {v.x, v.y, v.z, v.w};
#pragma unroll
              for (int k = 0; k < 4; k++) { const float a = bf_lo(u[k]), c = bf_hi(u[k]); s1[i >> 2] += a + c; s2[i >> 2] = fmaf(a, a, fmaf(c, c, s2[i >> 2])); }
            }
#pragma unroll
            for (int o = 16; o; o >>= 1)
#pragma unroll
              for (int rr = 0; rr < 2; rr++) { s1[rr] += __shfl_xor_sync(~0u, s1[rr], o); s2[rr] += __shfl_xor_sync(~0u, s2[rr], o); }
            if (lane == 0) *(float4*)&g_stats[b * 16 + r] = make_float4(s1[0], s2[0], s1[1], s2[1]);
          }
        }
        if (l == 1) { uint32_t rdy = 0; await_bit<true>(sb + W_X, 1, pn, rdy); mbar_hint(sb + B_QF + 8, 0); }
        if (l < 2) {
          float cs[8];
#pragma unroll
          for (int i = 0; i < 8; i++) cs[i] = 0.f;
          const uint4* wp = (const uint4*)(prm.wq[l] + (size_t)(bm * 128 + (lane >> 3)) * 3072 + hw * 1024 + bn * 64) + (lane & 7);
#pragma unroll 8
          for (int i = 0; i < 32; i++) {
            const uint4 v = __ldg(wp + (size_t)i * 4 * 384);
            cs[0] += bf_lo(v.x); cs[1] += bf_hi(v.x); cs[2] += bf_lo(v.y); cs[3] += bf_hi(v.y);
            cs[4] += bf_lo(v.z); cs[5] += bf_hi(v.z); cs[6] += bf_lo(v.w); cs[7] += bf_hi(v.w);
          }
#pragma unroll
          for (int i = 0; i < 8; i++) { cs[i] += __shfl_xor_sync(~0u, cs[i], 8); cs[i] += __shfl_xor_sync(~0u, cs[i], 16); }
          if (lane < 8) {
            float4* d = (float4*)(g_csp + ((l * 16 + bn) * 8 + bm) * 192 + hw * 64 + lane * 8);
            d[0] = make_float4(cs[0], cs[1], cs[2], cs[3]); d[1] = make_float4(cs[4], cs[5], cs[6], cs[7]);
          }
          __syncwarp();
          asm volatile("fence.acq_rel.gpu;" ::: "memory");
          e_red_relaxed(cnt_cs(l, bn));
          if (l == 0) e_red_relaxed(cnt_x(0, bm) + pn);
          poll_ge(lane < 8 && l == 0 ? cnt_x(0, bm) + lane : cnt_cs(l, bn), ep1 * (lane < 8 && l == 0 ? 6 : 24));
        }
        if (l > 0) {
          uint32_t rdy = 0;
#pragma unroll 1
          for (int j = 0; j < 8; j++) await_bit<true>(sb + W_X, l, j, rdy);
        }
#pragma unroll 1
        for (int it = hw * 32 + lane; it < 176; it += 96) {
          const bool rows = it < 128;
          const float4* p = rows ? (const float4*)(g_stats + bm * 256) + it : (const float4*)(g_csp + ((l & 1) * 16 + bn) * 8 * 192) + (it - 128);
          const int stride = rows ? 1024 : 48, np = rows && l == 0 ? 1 : 8;
          float4 a = make_float4(0.f, 0.f, 0.f, 0.f);
#pragma unroll
          for (int k = 0; k < 8; k++) if (k < np) { const float4 v = __ldcg(p + k * stride); a.x += v.x; a.y += v.y; a.z += v.z; a.w += v.w; }
          if (rows) {
            const float m0 = a.x * (1.f / 1024.f), m1 = a.z * (1.f / 1024.f);
            const float v0 = fmaxf(a.y * (1.f / 1024.f) - m0 * m0, 0.f), v1 = fmaxf(a.w * (1.f / 1024.f) - m1 * m1, 0.f);
            const float r0 = __fdividef(1.f, bf_round(sqrtf(bf_round(bf_round(v0) + 1e-5f)))), r1 = __fdividef(1.f, bf_round(sqrtf(bf_round(bf_round(v1) + 1e-5f))));
            *(float2*)(smem + RSTD + it * 8) = make_float2(r0, r1);
            *(uint32_t*)(smem + MEAN + it * 4) = pack2(-m0, -m1);
          } else {
            float2* d = (float2*)(smem + COLS) + ((it - 128) >> 2) * 8 + (it & 1) * 4 + ((it >> 1) & 1);
            d[0] = make_float2(a.y, a.x); d[2] = make_float2(a.w, a.z);
          }
        }
        __syncwarp();
        if (lane == 0) asm volatile("red.release.cta.shared.add.u32 [%0], 0x100;" ::"r"(sb + W_X) : "memory");
        if (hw == 2) {
          if (!(l & 1)) {
            bar_sync(NB_ST, 288);
            const volatile unsigned long long* hp = g_halo + ((size_t)(l >> 1) * 128 + b - 16) * 1024 + lane;
#pragma unroll 1
            for (int h = 0; h < 2; h++) {
              uint32_t t[16];
#pragma unroll
              for (int i = 0; i < 16; i++) t[i] = 0;
#pragma unroll 1
              for (uint32_t n = bm ? 0 : 100000u; n < 100000u; n++) {
                uint32_t miss = 0;
#pragma unroll
                for (int i = 0; i < 16; i++) {
                  const unsigned long long v = hp[h * 512 + i * 32];
                  t[i] = (uint32_t)v; miss |= (uint32_t)(v >> 32) ^ ep1;
                }
                if (__all_sync(~0u, !miss)) break;
              }
              const uint32_t r = (lane & 7) + ((lane >> 3) & 1) * 8, rv = lane >> 2;
#pragma unroll
              for (int jj = 0; jj < 2; jj++) stsm4(sb + 2 * h * ASC + r * 64 + (((2 * jj + (lane >> 4)) ^ ((r >> 1) & 3)) << 4), t[4 * jj], t[4 * jj + 1], t[4 * jj + 2], t[4 * jj + 3]);
              const uint32_t ad = sb + (2 * h + 1) * ASC + rv * 64 + (((lane & 3) ^ ((rv >> 1) & 3)) << 4);
              sts128(ad, t[8], t[10], t[12], t[14]); sts128(ad + 512, t[9], t[11], t[13], t[15]);
              bar_arrive(NB_HALO + h, 64);
            }
          } else {
            bar_sync(NB_HALO, 64);
            const uint4* kp = (const uint4*)(g_kn + ((l >> 1) * 128 + bn * 8) * 32) + 2 * lane;
            const uint4 v = __ldcg(kp), u = __ldcg(kp + 1);
            const uint32_t mx = max(max(max(v.x, v.y), max(v.z, v.w)), max(max(u.x, u.y), max(u.z, u.w)));
            const uint32_t m0 = __reduce_max_sync(~0u, (lane & 2) ? 0u : mx), m1 = __reduce_max_sync(~0u, (lane & 2) ? mx : 0u);
            if (lane == 0) *(uint2*)(smem + KMAX) = make_uint2(m0, m1);
            __syncwarp();
            bar_arrive(NB_KN, 160); bar_arrive(NB_KN + 1, 160);
            bar_sync(NB_HALO + 1, 64);
            watch(cnt_o(l, pm, 0) + (lane & 7), ep1 * 2, 0xFFu, l + 1, sb + W_O);
          }
        } else {
          bar_sync(NB_SIG + 2 * hw, 160); bar_sync(NB_SIG + 2 * hw + 1, 160);
          if (!(l & 1)) bar_arrive(NB_DONE, 96);
          if (hw == (l & 1)) bar_arrive((l & 1) ? NB_DONE : NB_KN, (l & 1) ? 64 : 64 + 32 * PLATE);
          asm volatile("fence.acq_rel.gpu;" ::: "memory");
          e_red_relaxed(cnt_o(l, 2 * bm, hw) + (bn >> 1));
          e_red_relaxed(cnt_o(l, 2 * bm + 1, hw) + (bn >> 1));
          if (hw == 1 && l == 1) { e_red_relaxed(cnt_ad(bn)); e_red_relaxed(cnt_ad(bn)); }
        }
        if (hw == 2) { bar_sync((l & 1) ? NB_DONE : NB_KN, (l & 1) ? 64 : 64 + 32 * PLATE); watch(cnt_o(l, pm, (lane >> 3) & 1) + (lane & 7), ep1 * 2, 0xFFFFu, l + 1, sb + W_O); }
        if (hw < 2 + XLATE && l < 3) {
          bar_sync(NB_X0, 320 + 32 * XLATE);
          if (hw == 0) {
            e_red(cnt_x(l + 1, bm) + pn);
          } else if (hw == 1) {
            mbar_wait(sb + B_PE + 8 * 3, l & 1);
            push_peer(sb + 2 * QSTG + po * 16384, sb + po * 16384, sb + B_QD, rank ^ 1);
            push_peer(sb + 3 * QSTG + po * 16384, sb + QSTG + po * 16384, sb + B_QD + 8, rank ^ 1);
          }
        }
      }
    }
  } else {
    asm volatile("setmaxnreg.inc.sync.aligned.u32 224;");
    const uint32_t zero = prm.zero;
    cluster_wait();
    const uint32_t ep1 = __shfl_sync(~0u, epoch + 1, 0);
#pragma unroll 1
    for (int l = 0; l < 4; l++) {
      {
        float acc[2][96];
#pragma unroll
        for (int i = 0; i < 96; i++) { acc[0][i] = 0.f; acc[1][i] = 0.f; }
        fence_regs(acc[0]); fence_regs(acc[1]);
        const bool early = l > 0 && wg == ((cta_id() >> 3) & 1);
#pragma unroll 1
        for (int kt = 0; kt < 14; kt++) {
          const int s = kt & 3;
          if (l > 0 && kt < 4 && kt != 1) mbar_wait(sb + (kt ? B_QD - 16 + 8 * kt : B_QL), (l + 1) & 1);
          if (!(early && kt < 4)) mbar_wait(sb + B_QF + 8 * s, (kt >> 2) & 1);
          const uint64_t da = mkdesc(sb + s * QSTG + wg * 16384, 16, 1024, 1), db = mkdesc(sb + s * QSTG + 32768, 8192, 1024, 1);
          wg_fence();
#pragma unroll
          for (int k = 0; k < 4; k++)
#pragma unroll
            for (int m = 0; m < 2; m++) wgmma_m64n192k16_ss_tb(acc[m], da + m * 512 + k * 2, db + k * 128, 1);
          wg_commit();
          wg_wait<1>();
          if (early && kt < 5) {
#pragma unroll 1
            for (int i = kt == 3 ? 0 : 3; i < kt; i++) { mbar_wait(sb + B_QF + 8 * i, 0); if (w == 0) e_arrive_both(sb + B_QE + 8 * i); }
          } else if (kt > 0 && w == 0) e_arrive_both(sb + B_QE + 8 * ((kt - 1) & 3));
          if (kt == KC) {
#pragma unroll 1
            for (uint32_t n = 0; n < 4000000u; n++) {
              uint32_t v;
              asm volatile("ld.acquire.cta.shared.u32 %0, [%1];" : "=r"(v) : "r"(sb + W_X) : "memory");
              if ((v >> 8) == (uint32_t)(l * 256 + 3)) break;
            }
            const int lane = lane_id();
            float nm[4];
#pragma unroll
            for (int i = 0; i < 4; i++) nm[i] = bf_lo(*(volatile unsigned short*)(smem + MEAN + (wg * 128 + w * 16 + (lane >> 2) + (i >> 1) * 64 + (i & 1) * 8) * 2));
            wg_wait<0>();
            fence_regs(acc[0]); fence_regs(acc[1]);
#pragma unroll
            for (int j = 0; j < 12; j++) {
              const float4 c = lds128f(sb + COLS + j * 64 + (lane & 3) * 16);
#pragma unroll
              for (int m = 0; m < 2; m++) {
                float* a = &acc[m][8 * j];
                a[0] = fmaf(nm[2 * m], c.y, a[0]); a[1] = fmaf(nm[2 * m], c.x, a[1]); a[2] = fmaf(nm[2 * m + 1], c.y, a[2]); a[3] = fmaf(nm[2 * m + 1], c.x, a[3]);
                a[4] = fmaf(nm[2 * m], c.w, a[4]); a[5] = fmaf(nm[2 * m], c.z, a[5]); a[6] = fmaf(nm[2 * m + 1], c.w, a[6]); a[7] = fmaf(nm[2 * m + 1], c.z, a[7]);
              }
            }
            fence_regs(acc[0]); fence_regs(acc[1]);
          }
        }
        auto part = [&](int s, int m, int k0, int k1) {
          const uint64_t da = mkdesc(sb + s * QSTG + wg * 16384 + m * 8192, 16, 1024, 1), db = mkdesc(sb + s * QSTG + 32768, 8192, 1024, 1);
          pin(zero);
          wg_fence();
#pragma unroll
          for (int k = k0; k < k1; k++) wgmma_m64n192k16_ss_tb(acc[m], da + k * 2, db + k * 128, 1);
          wg_commit();
          pin(zero);
        };
        mbar_wait(sb + B_QF + 16, 1);
        part(2, 1, 0, 4);
        wg_wait<1>();
        if (w == 0) e_arrive_both(sb + B_QE + 8);
        if (!(l & 1)) bar_arrive(NB_ST, 288);
        mbar_wait(sb + B_QF + 24, 1);
        part(3, 1, 0, 4);
        part(2, 0, 0, G1);
        IDS();
        const int g = lane >> 2, qd = lane & 3;
        float rs[2][2];
#pragma unroll
        for (int i = 0; i < 4; i++) rs[i >> 1][i & 1] = lds32f(sb + RSTD + (wg * 128 + w * 16 + g + (i >> 1) * 64 + (i & 1) * 8) * 4);
        auto scale = [&](int gi, int m, float sc) {
          const float r0 = rs[m][0] * sc, r1 = rs[m][1] * sc;
#pragma unroll
          for (int i = 0; i < 16; i++) acc[m][16 * gi + i] *= (i & 2) ? r1 : r0;
        };
        auto pack_b = [&](int gi, int m, uint32_t (&t)[8]) {
#pragma unroll
          for (int i = 0; i < 8; i++) t[i] = pack2(acc[m][16 * gi + 2 * i], acc[m][16 * gi + 2 * i + 1]);
        };
        auto norm_tile = [&](int gi, int m, uint32_t (&t)[8]) { scale(gi, m, 1.f); pack_b(gi, m, t); };
        auto pack_h = [&](int gi, int m, uint32_t (&t)[8]) {
#pragma unroll
          for (int i = 0; i < 8; i++) t[i] = pack2h(acc[m][16 * gi + 2 * i], acc[m][16 * gi + 2 * i + 1]);
        };
        uint32_t q[2][2][8], qn[2][2];
        const uint32_t srow = (lane & 7) + ((lane >> 3) & 1) * 8;
        const uint32_t row0 = wg * 128 + w * 16;
        auto put_kv = [&](int h, int v, int m, const uint32_t (&t)[8]) {
          const uint32_t base = sb + ((l & 1) ? (h ? 0 : T0) + v * 16384 : (2 * h + v) * ASC + 1024) + (row0 + m * 64) * 64;
          if (!v) {
#pragma unroll
            for (int jj = 0; jj < 2; jj++) stsm4(base + srow * 64 + (((2 * jj + (lane >> 4)) ^ ((srow >> 1) & 3)) << 4), t[4 * jj], t[4 * jj + 1], t[4 * jj + 2], t[4 * jj + 3]);
          } else {
            const uint32_t ad = base + g * 64 + ((qd ^ (g >> 1)) << 4);
            sts128(ad, t[0], t[2], t[4], t[6]); sts128(ad + 512, t[1], t[3], t[5], t[7]);
          }
        };
        auto send_halo = [&](int h, int v, const uint32_t (&t)[8]) {
          unsigned long long* hp = g_halo + ((size_t)(l >> 1) * 128 + b) * 1024 + h * 512 + v * 256 + lane;
#pragma unroll
          for (int i = 0; i < 8; i++) st_tagged(hp + i * 32, t[i], ep1);
        };
        auto put_kn = [&](int h, int m, uint32_t kn) {
          if (lane == 0) g_kn[((l >> 1) * 128 + bn * 8 + bm) * 32 + 16 * h + 8 * m + wg * 4 + w] = __uint_as_float(kn);
        };
        auto conv_tile1 = [&](int h) {
          uint32_t t[8], tv[8], kn = NOT_F16;
          norm_tile(4 + h, 1, tv);
          put_kv(h, 1, 1, tv);
          scale(2 + h, 1, 1.f);
          if (h == 0) { if (G1 < 4) part(2, 0, G1, 4); if (G2) part(3, 0, 0, G2); } else if (G3 < 4) part(3, 0, G3, 4);
          if (l & 1) {
            float n[2] = {0.f, 0.f};
#pragma unroll
            for (int i = 0; i < 16; i++) n[(i >> 1) & 1] = fmaf(acc[1][32 + 16 * h + i], acc[1][32 + 16 * h + i], n[(i >> 1) & 1]);
            const float a = ((qd & 1) ? n[1] : n[0]) + __shfl_xor_sync(~0u, (qd & 1) ? n[0] : n[1], 1);
            scale(h, 1, QSCALE / 128.f);
            kn = f16_class(__reduce_max_sync(~0u, __float_as_uint(a + __shfl_xor_sync(~0u, a, 2))), K_LO);
            put_kn(h, 1, kn);
          } else scale(h, 1, 1.f);
          if (kn == NOT_F16) pack_b(2 + h, 1, t); else pack_h(2 + h, 1, t);
          put_kv(h, 0, 1, t);
          if (!(l & 1) && row0 == 176 && bm < 7) { send_halo(h, 0, t); send_halo(h, 1, tv); }
        };
        mbar_wait(sb + B_QE + 8, 1);
        wg_wait<1>();
        fence_regs(acc[1]);
        conv_tile1(0);
        if (G2 < G3) part(3, 0, G2, G3);
        if (l & 1) { fence_async_smem(); bar_arrive(NB_ST, 288); }
        conv_tile1(1);
        if (WGBAR && !(l & 1) && row0 == 48) bar_arrive(NB_KV + 12, 64);
        wg_wait<(G2 > 0) + (G2 < G3) + (G3 < 4)>();
        if (w == 0) e_arrive_both(sb + B_QE + 16);
        wg_wait<0>();
        fence_regs(acc[0]);
        if (w == 0) e_arrive_both(sb + B_QE + 24);
        bf16* const op0 = [&] { IDS(); return g_os + (size_t)(bm * 256 + row0 + (lane >> 2)) * 1024 + bn * 32 + (lane & 3) * 8; }();
        auto put_o = [&](int h, int m, const float (&o)[16], float i0, float i1) {
          bf16* op = op0 + m * 65536 + h * 512;
          const uint4 a = make_uint4(pack2(o[0] * i0, o[1] * i0), pack2(o[4] * i0, o[5] * i0), pack2(o[8] * i0, o[9] * i0), pack2(o[12] * i0, o[13] * i0));
          const uint4 c = make_uint4(pack2(o[2] * i1, o[3] * i1), pack2(o[6] * i1, o[7] * i1), pack2(o[10] * i1, o[11] * i1), pack2(o[14] * i1, o[15] * i1));
          *(uint4*)op = a; *(uint4*)(op + 8 * 1024) = c;
          const uint32_t hi = __vimax3_u16x2(__vimax3_u16x2(a.x, a.y, a.z), __vimax3_u16x2(a.w, c.x, c.y), __vmaxu2(c.z, c.w));
          const uint32_t lo = __vimax3_s16x2(__vimax3_s16x2(a.x, a.y, a.z), __vimax3_s16x2(a.w, c.x, c.y), __vmaxs2(c.z, c.w));
          return __vmaxu2(hi & 0x7FFF7FFFu, lo & 0x7FFF7FFFu);
        };
        if (!(l & 1)) {
          auto conv_kv = [&](int h) {
            uint32_t t[8];
            norm_tile(2 + h, 0, t); put_kv(h, 0, 0, t);
            norm_tile(4 + h, 0, t); put_kv(h, 1, 0, t);
          };
          conv_kv(0);
          if (!PERHEAD) conv_kv(1);
          norm_tile(0, 0, q[0][0]); pack_b(0, 1, q[0][1]);
          bar_sync(NB_SC, 256);
          const bool e = g & 1, sel = 2 * qd + (g & 1) >= g + 2, first = bm == 0 && row0 == 0;
#pragma unroll 1
          for (int h = 0; h < 2; h++) {
            if (row0 == 0) bar_sync(NB_HALO + h, 64);
            float s[2][4][4];
            uint32_t vf[2][4][4], pf[2][2][4];
#pragma unroll
            for (int m = 0; m < 2; m++)
#pragma unroll
              for (int nt = 0; nt < 4; nt++) {
                uint32_t kf[4];
                const uint32_t r = row0 + m * 64 + 8 * nt + (lane & 7);
                ldsm4(sb + 2 * h * ASC + r * 64 + (((lane >> 3) ^ ((r >> 1) & 3)) << 4), kf);
                s[m][nt][0] = s[m][nt][1] = s[m][nt][2] = s[m][nt][3] = 0.f;
                mma16816(s[m][nt], q[0][m][0], q[0][m][1], q[0][m][2], q[0][m][3], kf[0], kf[1]);
                mma16816(s[m][nt], q[0][m][4], q[0][m][5], q[0][m][6], q[0][m][7], kf[2], kf[3]);
              }
#pragma unroll
            for (int m = 0; m < 2; m++)
#pragma unroll
              for (int i = 0; i < 4; i++) {
                const uint32_t r = row0 + m * 64 + 16 * (i >> 1) + srow, ch = 2 * (i & 1) + (lane >> 4);
                ldsm4t(sb + (2 * h + 1) * ASC + r * 64 + ((ch ^ ((r >> 1) & 3)) << 4), vf[m][i]);
              }
            float va[4], vb[4], mx[4];
#pragma unroll
            for (int i = 0; i < 4; i++) {
              const int m = i >> 1, hh = i & 1;
              const float a = e ? s[m][hh + 1][2 * hh + 1] : s[m][hh + 1][2 * hh];
              const float lo = e ? s[m][hh][2 * hh + 1] : s[m][hh][2 * hh], hi = e ? s[m][hh + 2][2 * hh + 1] : s[m][hh + 2][2 * hh];
              const uint32_t t = pack2(a, sel ? lo : hi);
              const uint32_t u = pack2(bf_lo(t) * 0.17677669529663687f, bf_hi(t) * 0.17677669529663687f);
              va[i] = (m == 0 && hh == 0 && first) ? -INFINITY : bf_lo(u);
              vb[i] = (m == 0 && first && sel) ? -INFINITY : bf_hi(u);
              mx[i] = fmaxf(va[i], vb[i]);
            }
#pragma unroll
            for (int i = 0; i < 4; i++) mx[i] = fmaxf(mx[i], __shfl_xor_sync(~0u, mx[i], 1));
#pragma unroll
            for (int i = 0; i < 4; i++) mx[i] = fmaxf(mx[i], __shfl_xor_sync(~0u, mx[i], 2));
#pragma unroll
            for (int i = 0; i < 4; i++) {
              va[i] = ex2((va[i] - mx[i]) * 1.4426950408889634f); vb[i] = ex2((vb[i] - mx[i]) * 1.4426950408889634f);
              mx[i] = va[i] + vb[i];
            }
#pragma unroll
            for (int i = 0; i < 4; i++) mx[i] += __shfl_xor_sync(~0u, mx[i], 1);
#pragma unroll
            for (int i = 0; i < 4; i++) mx[i] += __shfl_xor_sync(~0u, mx[i], 2);
#pragma unroll
            for (int i = 0; i < 4; i++) {
              const int m = i >> 1, hh = i & 1;
              const float inv = rcp(mx[i]);
              const uint32_t t = pack2(va[i] * inv, vb[i] * inv);
              const uint32_t pa = e ? t << 16 : t & 0xFFFFu, pb = e ? t & 0xFFFF0000u : t >> 16;
              pf[m][hh][hh + 1] = pa; pf[m][hh][hh] = sel ? pb : 0u; pf[m][hh][hh + 2] = sel ? 0u : pb; pf[m][hh][3 - 3 * hh] = 0u;
            }
#pragma unroll
            for (int m = 0; m < 2; m++) {
              float o[4][4];
#pragma unroll
              for (int j = 0; j < 4; j++) o[j][0] = o[j][1] = o[j][2] = o[j][3] = 0.f;
#pragma unroll
              for (int i = 0; i < 4; i++) {
                const int kk = i >> 1, jj = 2 * (i & 1);
                mma16816(o[jj], pf[m][0][2 * kk], pf[m][1][2 * kk], pf[m][0][2 * kk + 1], pf[m][1][2 * kk + 1], vf[m][i][0], vf[m][i][1]);
                mma16816(o[jj + 1], pf[m][0][2 * kk], pf[m][1][2 * kk], pf[m][0][2 * kk + 1], pf[m][1][2 * kk + 1], vf[m][i][2], vf[m][i][3]);
              }
              const float of[16] = {o[0][0], o[0][1], o[0][2], o[0][3], o[1][0], o[1][1], o[1][2], o[1][3], o[2][0], o[2][1], o[2][2], o[2][3], o[3][0], o[3][1], o[3][2], o[3][3]};
              put_o(h, m, of, 1.f, 1.f);
            }
            bar_arrive(NB_SIG + 2 * h + wg, 160);
            if (h == 0) {
              if (PERHEAD) conv_kv(1);
              norm_tile(1, 0, q[0][0]); pack_b(1, 1, q[0][1]);
              if (WGBAR) bar_sync(wg ? NB_KV : NB_SC, 128); else bar_sync(NB_SC, 256);
            }
          }
        } else {
          auto conv_h = [&](int gi, int m, uint32_t (&t)[8]) {
            pack_h(gi, m, t);
            float d0[4] = {0.f, 0.f, 0.f, 0.f}, d1[4] = {0.f, 0.f, 0.f, 0.f};
            mma16816h(d0, t[0], t[1], t[2], t[3], t[0], t[2]); mma16816h(d1, t[0], t[1], t[2], t[3], t[1], t[3]);
            mma16816h(d0, t[4], t[5], t[6], t[7], t[4], t[6]); mma16816h(d1, t[4], t[5], t[6], t[7], t[5], t[7]);
            return (uint32_t)__reduce_max_sync(~0u, max(max(__float_as_int(d0[0]), __float_as_int(d0[1])), max(__float_as_int(d1[2]), __float_as_int(d1[3]))));
          };
#pragma unroll
          for (int h = 0; h < 2; h++) {
            uint32_t t[8], tv[8];
            scale(2 + h, 0, 1.f);
            const uint32_t kn = f16_class(conv_h(2 + h, 0, t), K_LO);
            if (h) {
#pragma unroll
              for (int i = 0; i < 2; i++) {
                scale(i, 0, QSCALE);
                qn[i][0] = f16_class(conv_h(i, 0, q[i][0]), K_LO);
                qn[i][1] = f16_class(conv_h(i, 1, q[i][1]), K_LO);
              }
            }
            norm_tile(4 + h, 0, tv);
            put_kv(h, 1, 0, tv);
            put_kn(h, 0, kn);
            if (kn == NOT_F16) pack_b(2 + h, 0, t);
            put_kv(h, 0, 0, t);
            fence_async_smem();
            bar_arrive(NB_KV + 12 * h, 288);
            if (h == 0) mbar_wait(sb + B_QF + 24, 1);
          }
          if (max(max(qn[0][0], qn[0][1]), max(qn[1][0], qn[1][1])) == NOT_F16) {
#pragma unroll
            for (int i = 0; i < 4; i++) if (qn[i >> 1][i & 1] == NOT_F16) pack_b(i >> 1, i & 1, q[i >> 1][i & 1]);
          }
          const bool elected = w == 0 && lane == 0;
          const uint64_t kd0 = mkdesc(sb + T0, 16, 512, 2);
          const uint64_t vd0 = mkdesc(sb + T0 + 16384, ONES - (T0 + 16384), 512, 2);
          constexpr uint64_t VSTEP = 64 - (64ull << 16);
          constexpr int RPC = NQ / 16;
          float o[2][20], SA[2][NQ / 2];
          uint32_t SB[2][NQB / 4], PA[4], PB[4];
#pragma unroll
          for (int m = 0; m < 2; m++) {
#pragma unroll
            for (int i = 0; i < NQ / 2; i++) SA[m][i] = 0.f;
#pragma unroll
            for (int i = 0; i < NQB / 4; i++) SB[m][i] = 0u;
            fence_regs(SA[m]); fence_regs(SB[m]);
          }
          auto qka = [&](int b, int k, uint64_t d, int h = 0) { QK_A(SA[b], q[h][0][4 * k], q[h][0][4 * k + 1], q[h][0][4 * k + 2], q[h][0][4 * k + 3], d + 2 * k, k ? 1 : zero); };
          auto qkb = [&](int b, int k, uint64_t d, int h = 0) { QK_B(SB[b], q[h][1][4 * k], q[h][1][4 * k + 1], q[h][1][4 * k + 2], q[h][1][4 * k + 3], d + 2 * k, k ? 1 : zero); };
          auto pv = [&](int m, const uint32_t (&Px)[4], uint64_t vd) { wgmma_m64n40k16_rs_tb(o[m], Px[0], Px[1], Px[2], Px[3], vd, 1); };
          auto clear = [&]() {
#pragma unroll
            for (int i = 0; i < 20; i++) o[0][i] = o[1][i] = 0.f;
            fence_regs(o[0]); fence_regs(o[1]);
#pragma unroll
            for (int i = 0; i < 4; i++) PA[i] = PB[i] = zero;
          };
          mbar_wait(sb + B_TF, 0);
          wg_fence(); qka(0, 0, kd0); qkb(0, 0, kd0); qka(0, 1, kd0); qkb(0, 1, kd0); wg_commit();
          clear();
          wg_wait<0>(); fence_regs(SA[0]); fence_regs(SB[0]);
#pragma unroll 1
          for (int pass = 0; pass < 2; pass++) {
            constexpr int IPS = 16 / NRB, NC = NRB / RPC, RPB = NQB / 16, RPM = RPB - (OB & 15) > RPC - (OA & 15) ? RPB - (OB & 15) : RPC - (OA & 15);
            uint32_t kc = (uint32_t)kd0, vc = (uint32_t)vd0, vp = (uint32_t)(vd0 + VSTEP);
#pragma unroll 1
            for (int it = 1; it <= 8 * IPS; it++) {
              const uint32_t sn = (it / IPS) & 3, un = it % IPS, par = (it / (4 * IPS)) & 1;
              const uint32_t kn = it < 8 * IPS ? (uint32_t)kd0 + sn * 2048 + un * (NRB * 64) : kc;
              const uint64_t hi = kd0 & 0xFFFFFFFF00000000ull, kd = hi | kc, vd = hi | vc, kdn = hi | kn, vdp = hi | vp;
              kc = kn; vp = vc + (uint32_t)(NRB * VSTEP); vc = (uint32_t)vd0 + (sn * 32 + un * NRB) * (uint32_t)VSTEP;
              bool landed = false;
#pragma unroll
              for (int r = 0; r < NRB; r++) {
                const int c = r / RPC, ro = r % RPC, cn = c + 1, cb = r / RPB, rb = r % RPB;
                if (r == NRB - RPM && !landed) mbar_wait(sb + B_TF + 8 * sn, par);
                wg_fence();
                const uint64_t kx = cn < NC ? kd + cn * NQ * 4 : kdn, vx = (r ? vd : vdp) + (r - 1) * VSTEP;
#pragma unroll
                for (int k = 0; k < 2; k++) {
                  if (ro == ((OA >> (4 * k)) & 15)) qka(cn & 1, k, kx);
                  if (rb == ((OB >> (4 * k)) & 15)) qkb((cb + 1) & 1, k, cb + 1 < NRB / RPB ? kd + (cb + 1) * NQB * 4 : kdn);
                }
                if ((ro == RPC - 1 && (OA >> 4) == ro) || (rb == RPB - 1 && (OB >> 4) == rb) || (LAG & 1)) wg_commit();
                if (LAG & 8) { pv(1, PB, vx); pv(0, PA, vx); } else { pv(0, PA, vx); pv(1, PB, vx); }
                wg_commit();
                if (r == NRB - RPM - 2) landed = mbar_test(sb + B_TF + 8 * sn, par) || it == 8 * IPS;
#pragma unroll
                for (int i = 0; i < 4; i++) {
                  if (LAG & 16) PB[i] = exp2_h2(SB[cb & 1][4 * rb + i], zero);
                  PA[i] = pack2(ex2(SA[c & 1][8 * ro + 2 * i]), ex2(SA[c & 1][8 * ro + 2 * i + 1]));
                  if (!(LAG & 16)) PB[i] = exp2_h2(SB[cb & 1][4 * rb + i], zero);
                }
                if (r == NRB - 1) wg_wait<0>(); else if (ro == RPC - 1 || rb == RPB - 1 || !(LAG & 2) || ((LAG & 4) && (ro & 1))) wg_wait<1>();
                if (ro == RPC - 1) fence_regs(SA[cn & 1]);
                if (rb == RPB - 1) fence_regs(SB[(cb + 1) & 1]);
                if (r == RPC && elected && un == 1 % IPS && it > 1) mbar_arrive(sb + B_TE + 8 * ((sn + (IPS > 1 ? 3 : 2)) & 3));
              }
            }
            int badm = 0;
            if (pass == 0) mbar_wait(sb + B_TF, 0);
            wg_fence();
            pv(0, PA, vd0 + 111 * VSTEP); pv(1, PB, vd0 + 111 * VSTEP); wg_commit();
            qka(0, 0, kd0, 1); qkb(0, 0, kd0, 1); qka(0, 1, kd0, 1); qkb(0, 1, kd0, 1); wg_commit();
            if (pass == 0) bar_sync(NB_KN + wg, 160);
            const float kmax = *(volatile float*)(smem + KMAX + 4 * pass);
            wg_wait<1>(); fence_regs(o[0]); fence_regs(o[1]);
            if (w == 0) e_arrive(sb + B_TE + 8 * 3);
#pragma unroll
            for (int m = 0; m < 2; m++) {
              if (ONECOL) { o[m][16] = __shfl_sync(~0u, o[m][16], 0, 4); o[m][18] = __shfl_sync(~0u, o[m][18], 0, 4); }
              const float of[16] = {o[m][0], o[m][1], o[m][2], o[m][3], o[m][4], o[m][5], o[m][6], o[m][7], o[m][8], o[m][9], o[m][10], o[m][11], o[m][12], o[m][13], o[m][14], o[m][15]};
              const uint32_t chk = put_o(pass, m, of, rcp(o[m][16]), rcp(o[m][18]));
              const bool bad = !(__uint_as_float(qn[0][m]) * kmax <= (m ? 0.875f * 0.875f : 112.f * 112.f)) || !(fminf(o[m][16], o[m][18]) >= 9.3e-10f) ||
                               !(o[m][16] + o[m][18] <= 3e38f) || ((chk + 0x00800080u) & 0x80008000u);
              badm |= __any_sync(~0u, bad) << m;
            }
            wg_wait<0>(); fence_regs(SA[0]); fence_regs(SB[0]);
            if (badm) {
#pragma unroll 1
              for (int m = 0; m < 2; m++) if ((badm >> m) & 1) {
                uint32_t qq[8]; float res[20];
#pragma unroll
                for (int i = 0; i < 8; i++) { qq[i] = m ? q[0][1][i] : q[0][0][i]; if ((m ? qn[0][1] : qn[0][0]) != NOT_F16) qq[i] = h2_to_bf2(qq[i]); }
                attn_slow(qq, m ? 128.f : 1.f, 2 * (cta_id() & 15) + pass, g_kn + ((l >> 1) * 128 + (cta_id() & 15) * 8) * 32 + 16 * pass, res, lane_id());
                const float of[16] = {res[0], res[1], res[2], res[3], res[4], res[5], res[6], res[7], res[8], res[9], res[10], res[11], res[12], res[13], res[14], res[15]};
                put_o(pass, m, of, rcp(res[16]), rcp(res[18]));
              }
            }
            bar_arrive(NB_SIG + 2 * pass + wg, 160);
            qn[0][0] = qn[1][0]; qn[0][1] = qn[1][1];
#pragma unroll
            for (int m = 0; m < 2; m++)
#pragma unroll
              for (int i = 0; i < 8; i++) q[0][m][i] = q[1][m][i];
            clear();
          }
        }
      }
      {
        float acc[64];
#pragma unroll
        for (int i = 0; i < 64; i++) acc[i] = 0.f;
        fence_regs(acc);
        uint32_t s = 0, lap = 0;
#pragma unroll 1
        for (int kt = 0; kt < 16; kt++) {
          mbar_wait(sb + B_PF + 8 * s, ((s < 4 ? l : 0) + lap) & 1);
          const uint64_t da = mkdesc(sb + pslot_a(s, l) + wg * 8192, 16, 1024, 1), db = mkdesc(sb + pslot_b(s, l), 8192, 1024, 1);
          wg_fence();
#pragma unroll
          for (int k = 0; k < 4; k++) wgmma_m64n128k16_ss_tb(acc, da + k * 2, db + k * 128, 1);
          wg_commit();
          wg_wait<1>();
          if (kt > 0 && w == 0) e_arrive_both(sb + B_PE + 8 * (s ? s - 1 : 5));
          if (++s == 6) { s = 0; lap++; }
        }
        IDS();
        const int g = lane >> 2, qd = lane & 3;
        const int r0 = wg * 64 + w * 16;
        const uint32_t r = r0 + (lane & 7) + ((lane >> 3) & 1) * 8;
        uint32_t x[8][4];
        mbar_wait(sb + B_RF, l & 1);
#pragma unroll
        for (int jj = 0; jj < 8; jj++) ldsm4(sb + ((l & 1) ? RES : 0) + (jj >> 2) * 16384 + r * 128 + ((((2 * jj + (lane >> 4)) & 7) ^ (r & 7)) << 4), x[jj]);
        wg_wait<0>();
        fence_regs(acc);
        bar_sync(NB_SC, 256);
        if (w == 0) e_arrive_both(sb + B_PE + 8 * 3);
        const CUtensorMap* mo = &prm.m[l == 3 ? M_OUT : M_XST];
#pragma unroll
        for (int jj = 0; jj < 8; jj++) {
#pragma unroll
          for (int i = 0; i < 4; i++) x[jj][i] = add_bf16x2(x[jj][i], pack2(acc[8 * jj + 2 * i], acc[8 * jj + 2 * i + 1]));
          stsm4(sb + (jj >> 2) * QSTG + po * 16384 + r * 128 + ((((2 * jj + (lane >> 4)) & 7) ^ (r & 7)) << 4), x[jj][0], x[jj][1], x[jj][2], x[jj][3]);
          if ((jj & 3) == 3) { fence_async_smem(); __syncwarp(); tma_st(mo, pn * 128 + (jj >> 2) * 64, pm * 128 + r0, sb + (jj >> 2) * QSTG + po * 16384 + r0 * 128); }
        }
        bulk_commit();
        if (l < 3) {
          bar_arrive(NB_X, 288);
          float s1[4] = {0.f, 0.f, 0.f, 0.f}, s2[4][4];
#pragma unroll
          for (int i = 0; i < 16; i++) s2[i >> 2][i & 3] = 0.f;
#pragma unroll
          for (int jj = 0; jj < 8; jj++) {
            mma16816(s1, x[jj][0], x[jj][1], x[jj][2], x[jj][3], 0x3f803f80u, 0x3f803f80u);
#pragma unroll
            for (int i = 0; i < 4; i++) mma1688(s2[i], x[jj][i & 2], x[jj][i | 1], x[jj][i]);
          }
          if (qd == (g >> 1)) {
            float2* sp = g_stats + pn * 2048 + pm * 128 + r0 + g;
            sp[0] = make_float2(s1[0], (g & 1) ? s2[0][1] + s2[2][1] : s2[0][0] + s2[2][0]);
            sp[8] = make_float2(s1[2], (g & 1) ? s2[1][3] + s2[3][3] : s2[1][2] + s2[3][2]);
          }
        }
        bulk_wait_n<0>();
        if (l < 3) bar_arrive(NB_X0, 320 + 32 * XLATE);
      }
    }
  }
  asm volatile("barrier.cluster.arrive.relaxed.aligned;\nbarrier.cluster.wait.aligned;" ::: "memory");
}

typedef CUresult (*EncodeFn)(CUtensorMap*, CUtensorMapDataType, cuuint32_t, void*, const cuuint64_t*, const cuuint64_t*, const cuuint32_t*,
                             const cuuint32_t*, CUtensorMapInterleave, CUtensorMapSwizzle, CUtensorMapL2promotion, CUtensorMapFloatOOBfill);

static void make_map(EncodeFn fn, CUtensorMap* m, const void* ptr, int rank, const uint64_t* dims, const uint64_t* strides, const uint32_t* box, CUtensorMapSwizzle sw) {
  cuuint64_t d[5], st[4];
  cuuint32_t bx[5], es[5];
  for (int i = 0; i < rank; i++) { d[i] = dims[i]; bx[i] = box[i]; es[i] = 1; if (i) st[i - 1] = strides[i - 1] * 2; }
  fn(m, CU_TENSOR_MAP_DATA_TYPE_BFLOAT16, rank, (void*)ptr, d, st, bx, es, CU_TENSOR_MAP_INTERLEAVE_NONE, sw,
     CU_TENSOR_MAP_L2_PROMOTION_L2_128B, CU_TENSOR_MAP_FLOAT_OOB_FILL_NONE);
}
static void map2(EncodeFn fn, CUtensorMap* m, const void* ptr, uint64_t inner, uint64_t outer, uint32_t bi, uint32_t bo, CUtensorMapSwizzle sw) {
  const uint64_t d[2] = {inner, outer}, st[1] = {inner};
  const uint32_t bx[2] = {bi, bo};
  make_map(fn, m, ptr, 2, d, st, bx, sw);
}

extern "C" void kernel_launch(void* const* d_in, const int* in_sizes, int n_in, void* d_out, int out_size) {
  (void)in_sizes; (void)n_in; (void)out_size;
  static EncodeFn enc = nullptr;
  static void *xs, *os, *kk, *vv, *ep;
  if (!enc) {
    void* p = nullptr;
    cudaDriverEntryPointQueryResult qr;
    cudaGetDriverEntryPoint("cuTensorMapEncodeTiled", &p, cudaEnableDefault, &qr);
    enc = (EncodeFn)p;
    cudaGetSymbolAddress(&xs, g_xs); cudaGetSymbolAddress(&os, g_os); cudaGetSymbolAddress(&kk, g_k); cudaGetSymbolAddress(&vv, g_v); cudaGetSymbolAddress(&ep, g_epoch);
    cudaFuncSetAttribute(fused_kernel, cudaFuncAttributeMaxDynamicSharedMemorySize, SMEM_BYTES);
  }
  Params prm;
  const CUtensorMapSwizzle S128 = CU_TENSOR_MAP_SWIZZLE_128B, S64 = CU_TENSOR_MAP_SWIZZLE_64B;
  map2(enc, &prm.m[M_X0A], d_in[0], 1024, 2048, 64, 256, S128);
  map2(enc, &prm.m[M_XSA], xs, 1024, 2048, 64, 256, S128);
  for (int t = 0; t < 2; t++) {
    const uint64_t d3[3] = {1024, 1024, 3}, s3[2] = {3072, 1024};
    const uint32_t b3[3] = {64, 64, 3};
    make_map(enc, &prm.m[M_WQA + t], d_in[1 + 3 * t], 3, d3, s3, b3, S128);
    const uint64_t d5[5] = {64, 32, 2, 16, 16}, s5[4] = {1024, 32 * 1024, 64 * 1024, 64};
    const uint32_t b5[5] = {64, 32, 1, 2, 2};
    make_map(enc, &prm.m[M_WOA + t], d_in[2 + 3 * t], 5, d5, s5, b5, S128);
    const uint64_t dr[3] = {64, 2048, 16}, sr[2] = {1024, 64};
    const uint32_t br[3] = {64, 128, 2};
    make_map(enc, &prm.m[M_X0R + t], t ? xs : d_in[0], 3, dr, sr, br, S128);
  }
  map2(enc, &prm.m[M_OS], os, 1024, 2048, 64, 64, S128);
  map2(enc, &prm.m[M_K], kk, 32, 65536, 32, 256, S64);
  map2(enc, &prm.m[M_V], vv, 32, 65536, 32, 256, S64);
  map2(enc, &prm.m[M_K4], kk, 32, 65536, 32, 64, S64);
  map2(enc, &prm.m[M_V4], vv, 32, 65536, 32, 64, S64);
  map2(enc, &prm.m[M_XSO], xs, 1024, 2048, 64, 128, S128);
  map2(enc, &prm.m[M_X0H], d_in[0], 1024, 2048, 64, 128, S128);
  map2(enc, &prm.m[M_XST], xs, 1024, 2048, 64, 16, S128);
  map2(enc, &prm.m[M_OUT], d_out, 1024, 2048, 64, 16, S128);
  prm.x0 = (const bf16*)d_in[0];
  prm.wq[0] = (const bf16*)d_in[1]; prm.wq[1] = (const bf16*)d_in[4];
  prm.wo[0] = (const bf16*)d_in[2]; prm.wo[1] = (const bf16*)d_in[5];
  prm.epoch = (uint32_t*)ep;
  prm.zero = 0;
  for (int i = 0; i < 128; i++) prm.map[i] = remap(i);
  fused_kernel<<<128, 384, SMEM_BYTES>>>(prm);
}
```

```cpp
#include <cuda_runtime.h>
#include <cuda_bf16.h>
#include <cuda.h>
#include <stdint.h>

typedef __nv_bfloat16 bf16;

__device__ __forceinline__ void wgmma_m64n192k16_ss_tb(float (&d)[96], uint64_t da, uint64_t db, int scale_d) {
  asm volatile("{\n.reg .pred p;\nsetp.ne.b32 p, %98, 0;\n"
    "wgmma.mma_async.sync.aligned.m64n192k16.f32.bf16.bf16 "
    "{%0, %1, %2, %3, %4, %5, %6, %7, %8, %9, %10, %11, %12, %13, %14, %15, "
    "%16, %17, %18, %19, %20, %21, %22, %23, %24, %25, %26, %27, %28, %29, %30, %31, "
    "%32, %33, %34, %35, %36, %37, %38, %39, %40, %41, %42, %43, %44, %45, %46, %47, "
    "%48, %49, %50, %51, %52, %53, %54, %55, %56, %57, %58, %59, %60, %61, %62, %63, "
    "%64, %65, %66, %67, %68, %69, %70, %71, %72, %73, %74, %75, %76, %77, %78, %79, "
    "%80, %81, %82, %83, %84, %85, %86, %87, %88, %89, %90, %91, %92, %93, %94, %95}, "
    "%96, %97, p, 1, 1, 0, 1;\n}\n"
    : "+f"(d[0]), "+f"(d[1]), "+f"(d[2]), "+f"(d[3]), "+f"(d[4]), "+f"(d[5]), "+f"(d[6]), "+f"(d[7]),
      "+f"(d[8]), "+f"(d[9]), "+f"(d[10]), "+f"(d[11]), "+f"(d[12]), "+f"(d[13]), "+f"(d[14]), "+f"(d[15]),
      "+f"(d[16]), "+f"(d[17]), "+f"(d[18]), "+f"(d[19]), "+f"(d[20]), "+f"(d[21]), "+f"(d[22]), "+f"(d[23]),
      "+f"(d[24]), "+f"(d[25]), "+f"(d[26]), "+f"(d[27]), "+f"(d[28]), "+f"(d[29]), "+f"(d[30]), "+f"(d[31]),
      "+f"(d[32]), "+f"(d[33]), "+f"(d[34]), "+f"(d[35]), "+f"(d[36]), "+f"(d[37]), "+f"(d[38]), "+f"(d[39]),
      "+f"(d[40]), "+f"(d[41]), "+f"(d[42]), "+f"(d[43]), "+f"(d[44]), "+f"(d[45]), "+f"(d[46]), "+f"(d[47]),
      "+f"(d[48]), "+f"(d[49]), "+f"(d[50]), "+f"(d[51]), "+f"(d[52]), "+f"(d[53]), "+f"(d[54]), "+f"(d[55]),
      "+f"(d[56]), "+f"(d[57]), "+f"(d[58]), "+f"(d[59]), "+f"(d[60]), "+f"(d[61]), "+f"(d[62]), "+f"(d[63]),
      "+f"(d[64]), "+f"(d[65]), "+f"(d[66]), "+f"(d[67]), "+f"(d[68]), "+f"(d[69]), "+f"(d[70]), "+f"(d[71]),
      "+f"(d[72]), "+f"(d[73]), "+f"(d[74]), "+f"(d[75]), "+f"(d[76]), "+f"(d[77]), "+f"(d[78]), "+f"(d[79]),
      "+f"(d[80]), "+f"(d[81]), "+f"(d[82]), "+f"(d[83]), "+f"(d[84]), "+f"(d[85]), "+f"(d[86]), "+f"(d[87]),
      "+f"(d[88]), "+f"(d[89]), "+f"(d[90]), "+f"(d[91]), "+f"(d[92]), "+f"(d[93]), "+f"(d[94]), "+f"(d[95])
    : "l"(da), "l"(db), "r"(scale_d));
}

__device__ __forceinline__ void wgmma_m64n128k16_ss_tb(float (&d)[64], uint64_t da, uint64_t db, int scale_d) {
  asm volatile("{\n.reg .pred p;\nsetp.ne.b32 p, %66, 0;\n"
    "wgmma.mma_async.sync.aligned.m64n128k16.f32.bf16.bf16 "
    "{%0, %1, %2, %3, %4, %5, %6, %7, %8, %9, %10, %11, %12, %13, %14, %15, "
    "%16, %17, %18, %19, %20, %21, %22, %23, %24, %25, %26, %27, %28, %29, %30, %31, "
    "%32, %33, %34, %35, %36, %37, %38, %39, %40, %41, %42, %43, %44, %45, %46, %47, "
    "%48, %49, %50, %51, %52, %53, %54, %55, %56, %57, %58, %59, %60, %61, %62, %63}, "
    "%64, %65, p, 1, 1, 0, 1;\n}\n"
    : "+f"(d[0]), "+f"(d[1]), "+f"(d[2]), "+f"(d[3]), "+f"(d[4]), "+f"(d[5]), "+f"(d[6]), "+f"(d[7]),
      "+f"(d[8]), "+f"(d[9]), "+f"(d[10]), "+f"(d[11]), "+f"(d[12]), "+f"(d[13]), "+f"(d[14]), "+f"(d[15]),
      "+f"(d[16]), "+f"(d[17]), "+f"(d[18]), "+f"(d[19]), "+f"(d[20]), "+f"(d[21]), "+f"(d[22]), "+f"(d[23]),
      "+f"(d[24]), "+f"(d[25]), "+f"(d[26]), "+f"(d[27]), "+f"(d[28]), "+f"(d[29]), "+f"(d[30]), "+f"(d[31]),
      "+f"(d[32]), "+f"(d[33]), "+f"(d[34]), "+f"(d[35]), "+f"(d[36]), "+f"(d[37]), "+f"(d[38]), "+f"(d[39]),
      "+f"(d[40]), "+f"(d[41]), "+f"(d[42]), "+f"(d[43]), "+f"(d[44]), "+f"(d[45]), "+f"(d[46]), "+f"(d[47]),
      "+f"(d[48]), "+f"(d[49]), "+f"(d[50]), "+f"(d[51]), "+f"(d[52]), "+f"(d[53]), "+f"(d[54]), "+f"(d[55]),
      "+f"(d[56]), "+f"(d[57]), "+f"(d[58]), "+f"(d[59]), "+f"(d[60]), "+f"(d[61]), "+f"(d[62]), "+f"(d[63])
    : "l"(da), "l"(db), "r"(scale_d));
}

__device__ __forceinline__ void wgmma_m64n32k16_rs_nb_h(float (&d)[16], uint32_t a0, uint32_t a1, uint32_t a2, uint32_t a3, uint64_t db, int scale_d) {
  asm volatile("{\n.reg .pred p;\nsetp.ne.b32 p, %21, 0;\n"
    "wgmma.mma_async.sync.aligned.m64n32k16.f32.f16.f16 "
    "{%0, %1, %2, %3, %4, %5, %6, %7, %8, %9, %10, %11, %12, %13, %14, %15}, "
    "{%16, %17, %18, %19}, %20, p, 1, 1, 0;\n}\n"
    : "+f"(d[0]), "+f"(d[1]), "+f"(d[2]), "+f"(d[3]), "+f"(d[4]), "+f"(d[5]), "+f"(d[6]), "+f"(d[7]),
      "+f"(d[8]), "+f"(d[9]), "+f"(d[10]), "+f"(d[11]), "+f"(d[12]), "+f"(d[13]), "+f"(d[14]), "+f"(d[15])
    : "r"(a0), "r"(a1), "r"(a2), "r"(a3), "l"(db), "r"(scale_d));
}

__device__ __forceinline__ void wgmma_m64n32k16_rs_nb_hh(uint32_t (&d)[8], uint32_t a0, uint32_t a1, uint32_t a2, uint32_t a3, uint64_t db, int scale_d) {
  asm volatile("{\n.reg .pred p;\nsetp.ne.b32 p, %13, 0;\n"
    "wgmma.mma_async.sync.aligned.m64n32k16.f16.f16.f16 "
    "{%0, %1, %2, %3, %4, %5, %6, %7}, "
    "{%8, %9, %10, %11}, %12, p, 1, 1, 0;\n}\n"
    : "+r"(d[0]), "+r"(d[1]), "+r"(d[2]), "+r"(d[3]), "+r"(d[4]), "+r"(d[5]), "+r"(d[6]), "+r"(d[7])
    : "r"(a0), "r"(a1), "r"(a2), "r"(a3), "l"(db), "r"(scale_d));
}

__device__ __forceinline__ void wgmma_m64n64k16_rs_nb_h(float (&d)[32], uint32_t a0, uint32_t a1, uint32_t a2, uint32_t a3, uint64_t db, int scale_d) {
  asm volatile("{\n.reg .pred p;\nsetp.ne.b32 p, %37, 0;\n"
    "wgmma.mma_async.sync.aligned.m64n64k16.f32.f16.f16 "
    "{%0, %1, %2, %3, %4, %5, %6, %7, %8, %9, %10, %11, %12, %13, %14, %15, "
    "%16, %17, %18, %19, %20, %21, %22, %23, %24, %25, %26, %27, %28, %29, %30, %31}, "
    "{%32, %33, %34, %35}, %36, p, 1, 1, 0;\n}\n"
    : "+f"(d[0]), "+f"(d[1]), "+f"(d[2]), "+f"(d[3]), "+f"(d[4]), "+f"(d[5]), "+f"(d[6]), "+f"(d[7]),
      "+f"(d[8]), "+f"(d[9]), "+f"(d[10]), "+f"(d[11]), "+f"(d[12]), "+f"(d[13]), "+f"(d[14]), "+f"(d[15]),
      "+f"(d[16]), "+f"(d[17]), "+f"(d[18]), "+f"(d[19]), "+f"(d[20]), "+f"(d[21]), "+f"(d[22]), "+f"(d[23]),
      "+f"(d[24]), "+f"(d[25]), "+f"(d[26]), "+f"(d[27]), "+f"(d[28]), "+f"(d[29]), "+f"(d[30]), "+f"(d[31])
    : "r"(a0), "r"(a1), "r"(a2), "r"(a3), "l"(db), "r"(scale_d));
}

__device__ __forceinline__ void wgmma_m64n64k16_rs_nb_hh(uint32_t (&d)[16], uint32_t a0, uint32_t a1, uint32_t a2, uint32_t a3, uint64_t db, int scale_d) {
  asm volatile("{\n.reg .pred p;\nsetp.ne.b32 p, %21, 0;\n"
    "wgmma.mma_async.sync.aligned.m64n64k16.f16.f16.f16 "
    "{%0, %1, %2, %3, %4, %5, %6, %7, %8, %9, %10, %11, %12, %13, %14, %15}, "
    "{%16, %17, %18, %19}, %20, p, 1, 1, 0;\n}\n"
    : "+r"(d[0]), "+r"(d[1]), "+r"(d[2]), "+r"(d[3]), "+r"(d[4]), "+r"(d[5]), "+r"(d[6]), "+r"(d[7]),
      "+r"(d[8]), "+r"(d[9]), "+r"(d[10]), "+r"(d[11]), "+r"(d[12]), "+r"(d[13]), "+r"(d[14]), "+r"(d[15])
    : "r"(a0), "r"(a1), "r"(a2), "r"(a3), "l"(db), "r"(scale_d));
}

__device__ __forceinline__ void wgmma_m64n40k16_rs_tb(float (&d)[20], uint32_t a0, uint32_t a1, uint32_t a2, uint32_t a3, uint64_t db, int scale_d) {
  asm volatile("{\n.reg .pred p;\nsetp.ne.b32 p, %25, 0;\n"
    "wgmma.mma_async.sync.aligned.m64n40k16.f32.bf16.bf16 "
    "{%0, %1, %2, %3, %4, %5, %6, %7, %8, %9, %10, %11, %12, %13, %14, %15, "
    "%16, %17, %18, %19}, "
    "{%20, %21, %22, %23}, %24, p, 1, 1, 1;\n}\n"
    : "+f"(d[0]), "+f"(d[1]), "+f"(d[2]), "+f"(d[3]), "+f"(d[4]), "+f"(d[5]), "+f"(d[6]), "+f"(d[7]),
      "+f"(d[8]), "+f"(d[9]), "+f"(d[10]), "+f"(d[11]), "+f"(d[12]), "+f"(d[13]), "+f"(d[14]), "+f"(d[15]),
      "+f"(d[16]), "+f"(d[17]), "+f"(d[18]), "+f"(d[19])
    : "r"(a0), "r"(a1), "r"(a2), "r"(a3), "l"(db), "r"(scale_d));
}

__device__ __forceinline__ void wgmma_m64n40k16_rs_tb_z(float (&d)[20], uint32_t a0, uint32_t a1, uint32_t a2, uint32_t a3, uint64_t db, int scale_d) {
  asm volatile("{\n.reg .pred p;\nsetp.ne.b32 p, %25, 0;\n"
    "wgmma.mma_async.sync.aligned.m64n40k16.f32.bf16.bf16 "
    "{%0, %1, %2, %3, %4, %5, %6, %7, %8, %9, %10, %11, %12, %13, %14, %15, "
    "%16, %17, %18, %19}, "
    "{%20, %21, %22, %23}, %24, p, 1, 1, 1;\n}\n"
    : "=f"(d[0]), "=f"(d[1]), "=f"(d[2]), "=f"(d[3]), "=f"(d[4]), "=f"(d[5]), "=f"(d[6]), "=f"(d[7]),
      "=f"(d[8]), "=f"(d[9]), "=f"(d[10]), "=f"(d[11]), "=f"(d[12]), "=f"(d[13]), "=f"(d[14]), "=f"(d[15]),
      "=f"(d[16]), "=f"(d[17]), "=f"(d[18]), "=f"(d[19])
    : "r"(a0), "r"(a1), "r"(a2), "r"(a3), "l"(db), "r"(scale_d));
}

__device__ __forceinline__ void wgmma_m64n32k16_rs_nb_z_h(float (&d)[16], uint32_t a0, uint32_t a1, uint32_t a2, uint32_t a3, uint64_t db, int scale_d) {
  asm volatile("{\n.reg .pred p;\nsetp.ne.b32 p, %21, 0;\n"
    "wgmma.mma_async.sync.aligned.m64n32k16.f32.f16.f16 "
    "{%0, %1, %2, %3, %4, %5, %6, %7, %8, %9, %10, %11, %12, %13, %14, %15}, "
    "{%16, %17, %18, %19}, %20, p, 1, 1, 0;\n}\n"
    : "=f"(d[0]), "=f"(d[1]), "=f"(d[2]), "=f"(d[3]), "=f"(d[4]), "=f"(d[5]), "=f"(d[6]), "=f"(d[7]),
      "=f"(d[8]), "=f"(d[9]), "=f"(d[10]), "=f"(d[11]), "=f"(d[12]), "=f"(d[13]), "=f"(d[14]), "=f"(d[15])
    : "r"(a0), "r"(a1), "r"(a2), "r"(a3), "l"(db), "r"(scale_d));
}

__device__ __forceinline__ void wgmma_m64n32k16_rs_nb_z_hh(uint32_t (&d)[8], uint32_t a0, uint32_t a1, uint32_t a2, uint32_t a3, uint64_t db, int scale_d) {
  asm volatile("{\n.reg .pred p;\nsetp.ne.b32 p, %13, 0;\n"
    "wgmma.mma_async.sync.aligned.m64n32k16.f16.f16.f16 "
    "{%0, %1, %2, %3, %4, %5, %6, %7}, "
    "{%8, %9, %10, %11}, %12, p, 1, 1, 0;\n}\n"
    : "=r"(d[0]), "=r"(d[1]), "=r"(d[2]), "=r"(d[3]), "=r"(d[4]), "=r"(d[5]), "=r"(d[6]), "=r"(d[7])
    : "r"(a0), "r"(a1), "r"(a2), "r"(a3), "l"(db), "r"(scale_d));
}

__device__ __forceinline__ void wgmma_m64n128k16_ss_tb_z(float (&d)[64], uint64_t da, uint64_t db, int scale_d) {
  asm volatile("{\n.reg .pred p;\nsetp.ne.b32 p, %66, 0;\n"
    "wgmma.mma_async.sync.aligned.m64n128k16.f32.bf16.bf16 "
    "{%0, %1, %2, %3, %4, %5, %6, %7, %8, %9, %10, %11, %12, %13, %14, %15, "
    "%16, %17, %18, %19, %20, %21, %22, %23, %24, %25, %26, %27, %28, %29, %30, %31, "
    "%32, %33, %34, %35, %36, %37, %38, %39, %40, %41, %42, %43, %44, %45, %46, %47, "
    "%48, %49, %50, %51, %52, %53, %54, %55, %56, %57, %58, %59, %60, %61, %62, %63}, "
    "%64, %65, p, 1, 1, 0, 1;\n}\n"
    : "=f"(d[0]), "=f"(d[1]), "=f"(d[2]), "=f"(d[3]), "=f"(d[4]), "=f"(d[5]), "=f"(d[6]), "=f"(d[7]),
      "=f"(d[8]), "=f"(d[9]), "=f"(d[10]), "=f"(d[11]), "=f"(d[12]), "=f"(d[13]), "=f"(d[14]), "=f"(d[15]),
      "=f"(d[16]), "=f"(d[17]), "=f"(d[18]), "=f"(d[19]), "=f"(d[20]), "=f"(d[21]), "=f"(d[22]), "=f"(d[23]),
      "=f"(d[24]), "=f"(d[25]), "=f"(d[26]), "=f"(d[27]), "=f"(d[28]), "=f"(d[29]), "=f"(d[30]), "=f"(d[31]),
      "=f"(d[32]), "=f"(d[33]), "=f"(d[34]), "=f"(d[35]), "=f"(d[36]), "=f"(d[37]), "=f"(d[38]), "=f"(d[39]),
      "=f"(d[40]), "=f"(d[41]), "=f"(d[42]), "=f"(d[43]), "=f"(d[44]), "=f"(d[45]), "=f"(d[46]), "=f"(d[47]),
      "=f"(d[48]), "=f"(d[49]), "=f"(d[50]), "=f"(d[51]), "=f"(d[52]), "=f"(d[53]), "=f"(d[54]), "=f"(d[55]),
      "=f"(d[56]), "=f"(d[57]), "=f"(d[58]), "=f"(d[59]), "=f"(d[60]), "=f"(d[61]), "=f"(d[62]), "=f"(d[63])
    : "l"(da), "l"(db), "r"(scale_d));
}

#define DEVINL __device__ __forceinline__
#define PSLEEP 0
#define XLATE 1
#define PLATE 1
#define HINT 4000
#define MWL mbar_wait_long
DEVINL void pin(uint32_t z) { asm volatile("{\n.reg .pred p;\nsetp.ne.u32 p, %0, 0;\nPIN:\n@p bra.uni PIN;\n}" ::"r"(z) : "memory"); }
DEVINL void wg_fence() { asm volatile("wgmma.fence.sync.aligned;" ::: "memory"); }
DEVINL void wg_commit() { asm volatile("wgmma.commit_group.sync.aligned;" ::: "memory"); }
template <int N> DEVINL void wg_wait() { asm volatile("wgmma.wait_group.sync.aligned %0;" ::"n"(N) : "memory"); }
DEVINL uint64_t mkdesc(uint32_t addr, uint32_t lbo, uint32_t sbo, int sw) {
  return (uint64_t)((addr & 0x3FFFF) >> 4) | ((uint64_t)(lbo >> 4) << 16) | ((uint64_t)(sbo >> 4) << 32) | ((uint64_t)sw << 62);
}
DEVINL void mbar_arrive(uint32_t bar) { asm volatile("mbarrier.arrive.shared::cta.b64 _, [%0];" ::"r"(bar) : "memory"); }
DEVINL bool mbar_try(uint32_t bar, uint32_t parity) {
  uint32_t ok;
  asm volatile("{\n.reg .pred p;\nmbarrier.try_wait.parity.shared::cta.b64 p, [%1], %2;\nselp.u32 %0, 1, 0, p;\n}" : "=r"(ok) : "r"(bar), "r"(parity) : "memory");
  return ok;
}
DEVINL bool mbar_test(uint32_t bar, uint32_t parity) {
  uint32_t ok;
  asm volatile("{\n.reg .pred p;\nmbarrier.test_wait.parity.shared::cta.b64 p, [%1], %2;\nselp.u32 %0, 1, 0, p;\n}" : "=r"(ok) : "r"(bar), "r"(parity) : "memory");
  return ok;
}
DEVINL void mbar_hint(uint32_t bar, uint32_t parity) {
#pragma unroll 1
  for (uint32_t n = 0; n < 16u; n++) if (mbar_try(bar, parity)) break;
}
DEVINL void mbar_wait(uint32_t bar, uint32_t parity) {
#pragma unroll 1
  for (uint32_t n = 0; n < 100000u; n++) if (mbar_try(bar, parity)) break;
}
DEVINL void mbar_wait_long(uint32_t bar, uint32_t parity) {
#pragma unroll 1
  for (uint32_t n = 0; n < 100000u; n++) {
    uint32_t ok;
    asm volatile("{\n.reg .pred p;\nmbarrier.try_wait.parity.shared::cta.b64 p, [%1], %2, %3;\nselp.u32 %0, 1, 0, p;\n}" : "=r"(ok) : "r"(bar), "r"(parity), "r"(HINT) : "memory");
    if (ok) break;
  }
}
#define EL(txt) "{\n.reg .pred pe;\nelect.sync _|pe, 0xffffffff;\n@pe " txt "\n}"
DEVINL void e_expect_tx(uint32_t bar, uint32_t bytes) { asm volatile(EL("mbarrier.arrive.expect_tx.shared::cta.b64 _, [%0], %1;") ::"r"(bar), "r"(bytes) : "memory"); }
DEVINL void e_init(uint32_t bar, uint32_t cnt) { asm volatile(EL("mbarrier.init.shared::cta.b64 [%0], %1;") ::"r"(bar), "r"(cnt) : "memory"); }
DEVINL void e_arrive(uint32_t bar) { asm volatile(EL("mbarrier.arrive.shared::cta.b64 _, [%0];") ::"r"(bar) : "memory"); }
DEVINL void e_red(uint32_t* p) { asm volatile(EL("red.release.gpu.global.add.u32 [%0], 1;") ::"l"(p) : "memory"); }
DEVINL void e_red_relaxed(uint32_t* p) { asm volatile(EL("red.relaxed.gpu.global.add.u32 [%0], 1;") ::"l"(p) : "memory"); }
DEVINL void tma_ld(uint32_t dst, const CUtensorMap* m, int c0, int c1, uint32_t bar) {
  asm volatile(EL("cp.async.bulk.tensor.2d.shared::cluster.global.mbarrier::complete_tx::bytes [%0], [%1, {%3, %4}], [%2];")
               ::"r"(dst), "l"(m), "r"(bar), "r"(c0), "r"(c1) : "memory");
}
DEVINL void tma_ld3(uint32_t dst, const CUtensorMap* m, int c0, int c1, int c2, uint32_t bar) {
  asm volatile(EL("cp.async.bulk.tensor.3d.shared::cluster.global.mbarrier::complete_tx::bytes [%0], [%1, {%3, %4, %5}], [%2];")
               ::"r"(dst), "l"(m), "r"(bar), "r"(c0), "r"(c1), "r"(c2) : "memory");
}
DEVINL void tma_ld5(uint32_t dst, const CUtensorMap* m, int c2, int c3, int c4, uint32_t bar) {
  asm volatile(EL("cp.async.bulk.tensor.5d.shared::cluster.global.mbarrier::complete_tx::bytes [%0], [%1, {0, 0, %3, %4, %5}], [%2];")
               ::"r"(dst), "l"(m), "r"(bar), "r"(c2), "r"(c3), "r"(c4) : "memory");
}
DEVINL void tma_ld_mc(uint32_t dst, const CUtensorMap* m, int c0, int c1, uint32_t bar) {
  asm volatile(EL("cp.async.bulk.tensor.2d.shared::cluster.global.mbarrier::complete_tx::bytes.multicast::cluster [%0], [%1, {%3, %4}], [%2], %5;")
               ::"r"(dst), "l"(m), "r"(bar), "r"(c0), "r"(c1), "h"((uint16_t)3) : "memory");
}
DEVINL void e_arrive_both(uint32_t bar) {
  asm volatile("{\n.reg .pred pe;\n.reg .b32 r0, r1;\nelect.sync _|pe, 0xffffffff;\nmapa.shared::cluster.u32 r0, %0, 0;\nmapa.shared::cluster.u32 r1, %0, 1;\n"
               "@pe mbarrier.arrive.shared::cluster.b64 _, [r0];\n@pe mbarrier.arrive.shared::cluster.b64 _, [r1];\n}" ::"r"(bar) : "memory");
}
DEVINL void push_peer(uint32_t dst, uint32_t src, uint32_t bar, uint32_t peer) {
  asm volatile("{\n.reg .pred pe;\n.reg .b32 d, b;\nelect.sync _|pe, 0xffffffff;\nmapa.shared::cluster.u32 d, %0, %3;\nmapa.shared::cluster.u32 b, %2, %3;\n"
               "@pe cp.async.bulk.shared::cluster.shared::cta.mbarrier::complete_tx::bytes [d], [%1], 16384, [b];\n}" ::"r"(dst), "r"(src), "r"(bar), "r"(peer) : "memory");
}
DEVINL void tma_st(const CUtensorMap* m, int c0, int c1, uint32_t src) {
  asm volatile(EL("cp.async.bulk.tensor.2d.global.shared::cta.bulk_group [%0, {%2, %3}], [%1];") ::"l"(m), "r"(src), "r"(c0), "r"(c1) : "memory");
}
DEVINL void bulk_commit() { asm volatile("cp.async.bulk.commit_group;" ::: "memory"); }
template <int N> DEVINL void bulk_wait_n() { asm volatile("cp.async.bulk.wait_group %0;\nbar.warp.sync 0xffffffff;" ::"n"(N) : "memory"); }
DEVINL void l2_prefetch(const void* g, uint32_t bytes) { asm volatile(EL("cp.async.bulk.prefetch.L2.global [%0], %1;") ::"l"(g), "r"(bytes) : "memory"); }
DEVINL void fence_async_smem() { asm volatile("fence.proxy.async.shared::cta;" ::: "memory"); }
DEVINL void fence_async_gl() { asm volatile("fence.proxy.async.global;" ::: "memory"); }
DEVINL void cluster_wait() { asm volatile("barrier.cluster.wait.aligned;" ::: "memory"); }
DEVINL void bar_sync(int id, int n) { asm volatile("bar.sync %0, %1;" ::"r"(id), "r"(n) : "memory"); }
DEVINL void bar_arrive(int id, int n) { asm volatile("bar.arrive %0, %1;" ::"r"(id), "r"(n) : "memory"); }
DEVINL uint32_t ld_acquire(const uint32_t* p) { uint32_t v; asm volatile("ld.acquire.gpu.global.u32 %0, [%1];" : "=r"(v) : "l"(p) : "memory"); return v; }
DEVINL void watch(const uint32_t* p, uint32_t target, uint32_t all, uint32_t tag, uint32_t slot) {
  uint32_t seen = 0;
#pragma unroll 1
  for (uint32_t n = 0; n < 200000u && seen != all; n++) {
    const uint32_t m = __ballot_sync(~0u, (int)(ld_acquire(p) - target) >= 0) & all;
    if (m != seen) { seen = m; asm volatile("st.release.cta.shared.u32 [%0], %1;" ::"r"(slot), "r"(tag << 16 | m) : "memory"); }
  }
}
template <bool RELAXED = false> DEVINL void await_bit(uint32_t slot, uint32_t tag, int j, uint32_t& rdy) {
  if ((rdy >> j) & 1) return;
#pragma unroll 1
  for (uint32_t n = 0; n < 8000000u; n++) {
    uint32_t v;
    asm volatile("ld.acquire.cta.shared.u32 %0, [%1];" : "=r"(v) : "r"(slot) : "memory");
    if ((v >> 16) == tag && ((v >> j) & 1)) { rdy = v; break; }
    if (RELAXED) __nanosleep(200); else if (PSLEEP) __nanosleep(PSLEEP);
  }
  asm volatile("fence.proxy.async.global;" ::: "memory");
}
DEVINL void poll_ge(const uint32_t* p, uint32_t target) {
#pragma unroll 1
  for (uint32_t n = 0; n < 200000u; n++) if (__all_sync(~0u, (int)(ld_acquire(p) - target) >= 0)) break;
}
DEVINL int lane_id() { int v; asm volatile("mov.u32 %0, %%laneid;" : "=r"(v)); return v; }
__host__ DEVINL int remap(int v) {
  const int c = v >> 1, u = c - 36, r = (u * 37) >> 8;
  const int L = max(c - 4 + max(r + 1, 0), (c - 4) >> 31 & (32 + 8 * c));
  return 2 * L + (v & 1);
}
DEVINL int block_id() { int v; asm volatile("mov.u32 %0, %%ctaid.x;" : "=r"(v)); return v; }
#define cta_id() prm.map[block_id()]
#define IDS() const int lane = lane_id(), b = cta_id(), bm = b >> 4, bn = b & 15, rank = b & 1, pm = 2 * bm + (bn >> 3), pn = bn & 7, po = pm & 1; \
  (void)lane; (void)bm; (void)bn; (void)rank; (void)pm; (void)pn; (void)po
DEVINL void st_tagged(unsigned long long* p, uint32_t v, uint32_t tag) {
  asm volatile("{\n.reg .b64 t;\nmov.b64 t, {%1, %2};\nst.relaxed.gpu.global.b64 [%0], t;\n}" ::"l"(p), "r"(v), "r"(tag) : "memory");
}
DEVINL float ex2(float x) { float y; asm("ex2.approx.ftz.f32 %0, %1;" : "=f"(y) : "f"(x)); return y; }
DEVINL float rcp(float x) { float y; asm("rcp.approx.ftz.f32 %0, %1;" : "=f"(y) : "f"(x)); return y; }
DEVINL uint32_t pack2(float lo, float hi) { uint32_t r; asm("cvt.rn.bf16x2.f32 %0, %1, %2;" : "=r"(r) : "f"(hi), "f"(lo)); return r; }
DEVINL float bf_lo(uint32_t w) { return __uint_as_float(w << 16); }
DEVINL float bf_hi(uint32_t w) { return __uint_as_float(w & 0xFFFF0000u); }
DEVINL float bf_round(float x) { return bf_lo(pack2(x, 0.f)); }
DEVINL uint32_t add_bf16x2(uint32_t a, uint32_t b) { uint32_t r; asm("add.rn.bf16x2 %0, %1, %2;" : "=r"(r) : "r"(a), "r"(b)); return r; }
DEVINL void stsm4(uint32_t addr, uint32_t a, uint32_t b, uint32_t c, uint32_t d) {
  asm volatile("stmatrix.sync.aligned.m8n8.x4.shared.b16 [%0], {%1, %2, %3, %4};" ::"r"(addr), "r"(a), "r"(b), "r"(c), "r"(d) : "memory");
}
DEVINL void ldsm4(uint32_t addr, uint32_t (&r)[4]) {
  asm volatile("ldmatrix.sync.aligned.m8n8.x4.shared.b16 {%0, %1, %2, %3}, [%4];" : "=r"(r[0]), "=r"(r[1]), "=r"(r[2]), "=r"(r[3]) : "r"(addr) : "memory");
}
DEVINL void ldsm4t(uint32_t addr, uint32_t (&r)[4]) {
  asm volatile("ldmatrix.sync.aligned.m8n8.x4.trans.shared.b16 {%0, %1, %2, %3}, [%4];" : "=r"(r[0]), "=r"(r[1]), "=r"(r[2]), "=r"(r[3]) : "r"(addr) : "memory");
}
DEVINL void sts128(uint32_t addr, uint32_t a, uint32_t b, uint32_t c, uint32_t d) {
  asm volatile("st.shared.v4.b32 [%0], {%1, %2, %3, %4};" ::"r"(addr), "r"(a), "r"(b), "r"(c), "r"(d) : "memory");
}
DEVINL float4 lds128f(uint32_t addr) { float4 v; asm volatile("ld.shared.v4.f32 {%0, %1, %2, %3}, [%4];" : "=f"(v.x), "=f"(v.y), "=f"(v.z), "=f"(v.w) : "r"(addr) : "memory"); return v; }
DEVINL float lds32f(uint32_t addr) { float v; asm volatile("ld.shared.f32 %0, [%1];" : "=f"(v) : "r"(addr) : "memory"); return v; }
DEVINL float2 lds64f(uint32_t addr) { float2 v; asm volatile("ld.shared.v2.f32 {%0, %1}, [%2];" : "=f"(v.x), "=f"(v.y) : "r"(addr) : "memory"); return v; }
DEVINL void mma16816(float (&d)[4], uint32_t a0, uint32_t a1, uint32_t a2, uint32_t a3, uint32_t b0, uint32_t b1) {
  asm("mma.sync.aligned.m16n8k16.row.col.f32.bf16.bf16.f32 {%0, %1, %2, %3}, {%4, %5, %6, %7}, {%8, %9}, {%0, %1, %2, %3};"
               : "+f"(d[0]), "+f"(d[1]), "+f"(d[2]), "+f"(d[3]) : "r"(a0), "r"(a1), "r"(a2), "r"(a3), "r"(b0), "r"(b1));
}
DEVINL void mma1688(float (&d)[4], uint32_t a0, uint32_t a1, uint32_t b0) {
  asm("mma.sync.aligned.m16n8k8.row.col.f32.bf16.bf16.f32 {%0, %1, %2, %3}, {%4, %5}, {%6}, {%0, %1, %2, %3};"
               : "+f"(d[0]), "+f"(d[1]), "+f"(d[2]), "+f"(d[3]) : "r"(a0), "r"(a1), "r"(b0));
}
DEVINL void mma1688h(float (&d)[4], uint32_t a0, uint32_t a1, uint32_t b0) {
  asm("mma.sync.aligned.m16n8k8.row.col.f32.f16.f16.f32 {%0, %1, %2, %3}, {%4, %5}, {%6}, {%0, %1, %2, %3};"
               : "+f"(d[0]), "+f"(d[1]), "+f"(d[2]), "+f"(d[3]) : "r"(a0), "r"(a1), "r"(b0));
}
DEVINL void mma16816h(float (&d)[4], uint32_t a0, uint32_t a1, uint32_t a2, uint32_t a3, uint32_t b0, uint32_t b1) {
  asm("mma.sync.aligned.m16n8k16.row.col.f32.f16.f16.f32 {%0, %1, %2, %3}, {%4, %5, %6, %7}, {%8, %9}, {%0, %1, %2, %3};"
               : "+f"(d[0]), "+f"(d[1]), "+f"(d[2]), "+f"(d[3]) : "r"(a0), "r"(a1), "r"(a2), "r"(a3), "r"(b0), "r"(b1));
}
template <int N> DEVINL void fence_regs(uint32_t (&d)[N]) {
#pragma unroll
  for (int i = 0; i < N; i++) asm volatile("" : "+r"(d[i])::"memory");
}
template <int N> DEVINL void fence_regs(float (&d)[N]) {
#pragma unroll
  for (int i = 0; i < N; i++) asm volatile("" : "+f"(d[i])::"memory");
}

__device__ __align__(1024) bf16 g_xs[2048 * 1024];
__device__ __align__(1024) bf16 g_os[2048 * 1024];
__device__ __align__(1024) bf16 g_k[32 * 2048 * 32];
__device__ __align__(1024) bf16 g_v[32 * 2048 * 32];
__device__ __align__(128) float2 g_stats[8 * 2048];
__device__ __align__(16) float g_csp[2 * 16 * 8 * 192];
__device__ __align__(128) float g_kn[2 * 128 * 32];
__device__ unsigned long long g_halo[2 * 128 * 32 * 32];
__device__ __align__(128) uint32_t g_cnt[256 * 32];
__device__ uint32_t g_epoch;

DEVINL uint32_t* cnt_x(int l, int bm) { return g_cnt + (l * 8 + bm) * 32; }
DEVINL uint32_t* cnt_o(int l, int pm, int h) { return g_cnt + (32 + (l * 16 + pm) * 2 + h) * 32; }
DEVINL uint32_t* cnt_kv(int lb, int bn) { return g_cnt + (160 + lb * 16 + bn) * 32; }
DEVINL uint32_t* cnt_ad(int bn) { return g_cnt + (192 + bn) * 32; }
DEVINL uint32_t* cnt_cs(int t, int bn) { return g_cnt + (208 + t * 16 + bn) * 32; }

DEVINL int qord(int i, int l, int pn) { return l == 0 ? i : i < 4 ? ((2 * pn) ^ (i & 2)) + (i & 1) : i - 4 < 2 * (pn & 6) ? i - 4 : i; }
struct Params {
  CUtensorMap m[17];
  const bf16* x0;
  const bf16* wq[2];
  const bf16* wo[2];
  uint32_t* epoch;
  uint32_t zero;
  int map[128];
};
enum { M_X0A = 0, M_XSA, M_WQA, M_WQB, M_WOA, M_WOB, M_OS, M_K, M_V, M_X0R, M_XSR, M_XSO, M_OUT, M_XST, M_X0H, M_K4, M_V4, M_COUNT };

constexpr uint32_t QSTG = 57344;
constexpr uint32_t T0 = 65536, TSTG = 32768;
constexpr uint32_t ONES = 229376;
constexpr uint32_t PSTG = 32768, RES = 196608;
constexpr uint32_t ASC = 17408;
constexpr uint32_t RSTD = 229376, MEAN = 230400, COLS = 230912, KMAX = 231680, B_QD = 231688, BARS = 232192, SMEM_BYTES = 232448;
constexpr uint32_t B_QF = BARS, B_QE = BARS + 32, B_TF = BARS + 64, B_TE = BARS + 96, B_PF = BARS + 128, B_PE = BARS + 176,
                   B_RF = BARS + 224, W_X = BARS + 232, W_O = BARS + 236, B_QL = BARS + 240, B_PA = BARS + 248;
enum { NB_ST = 1, NB_KV = 2  , NB_DONE = 3, NB_SC = 4, NB_SIG = 5  , NB_KN = 9  , NB_X = 11, NB_HALO = 12  , NB_X0 = 15 };

DEVINL uint32_t pslot_b(uint32_t s, int l) { return ((((l & 1) ? 0x320415u : 0x468795u) >> (4 * s)) & 15) * 16384u; }
DEVINL uint32_t pslot_a(uint32_t s, int l) { return ((((l & 1) ? 0xBA7896u : 0x32DCBAu) >> (4 * s)) & 15) * 16384u; }

#define G1 2
#define G2 0
#define G3 2
#define KC (11 + 2 * wg)
#define NA2 2
#define RESI 12
#define PERHEAD 1
#define PFETCH 0
#define PFW 3
#define PFI 8
#define H1ST 4
#define H1RED 5
#define WGBAR 0
#define NRB 16
#define LEAHI 2
#define ONECOL 0
#define OSD 1
#define PPEEL 0
#define NQ 32
#define OA 0x10
#define OB 0x10
#define LAG 2
#define NQB NQ
#define QK_A wgmma_m64n32k16_rs_nb_h
#define QK_B wgmma_m64n32k16_rs_nb_hh
constexpr float QSCALE = 0.17677669529663687f * 1.4426950408889634f;

DEVINL uint32_t hfma2(uint32_t a, uint32_t b, uint32_t c) { uint32_t r; asm("fma.rn.f16x2 %0, %1, %2, %3;" : "=r"(r) : "r"(a), "r"(b), "r"(c)); return r; }
DEVINL uint32_t pack2h(float lo, float hi) { uint32_t r; asm("cvt.rn.f16x2.f32 %0, %1, %2;" : "=r"(r) : "f"(hi), "f"(lo)); return r; }
DEVINL uint32_t h2_to_bf2(uint32_t h) {
  float a, b;
  asm("{\n.reg .b16 l, h;\nmov.b32 {l, h}, %2;\ncvt.f32.f16 %0, l;\ncvt.f32.f16 %1, h;\n}" : "=f"(a), "=f"(b) : "r"(h));
  return pack2(a, b);
}
DEVINL uint32_t exp2_h2(uint32_t s, uint32_t zero) {
  const uint32_t r = hfma2(s, 0x00800080u, 0x007E007Eu);
  const uint32_t g = hfma2(hfma2(r, 0xF800F800u, 0x33FD33FDu), 0x44004400u, s);
  return (LEAHI == 2 ? __funnelshift_l(r, r, 7) : LEAHI ? __funnelshift_l(zero, r, 7) : r * 128u) + hfma2(hfma2(g, g, 0x0DE10DE1u), g, 0x00300030u);
}
constexpr uint32_t NOT_F16 = 0x7FC00000u, K_LO = 0x35000000u  ;
DEVINL uint32_t f16_class(uint32_t norm2, uint32_t lo) { return norm2 - lo > 0x4E800000u - lo ? NOT_F16 : norm2; }

DEVINL void attn_slow(const uint32_t (&q)[8], float up, int head, const float* kn, float (&res)[20], int lane) {
  const int g = lane >> 2, qd = lane & 3;
  const bf16* kb = g_k + (size_t)head * 2048 * 32;
  const bf16* vb = g_v + (size_t)head * 2048 * 32;
  float o[4][4], m0 = -INFINITY, m1 = -INFINITY, l0 = 0.f, l1 = 0.f;
#pragma unroll
  for (int j = 0; j < 4; j++) { o[j][0] = o[j][1] = o[j][2] = o[j][3] = 0.f; }
#pragma unroll 1
  for (int k0 = 0; k0 < 2048; k0 += 16) {
    float s[2][4];
    const bool kh = __float_as_uint(__ldcg(kn + (k0 >> 8) * 32 + ((k0 >> 6) & 1) * 8 + ((k0 >> 7) & 1) * 4 + ((k0 >> 4) & 3))) != NOT_F16;
#pragma unroll
    for (int nt = 0; nt < 2; nt++) {
      s[nt][0] = s[nt][1] = s[nt][2] = s[nt][3] = 0.f;
      const uint32_t* kp = (const uint32_t*)(kb + (size_t)(k0 + nt * 8 + g) * 32) + qd;
      uint32_t kf[4];
#pragma unroll
      for (int i = 0; i < 4; i++) { kf[i] = __ldcg(kp + 4 * i); if (kh) kf[i] = h2_to_bf2(kf[i]); }
      mma16816(s[nt], q[0], q[1], q[2], q[3], kf[0], kf[1]);
      mma16816(s[nt], q[4], q[5], q[6], q[7], kf[2], kf[3]);
      s[nt][0] *= up; s[nt][1] *= up; s[nt][2] *= up; s[nt][3] *= up;
    }
    float a0 = fmaxf(fmaxf(s[0][0], s[0][1]), fmaxf(s[1][0], s[1][1]));
    float a1 = fmaxf(fmaxf(s[0][2], s[0][3]), fmaxf(s[1][2], s[1][3]));
    a0 = fmaxf(a0, __shfl_xor_sync(~0u, a0, 1)); a0 = fmaxf(a0, __shfl_xor_sync(~0u, a0, 2));
    a1 = fmaxf(a1, __shfl_xor_sync(~0u, a1, 1)); a1 = fmaxf(a1, __shfl_xor_sync(~0u, a1, 2));
    const float n0 = fmaxf(m0, a0), n1 = fmaxf(m1, a1);
    const float c0 = (m0 == n0) ? 1.f : ex2(m0 - n0), c1 = (m1 == n1) ? 1.f : ex2(m1 - n1);
    m0 = n0; m1 = n1;
    const uint32_t p0 = pack2(ex2(s[0][0] - n0), ex2(s[0][1] - n0)), p1 = pack2(ex2(s[0][2] - n1), ex2(s[0][3] - n1));
    const uint32_t p2 = pack2(ex2(s[1][0] - n0), ex2(s[1][1] - n0)), p3 = pack2(ex2(s[1][2] - n1), ex2(s[1][3] - n1));
    l0 = l0 * c0 + bf_lo(p0) + bf_hi(p0) + bf_lo(p2) + bf_hi(p2);
    l1 = l1 * c1 + bf_lo(p1) + bf_hi(p1) + bf_lo(p3) + bf_hi(p3);
#pragma unroll
    for (int j = 0; j < 4; j++) {
      o[j][0] *= c0; o[j][1] *= c0; o[j][2] *= c1; o[j][3] *= c1;
      const unsigned short* vp = (const unsigned short*)(vb + (size_t)(k0 + 2 * qd) * 32 + j * 8 + g);
      const uint32_t b0 = (uint32_t)__ldcg(vp) | ((uint32_t)__ldcg(vp + 32) << 16);
      const uint32_t b1 = (uint32_t)__ldcg(vp + 256) | ((uint32_t)__ldcg(vp + 288) << 16);
      mma16816(o[j], p0, p1, p2, p3, b0, b1);
    }
  }
  l0 += __shfl_xor_sync(~0u, l0, 1); l0 += __shfl_xor_sync(~0u, l0, 2);
  l1 += __shfl_xor_sync(~0u, l1, 1); l1 += __shfl_xor_sync(~0u, l1, 2);
#pragma unroll
  for (int j = 0; j < 4; j++) { res[4 * j] = o[j][0]; res[4 * j + 1] = o[j][1]; res[4 * j + 2] = o[j][2]; res[4 * j + 3] = o[j][3]; }
  res[16] = l0; res[18] = l1;
}

__global__ void __cluster_dims__(2, 1, 1) __launch_bounds__(384, 1) fused_kernel(const __grid_constant__ Params prm) {
  extern __shared__ __align__(1024) char smem[];
  const uint32_t sb = (uint32_t)__cvta_generic_to_shared(smem);
  const int tid = threadIdx.x;
  const int wid = __shfl_sync(0xffffffffu, tid >> 5, 0), wg = wid >> 2, w = wid & 3;
  const int bm = remap(blockIdx.x) >> 4, bn = remap(blockIdx.x) & 15;
  auto first_tile = [&](int kt) {
    e_expect_tx(sb + B_QF + 8 * kt, QSTG);
    tma_ld(sb + kt * QSTG, &prm.m[M_X0A], kt * 64, bm * 256, sb + B_QF + 8 * kt);
    tma_ld3(sb + kt * QSTG + 32768, &prm.m[M_WQA], bn * 64, kt * 64, 0, sb + B_QF + 8 * kt);
  };
  if (wid == 8) {
    e_init(sb + B_QF, 1);
    asm volatile("fence.mbarrier_init.release.cluster;" ::: "memory");
    first_tile(0);
  }
  if (wid < 8) {
#pragma unroll
    for (int i = 0; i < 4; i++) {
      const uint32_t cnt = (uint32_t)((i == 0 ? 0x14112140 : i == 1 ? 0x04112141 : i == 2 ? 0x14412141 : 0x24412141) >> (4 * wid)) & 7;
      if (cnt) e_init(sb + BARS + 32 * wid + 8 * i, cnt);
    }
    if (wid == 0 || wid == 7) e_init(sb + B_QD + (wid & 1) * 8, 1);
    if (tid == 255) *(uint2*)(smem + W_X) = make_uint2(0u, 0u);
    asm volatile("fence.mbarrier_init.release.cluster;" ::: "memory");
  }
  const uint32_t epoch = *(volatile uint32_t*)prm.epoch;
  __syncthreads();
  asm volatile("barrier.cluster.arrive.relaxed.aligned;" ::: "memory");

  if (wg == 2) {
    asm volatile("setmaxnreg.dec.sync.aligned.u32 56;");
    const uint32_t ep1 = epoch + 1;
    if (w == 0) {
      first_tile(1);
      mbar_wait(sb + B_QF, 0);
      first_tile(2); first_tile(3);
#pragma unroll 1
      for (int kt = 4; kt < 16; kt++) l2_prefetch(prm.wq[0] + kt * 196608 + blockIdx.x * 1536, 3072);
      cluster_wait();
#pragma unroll 1
      for (int l = 0; l < 4; l++) {
        IDS();
        const CUtensorMap* mw = &prm.m[M_WQA + (l & 1)];
        const CUtensorMap* mh = &prm.m[l == 0 ? M_X0H : M_XSO];
        const CUtensorMap* mo = &prm.m[M_WOA + (l & 1)];
        auto q_b = [&](int i) {
          const int s = i & 3;
          mbar_wait(sb + B_QE + 8 * s, ((i >> 2) & 1) ^ 1);
          e_expect_tx(sb + B_QF + 8 * s, QSTG);
          tma_ld3(sb + s * QSTG + 32768, mw, bn * 64, qord(i, l, pn) * 64, 0, sb + B_QF + 8 * s);
        };
        uint32_t rdy = l ? 0u : ~0u;
        auto q_a = [&](int i) {
          const int kt = qord(i, l, pn);
          await_bit(sb + W_X, l, kt >> 1, rdy);
          tma_ld_mc(sb + (i & 3) * QSTG + rank * 16384, mh, kt * 64, bm * 256 + rank * 128, sb + B_QF + 8 * (i & 3));
        };
        if (l > 0) {
#pragma unroll 1
          for (int i = 0; i < 4; i++) {
            const int kt = qord(i, l, pn);
            await_bit(sb + W_X, l, kt >> 1, rdy);
            e_expect_tx(sb + B_QF + 8 * i, 16384);
            tma_ld(sb + i * QSTG + (po ^ 1) * 16384, &prm.m[M_XSO], kt * 64, (pm ^ 1) * 128, sb + B_QF + 8 * i);
          }
        }
#pragma unroll 1
        for (int i = 4; i < 16; i++) {
          q_b(i); q_a(i);
          if (l == 0 && (PFW & 1) && i >= PFI && i < PFI + 4) l2_prefetch(prm.wq[1] + (blockIdx.x * 4 + i - PFI) * 6144, 12288);
          if (l < 2 && (PFW & 2) && i == PFI + 4) l2_prefetch(prm.wo[l] + blockIdx.x * 8192, 16384);
        }
        if (l & 1) {
          if (l == 3) poll_ge(cnt_ad(bn), ep1 * 16);
          const int krow = 2 * bn * 2048 + bm * 256;
          uint32_t* kvc = cnt_kv(l >> 1, bn);
#pragma unroll 1
          for (int m = 1; m >= 0; m--) {
            bar_sync(m ? NB_ST : NB_KV, 288);
#pragma unroll
            for (int i = 0; i < 4; i++) tma_st(&prm.m[M_K4 + (i >> 1)], 0, krow + (i & 1) * 128 + m * 64, sb + T0 + i * 8192 + m * 4096);
            if (m) {
              sts128(sb + ONES + lane * 32, 0x3f803f80u, 0x3f803f80u, 0x3f803f80u, 0x3f803f80u);
              sts128(sb + ONES + lane * 32 + 16, 0x3f803f80u, 0x3f803f80u, 0x3f803f80u, 0x3f803f80u);
              fence_async_smem();
              __syncwarp();
            }
          }
          e_arrive(sb + B_TF);
          bulk_commit(); bulk_wait_n<0>();
          e_red(kvc + bm);
          bar_sync(NB_KV + 12, 288);
          uint32_t seen = 0;
#pragma unroll 1
          for (int it = 1; it < 16; it++) {
            const int s = it & 3, blk = it;
            if (it == H1ST) { tma_st(&prm.m[M_K], 0, krow + 2048, sb); tma_st(&prm.m[M_V], 0, krow + 2048, sb + 16384); bulk_commit(); }
            if (it == H1RED) { bulk_wait_n<0>(); e_red(kvc + bm); }
            if (it == 12) { e_expect_tx(sb + B_RF, 32768); tma_ld3(sb + RES, &prm.m[M_XSR], 0, pm * 128, 2 * pn, sb + B_RF); }
            if (it == 2 || it == 3) mbar_wait(sb + B_TF + 8 * (it - 1), 0);
            MWL(sb + B_TE + 8 * s, ((it >> 2) & 1) ^ 1);
            if (it < 8) {
#pragma unroll 1
              for (uint32_t n = 0; n < 200000u && !((seen >> it) & 1); n++)
                seen = __ballot_sync(~0u, (int)(ld_acquire(kvc + ((bm + lane) & 7)) - (ep1 * 2 - 1)) >= 0);
              fence_async_gl();
            } else if (it == 8) { poll_ge(kvc + (lane & 7), ep1 * 2); fence_async_gl(); bar_arrive(NB_HALO, 64); }
            else if (it == 15) bar_arrive(NB_HALO + 1, 64);
            const int row = (2 * bn + (it >> 3)) * 2048 + ((bm + blk) & 7) * 256;
            e_expect_tx(sb + B_TF + 8 * s, 32768);
            tma_ld(sb + T0 + s * TSTG, &prm.m[M_K], 0, row, sb + B_TF + 8 * s);
            tma_ld(sb + T0 + s * TSTG + 16384, &prm.m[M_V], 0, row, sb + B_TF + 8 * s);
          }
        }
        auto p_b = [&](int i, uint32_t s, uint32_t par) {
          mbar_wait(sb + B_PE + 8 * s, par ^ 1);
          e_expect_tx(sb + B_PF + 8 * s, PSTG);
          tma_ld5(sb + pslot_b(s, l), mo, i >> 3, 2 * (i & 7), 2 * pn, sb + B_PF + 8 * s);
        };
        auto p_a = [&](int i, uint32_t s) {
          await_bit(sb + W_O, l + 1, i, rdy);
          tma_ld_mc(sb + pslot_a(s, l) + rank * 8192, &prm.m[M_OS], i * 64, pm * 128 + rank * 64, sb + B_PF + 8 * s);
        };
        auto p_a2 = [&](int i) {
          await_bit(sb + W_O, l + 1, i, rdy);
          tma_ld(sb + pslot_a(i, l), &prm.m[M_OS], i * 64, pm * 128, sb + B_PF + 8 * i);
          tma_ld(sb + pslot_a(i, l) + 8192, &prm.m[M_OS], i * 64, pm * 128 + 64, sb + B_PF + 8 * i);
        };
        rdy = 0;
        if (l & 1) {
#pragma unroll 1
          for (int u = 0; u < 6; u++) { const int i = (0x205413 >> (4 * u)) & 7; if (u == 4) MWL(sb + B_TE, 1); p_b(i, i, i < 4 ? 1 : 0); }
#pragma unroll 1
          for (int u = 0; u < 6; u++) {
            const int i = (0x542130 >> (4 * u)) & 7;
            if (!(u & 1)) MWL(sb + B_TE + 8 + 4 * u, 1);
            p_a2(i);
          }
        } else {
#pragma unroll 1
          for (int u = 0; u < 5; u++) { const int i = (0x32140 >> (4 * u)) & 7; if (!(u & 5)) mbar_wait(sb + B_QE + 8 + 4 * u, 1); p_b(i, i, 0); }
          mbar_wait(sb + B_QE + 24, 1);
          if (PLATE) bar_sync(NB_KN, 96);
#pragma unroll 1
          for (int i = 0; i < 4; i++) { if (i < NA2) p_a2(i); else p_a(i, i); }
          bar_sync(NB_DONE, 96);
          e_arrive_both(sb + B_PA);
          p_b(5, 5, 0);
          mbar_wait(sb + B_PA, (l >> 1) & 1);
          p_a(4, 4); p_a(5, 5);
        }
        uint32_t s = 0, lap = 1;
#pragma unroll 1
        for (int i = 6; i < 16; i++) {
          if (i == RESI && !(l & 1)) { e_expect_tx(sb + B_RF, 32768); tma_ld3(sb, &prm.m[l == 0 ? M_X0R : M_XSR], 0, pm * 128, 2 * pn, sb + B_RF); }
          p_b(i, s, ((s < 4 ? l : 0) + lap) & 1);
          p_a(i, s);
          if (++s == 6) { s = 0; lap++; }
        }
        const CUtensorMap* mn = &prm.m[M_WQA + ((l + 1) & 1)];
        if (l < 3) {
          mbar_wait(sb + B_PE + 8 * 4, 1); mbar_wait(sb + B_PE + 8 * 5, 1);
          tma_ld3(sb + 32768, mn, bn * 64, 2 * pn * 64, 0, sb + B_QL);
          mbar_wait(sb + B_PE + 8 * 0, l & 1);
          tma_ld3(sb + QSTG + 32768, mn, bn * 64, (2 * pn + 1) * 64, 0, sb + B_QL);
          mbar_wait(sb + B_PE + 8 * 1, l & 1);
          e_expect_tx(sb + B_QD, 40960);
          tma_ld3(sb + 2 * QSTG + 32768, mn, bn * 64, ((2 * pn) ^ 2) * 64, 0, sb + B_QD);
          bar_sync(NB_X, 288);
          e_expect_tx(sb + B_QL, 49152);
          e_expect_tx(sb + B_QD + 8, 40960);
          tma_ld3(sb + 3 * QSTG + 32768, mn, bn * 64, (((2 * pn) ^ 2) + 1) * 64, 0, sb + B_QD + 8);
        }
      }
      if (blockIdx.x == 0 && lane_id() == 0) *(volatile uint32_t*)prm.epoch = ep1;
    } else {
      const int hw = w - 1;
      if (hw == 1 && lane_id() < M_COUNT) asm volatile("prefetch.tensormap [%0];" ::"l"(&prm.m[lane_id()]) : "memory");
      cluster_wait();
      mbar_wait(sb + B_QF, 0);
#pragma unroll 1
      for (int l = 0; l < 4; l++) {
        IDS();
        if (hw == 2 && l > 0) watch(cnt_x(l, bm) + (lane & 7), ep1 * 2, 0xFFu, l, sb + W_X);
        if (l == 0) {
#pragma unroll 1
          for (int r = 2 * hw; r < 16; r += 6) {
            const uint4* p = (const uint4*)(prm.x0 + (size_t)(b * 16 + r) * 1024) + lane;
            float s1[2] = {0.f, 0.f}, s2[2] = {0.f, 0.f};
#pragma unroll
            for (int i = 0; i < 8; i++) {
              const uint4 v = __ldg(p + 32 * i);
              const uint32_t u[4] = {v.x, v.y, v.z, v.w};
#pragma unroll
              for (int k = 0; k < 4; k++) { const float a = bf_lo(u[k]), c = bf_hi(u[k]); s1[i >> 2] += a + c; s2[i >> 2] = fmaf(a, a, fmaf(c, c, s2[i >> 2])); }
            }
#pragma unroll
            for (int o = 16; o; o >>= 1)
#pragma unroll
              for (int rr = 0; rr < 2; rr++) { s1[rr] += __shfl_xor_sync(~0u, s1[rr], o); s2[rr] += __shfl_xor_sync(~0u, s2[rr], o); }
            if (lane == 0) *(float4*)&g_stats[b * 16 + r] = make_float4(s1[0], s2[0], s1[1], s2[1]);
          }
        }
        if (l == 1) { uint32_t rdy = 0; await_bit<true>(sb + W_X, 1, pn, rdy); mbar_hint(sb + B_QF + 8, 0); }
        if (l < 2) {
          float cs[8];
#pragma unroll
          for (int i = 0; i < 8; i++) cs[i] = 0.f;
          const uint4* wp = (const uint4*)(prm.wq[l] + (size_t)(bm * 128 + (lane >> 3)) * 3072 + hw * 1024 + bn * 64) + (lane & 7);
#pragma unroll 8
          for (int i = 0; i < 32; i++) {
            const uint4 v = __ldg(wp + (size_t)i * 4 * 384);
            cs[0] += bf_lo(v.x); cs[1] += bf_hi(v.x); cs[2] += bf_lo(v.y); cs[3] += bf_hi(v.y);
            cs[4] += bf_lo(v.z); cs[5] += bf_hi(v.z); cs[6] += bf_lo(v.w); cs[7] += bf_hi(v.w);
          }
#pragma unroll
          for (int i = 0; i < 8; i++) { cs[i] += __shfl_xor_sync(~0u, cs[i], 8); cs[i] += __shfl_xor_sync(~0u, cs[i], 16); }
          if (lane < 8) {
            float4* d = (float4*)(g_csp + ((l * 16 + bn) * 8 + bm) * 192 + hw * 64 + lane * 8);
            d[0] = make_float4(cs[0], cs[1], cs[2], cs[3]); d[1] = make_float4(cs[4], cs[5], cs[6], cs[7]);
          }
          __syncwarp();
          asm volatile("fence.acq_rel.gpu;" ::: "memory");
          e_red_relaxed(cnt_cs(l, bn));
          if (l == 0) e_red_relaxed(cnt_x(0, bm) + pn);
          poll_ge(lane < 8 && l == 0 ? cnt_x(0, bm) + lane : cnt_cs(l, bn), ep1 * (lane < 8 && l == 0 ? 6 : 24));
        }
        if (l > 0) {
          uint32_t rdy = 0;
#pragma unroll 1
          for (int j = 0; j < 8; j++) await_bit<true>(sb + W_X, l, j, rdy);
        }
#pragma unroll 1
        for (int it = hw * 32 + lane; it < 176; it += 96) {
          const bool rows = it < 128;
          const float4* p = rows ? (const float4*)(g_stats + bm * 256) + it : (const float4*)(g_csp + ((l & 1) * 16 + bn) * 8 * 192) + (it - 128);
          const int stride = rows ? 1024 : 48, np = rows && l == 0 ? 1 : 8;
          float4 a = make_float4(0.f, 0.f, 0.f, 0.f);
#pragma unroll
          for (int k = 0; k < 8; k++) if (k < np) { const float4 v = __ldcg(p + k * stride); a.x += v.x; a.y += v.y; a.z += v.z; a.w += v.w; }
          if (rows) {
            const float m0 = a.x * (1.f / 1024.f), m1 = a.z * (1.f / 1024.f);
            const float v0 = fmaxf(a.y * (1.f / 1024.f) - m0 * m0, 0.f), v1 = fmaxf(a.w * (1.f / 1024.f) - m1 * m1, 0.f);
            const float r0 = __fdividef(1.f, bf_round(sqrtf(bf_round(bf_round(v0) + 1e-5f)))), r1 = __fdividef(1.f, bf_round(sqrtf(bf_round(bf_round(v1) + 1e-5f))));
            *(float2*)(smem + RSTD + it * 8) = make_float2(r0, r1);
            *(uint32_t*)(smem + MEAN + it * 4) = pack2(-m0, -m1);
          } else {
            float2* d = (float2*)(smem + COLS) + ((it - 128) >> 2) * 8 + (it & 1) * 4 + ((it >> 1) & 1);
            d[0] = make_float2(a.y, a.x); d[2] = make_float2(a.w, a.z);
          }
        }
        __syncwarp();
        if (lane == 0) asm volatile("red.release.cta.shared.add.u32 [%0], 0x100;" ::"r"(sb + W_X) : "memory");
        if (hw == 2) {
          if (!(l & 1)) {
            bar_sync(NB_ST, 288);
            const volatile unsigned long long* hp = g_halo + ((size_t)(l >> 1) * 128 + b - 16) * 1024 + lane;
#pragma unroll 1
            for (int h = 0; h < 2; h++) {
              uint32_t t[16];
#pragma unroll
              for (int i = 0; i < 16; i++) t[i] = 0;
#pragma unroll 1
              for (uint32_t n = bm ? 0 : 100000u; n < 100000u; n++) {
                uint32_t miss = 0;
#pragma unroll
                for (int i = 0; i < 16; i++) {
                  const unsigned long long v = hp[h * 512 + i * 32];
                  t[i] = (uint32_t)v; miss |= (uint32_t)(v >> 32) ^ ep1;
                }
                if (__all_sync(~0u, !miss)) break;
              }
              const uint32_t r = (lane & 7) + ((lane >> 3) & 1) * 8, rv = lane >> 2;
#pragma unroll
              for (int jj = 0; jj < 2; jj++) stsm4(sb + 2 * h * ASC + r * 64 + (((2 * jj + (lane >> 4)) ^ ((r >> 1) & 3)) << 4), t[4 * jj], t[4 * jj + 1], t[4 * jj + 2], t[4 * jj + 3]);
              const uint32_t ad = sb + (2 * h + 1) * ASC + rv * 64 + (((lane & 3) ^ ((rv >> 1) & 3)) << 4);
              sts128(ad, t[8], t[10], t[12], t[14]); sts128(ad + 512, t[9], t[11], t[13], t[15]);
              bar_arrive(NB_HALO + h, 64);
            }
          } else {
            bar_sync(NB_HALO, 64);
            const uint4* kp = (const uint4*)(g_kn + ((l >> 1) * 128 + bn * 8) * 32) + 2 * lane;
            const uint4 v = __ldcg(kp), u = __ldcg(kp + 1);
            const uint32_t mx = max(max(max(v.x, v.y), max(v.z, v.w)), max(max(u.x, u.y), max(u.z, u.w)));
            const uint32_t m0 = __reduce_max_sync(~0u, (lane & 2) ? 0u : mx), m1 = __reduce_max_sync(~0u, (lane & 2) ? mx : 0u);
            if (lane == 0) *(uint2*)(smem + KMAX) = make_uint2(m0, m1);
            __syncwarp();
            bar_arrive(NB_KN, 160); bar_arrive(NB_KN + 1, 160);
            bar_sync(NB_HALO + 1, 64);
            watch(cnt_o(l, pm, 0) + (lane & 7), ep1 * 2, 0xFFu, l + 1, sb + W_O);
          }
        } else {
          bar_sync(NB_SIG + 2 * hw, 160); bar_sync(NB_SIG + 2 * hw + 1, 160);
          if (!(l & 1)) bar_arrive(NB_DONE, 96);
          if (hw == (l & 1)) bar_arrive((l & 1) ? NB_DONE : NB_KN, (l & 1) ? 64 : 64 + 32 * PLATE);
          asm volatile("fence.acq_rel.gpu;" ::: "memory");
          e_red_relaxed(cnt_o(l, 2 * bm, hw) + (bn >> 1));
          e_red_relaxed(cnt_o(l, 2 * bm + 1, hw) + (bn >> 1));
          if (hw == 1 && l == 1) { e_red_relaxed(cnt_ad(bn)); e_red_relaxed(cnt_ad(bn)); }
        }
        if (hw == 2) { bar_sync((l & 1) ? NB_DONE : NB_KN, (l & 1) ? 64 : 64 + 32 * PLATE); watch(cnt_o(l, pm, (lane >> 3) & 1) + (lane & 7), ep1 * 2, 0xFFFFu, l + 1, sb + W_O); }
        if (hw < 2 + XLATE && l < 3) {
          bar_sync(NB_X0, 320 + 32 * XLATE);
          if (hw == 0) {
            e_red(cnt_x(l + 1, bm) + pn);
          } else if (hw == 1) {
            mbar_wait(sb + B_PE + 8 * 3, l & 1);
            push_peer(sb + 2 * QSTG + po * 16384, sb + po * 16384, sb + B_QD, rank ^ 1);
            push_peer(sb + 3 * QSTG + po * 16384, sb + QSTG + po * 16384, sb + B_QD + 8, rank ^ 1);
          }
        }
      }
    }
  } else {
    asm volatile("setmaxnreg.inc.sync.aligned.u32 224;");
    const uint32_t zero = prm.zero;
    cluster_wait();
    const uint32_t ep1 = __shfl_sync(~0u, epoch + 1, 0);
#pragma unroll 1
    for (int l = 0; l < 4; l++) {
      {
        float acc[2][96];
#pragma unroll
        for (int i = 0; i < 96; i++) { acc[0][i] = 0.f; acc[1][i] = 0.f; }
        fence_regs(acc[0]); fence_regs(acc[1]);
        const bool early = l > 0 && wg == ((cta_id() >> 3) & 1);
#pragma unroll 1
        for (int kt = 0; kt < 14; kt++) {
          const int s = kt & 3;
          if (l > 0 && kt < 4 && kt != 1) mbar_wait(sb + (kt ? B_QD - 16 + 8 * kt : B_QL), (l + 1) & 1);
          if (!(early && kt < 4)) mbar_wait(sb + B_QF + 8 * s, (kt >> 2) & 1);
          const uint64_t da = mkdesc(sb + s * QSTG + wg * 16384, 16, 1024, 1), db = mkdesc(sb + s * QSTG + 32768, 8192, 1024, 1);
          wg_fence();
#pragma unroll
          for (int k = 0; k < 4; k++)
#pragma unroll
            for (int m = 0; m < 2; m++) wgmma_m64n192k16_ss_tb(acc[m], da + m * 512 + k * 2, db + k * 128, 1);
          wg_commit();
          wg_wait<1>();
          if (early && kt < 5) {
#pragma unroll 1
            for (int i = kt == 3 ? 0 : 3; i < kt; i++) { mbar_wait(sb + B_QF + 8 * i, 0); if (w == 0) e_arrive_both(sb + B_QE + 8 * i); }
          } else if (kt > 0 && w == 0) e_arrive_both(sb + B_QE + 8 * ((kt - 1) & 3));
          if (kt == KC) {
#pragma unroll 1
            for (uint32_t n = 0; n < 4000000u; n++) {
              uint32_t v;
              asm volatile("ld.acquire.cta.shared.u32 %0, [%1];" : "=r"(v) : "r"(sb + W_X) : "memory");
              if ((v >> 8) == (uint32_t)(l * 256 + 3)) break;
            }
            const int lane = lane_id();
            float nm[4];
#pragma unroll
            for (int i = 0; i < 4; i++) nm[i] = bf_lo(*(volatile unsigned short*)(smem + MEAN + (wg * 128 + w * 16 + (lane >> 2) + (i >> 1) * 64 + (i & 1) * 8) * 2));
            wg_wait<0>();
            fence_regs(acc[0]); fence_regs(acc[1]);
#pragma unroll
            for (int j = 0; j < 12; j++) {
              const float4 c = lds128f(sb + COLS + j * 64 + (lane & 3) * 16);
#pragma unroll
              for (int m = 0; m < 2; m++) {
                float* a = &acc[m][8 * j];
                a[0] = fmaf(nm[2 * m], c.y, a[0]); a[1] = fmaf(nm[2 * m], c.x, a[1]); a[2] = fmaf(nm[2 * m + 1], c.y, a[2]); a[3] = fmaf(nm[2 * m + 1], c.x, a[3]);
                a[4] = fmaf(nm[2 * m], c.w, a[4]); a[5] = fmaf(nm[2 * m], c.z, a[5]); a[6] = fmaf(nm[2 * m + 1], c.w, a[6]); a[7] = fmaf(nm[2 * m + 1], c.z, a[7]);
              }
            }
            fence_regs(acc[0]); fence_regs(acc[1]);
          }
        }
        auto part = [&](int s, int m, int k0, int k1) {
          const uint64_t da = mkdesc(sb + s * QSTG + wg * 16384 + m * 8192, 16, 1024, 1), db = mkdesc(sb + s * QSTG + 32768, 8192, 1024, 1);
          pin(zero);
          wg_fence();
#pragma unroll
          for (int k = k0; k < k1; k++) wgmma_m64n192k16_ss_tb(acc[m], da + k * 2, db + k * 128, 1);
          wg_commit();
          pin(zero);
        };
        mbar_wait(sb + B_QF + 16, 1);
        part(2, 1, 0, 4);
        wg_wait<1>();
        if (w == 0) e_arrive_both(sb + B_QE + 8);
        if (!(l & 1)) bar_arrive(NB_ST, 288);
        mbar_wait(sb + B_QF + 24, 1);
        part(3, 1, 0, 4);
        part(2, 0, 0, G1);
        IDS();
        const int g = lane >> 2, qd = lane & 3;
        float rs[2][2];
#pragma unroll
        for (int i = 0; i < 4; i++) rs[i >> 1][i & 1] = lds32f(sb + RSTD + (wg * 128 + w * 16 + g + (i >> 1) * 64 + (i & 1) * 8) * 4);
        auto scale = [&](int gi, int m, float sc) {
          const float r0 = rs[m][0] * sc, r1 = rs[m][1] * sc;
#pragma unroll
          for (int i = 0; i < 16; i++) acc[m][16 * gi + i] *= (i & 2) ? r1 : r0;
        };
        auto pack_b = [&](int gi, int m, uint32_t (&t)[8]) {
#pragma unroll
          for (int i = 0; i < 8; i++) t[i] = pack2(acc[m][16 * gi + 2 * i], acc[m][16 * gi + 2 * i + 1]);
        };
        auto norm_tile = [&](int gi, int m, uint32_t (&t)[8]) { scale(gi, m, 1.f); pack_b(gi, m, t); };
        auto pack_h = [&](int gi, int m, uint32_t (&t)[8]) {
#pragma unroll
          for (int i = 0; i < 8; i++) t[i] = pack2h(acc[m][16 * gi + 2 * i], acc[m][16 * gi + 2 * i + 1]);
        };
        uint32_t q[2][2][8], qn[2][2];
        const uint32_t srow = (lane & 7) + ((lane >> 3) & 1) * 8;
        const uint32_t row0 = wg * 128 + w * 16;
        auto put_kv = [&](int h, int v, int m, const uint32_t (&t)[8]) {
          const uint32_t base = sb + ((l & 1) ? (h ? 0 : T0) + v * 16384 : (2 * h + v) * ASC + 1024) + (row0 + m * 64) * 64;
          if (!v) {
#pragma unroll
            for (int jj = 0; jj < 2; jj++) stsm4(base + srow * 64 + (((2 * jj + (lane >> 4)) ^ ((srow >> 1) & 3)) << 4), t[4 * jj], t[4 * jj + 1], t[4 * jj + 2], t[4 * jj + 3]);
          } else {
            const uint32_t ad = base + g * 64 + ((qd ^ (g >> 1)) << 4);
            sts128(ad, t[0], t[2], t[4], t[6]); sts128(ad + 512, t[1], t[3], t[5], t[7]);
          }
        };
        auto send_halo = [&](int h, int v, const uint32_t (&t)[8]) {
          unsigned long long* hp = g_halo + ((size_t)(l >> 1) * 128 + b) * 1024 + h * 512 + v * 256 + lane;
#pragma unroll
          for (int i = 0; i < 8; i++) st_tagged(hp + i * 32, t[i], ep1);
        };
        auto put_kn = [&](int h, int m, uint32_t kn) {
          if (lane == 0) g_kn[((l >> 1) * 128 + bn * 8 + bm) * 32 + 16 * h + 8 * m + wg * 4 + w] = __uint_as_float(kn);
        };
        auto conv_tile1 = [&](int h) {
          uint32_t t[8], tv[8], kn = NOT_F16;
          norm_tile(4 + h, 1, tv);
          put_kv(h, 1, 1, tv);
          scale(2 + h, 1, 1.f);
          if (h == 0) { if (G1 < 4) part(2, 0, G1, 4); if (G2) part(3, 0, 0, G2); } else if (G3 < 4) part(3, 0, G3, 4);
          if (l & 1) {
            float n[2] = {0.f, 0.f};
#pragma unroll
            for (int i = 0; i < 16; i++) n[(i >> 1) & 1] = fmaf(acc[1][32 + 16 * h + i], acc[1][32 + 16 * h + i], n[(i >> 1) & 1]);
            const float a = ((qd & 1) ? n[1] : n[0]) + __shfl_xor_sync(~0u, (qd & 1) ? n[0] : n[1], 1);
            scale(h, 1, QSCALE / 128.f);
            kn = f16_class(__reduce_max_sync(~0u, __float_as_uint(a + __shfl_xor_sync(~0u, a, 2))), K_LO);
            put_kn(h, 1, kn);
          } else scale(h, 1, 1.f);
          if (kn == NOT_F16) pack_b(2 + h, 1, t); else pack_h(2 + h, 1, t);
          put_kv(h, 0, 1, t);
          if (!(l & 1) && row0 == 176 && bm < 7) { send_halo(h, 0, t); send_halo(h, 1, tv); }
        };
        mbar_wait(sb + B_QE + 8, 1);
        wg_wait<1>();
        fence_regs(acc[1]);
        conv_tile1(0);
        if (G2 < G3) part(3, 0, G2, G3);
        if (l & 1) { fence_async_smem(); bar_arrive(NB_ST, 288); }
        conv_tile1(1);
        if (WGBAR && !(l & 1) && row0 == 48) bar_arrive(NB_KV + 12, 64);
        wg_wait<(G2 > 0) + (G2 < G3) + (G3 < 4)>();
        if (w == 0) e_arrive_both(sb + B_QE + 16);
        wg_wait<0>();
        fence_regs(acc[0]);
        if (w == 0) e_arrive_both(sb + B_QE + 24);
        bf16* const op0 = [&] { IDS(); return g_os + (size_t)(bm * 256 + row0 + (lane >> 2)) * 1024 + bn * 32 + (lane & 3) * 8; }();
        auto put_o = [&](int h, int m, const float (&o)[16], float i0, float i1) {
          bf16* op = op0 + m * 65536 + h * 512;
          const uint4 a = make_uint4(pack2(o[0] * i0, o[1] * i0), pack2(o[4] * i0, o[5] * i0), pack2(o[8] * i0, o[9] * i0), pack2(o[12] * i0, o[13] * i0));
          const uint4 c = make_uint4(pack2(o[2] * i1, o[3] * i1), pack2(o[6] * i1, o[7] * i1), pack2(o[10] * i1, o[11] * i1), pack2(o[14] * i1, o[15] * i1));
          *(uint4*)op = a; *(uint4*)(op + 8 * 1024) = c;
          const uint32_t hi = __vimax3_u16x2(__vimax3_u16x2(a.x, a.y, a.z), __vimax3_u16x2(a.w, c.x, c.y), __vmaxu2(c.z, c.w));
          const uint32_t lo = __vimax3_s16x2(__vimax3_s16x2(a.x, a.y, a.z), __vimax3_s16x2(a.w, c.x, c.y), __vmaxs2(c.z, c.w));
          return __vmaxu2(hi & 0x7FFF7FFFu, lo & 0x7FFF7FFFu);
        };
        if (!(l & 1)) {
          auto conv_kv = [&](int h) {
            uint32_t t[8];
            norm_tile(2 + h, 0, t); put_kv(h, 0, 0, t);
            norm_tile(4 + h, 0, t); put_kv(h, 1, 0, t);
          };
          conv_kv(0);
          if (!PERHEAD) conv_kv(1);
          norm_tile(0, 0, q[0][0]); pack_b(0, 1, q[0][1]);
          bar_sync(NB_SC, 256);
          const bool e = g & 1, sel = 2 * qd + (g & 1) >= g + 2, first = bm == 0 && row0 == 0;
#pragma unroll 1
          for (int h = 0; h < 2; h++) {
            if (row0 == 0) bar_sync(NB_HALO + h, 64);
            float s[2][4][4];
            uint32_t vf[2][4][4], pf[2][2][4];
#pragma unroll
            for (int m = 0; m < 2; m++)
#pragma unroll
              for (int nt = 0; nt < 4; nt++) {
                uint32_t kf[4];
                const uint32_t r = row0 + m * 64 + 8 * nt + (lane & 7);
                ldsm4(sb + 2 * h * ASC + r * 64 + (((lane >> 3) ^ ((r >> 1) & 3)) << 4), kf);
                s[m][nt][0] = s[m][nt][1] = s[m][nt][2] = s[m][nt][3] = 0.f;
                mma16816(s[m][nt], q[0][m][0], q[0][m][1], q[0][m][2], q[0][m][3], kf[0], kf[1]);
                mma16816(s[m][nt], q[0][m][4], q[0][m][5], q[0][m][6], q[0][m][7], kf[2], kf[3]);
              }
#pragma unroll
            for (int m = 0; m < 2; m++)
#pragma unroll
              for (int i = 0; i < 4; i++) {
                const uint32_t r = row0 + m * 64 + 16 * (i >> 1) + srow, ch = 2 * (i & 1) + (lane >> 4);
                ldsm4t(sb + (2 * h + 1) * ASC + r * 64 + ((ch ^ ((r >> 1) & 3)) << 4), vf[m][i]);
              }
            float va[4], vb[4], mx[4];
#pragma unroll
            for (int i = 0; i < 4; i++) {
              const int m = i >> 1, hh = i & 1;
              const float a = e ? s[m][hh + 1][2 * hh + 1] : s[m][hh + 1][2 * hh];
              const float lo = e ? s[m][hh][2 * hh + 1] : s[m][hh][2 * hh], hi = e ? s[m][hh + 2][2 * hh + 1] : s[m][hh + 2][2 * hh];
              const uint32_t t = pack2(a, sel ? lo : hi);
              const uint32_t u = pack2(bf_lo(t) * 0.17677669529663687f, bf_hi(t) * 0.17677669529663687f);
              va[i] = (m == 0 && hh == 0 && first) ? -INFINITY : bf_lo(u);
              vb[i] = (m == 0 && first && sel) ? -INFINITY : bf_hi(u);
              mx[i] = fmaxf(va[i], vb[i]);
            }
#pragma unroll
            for (int i = 0; i < 4; i++) mx[i] = fmaxf(mx[i], __shfl_xor_sync(~0u, mx[i], 1));
#pragma unroll
            for (int i = 0; i < 4; i++) mx[i] = fmaxf(mx[i], __shfl_xor_sync(~0u, mx[i], 2));
#pragma unroll
            for (int i = 0; i < 4; i++) {
              va[i] = ex2((va[i] - mx[i]) * 1.4426950408889634f); vb[i] = ex2((vb[i] - mx[i]) * 1.4426950408889634f);
              mx[i] = va[i] + vb[i];
            }
#pragma unroll
            for (int i = 0; i < 4; i++) mx[i] += __shfl_xor_sync(~0u, mx[i], 1);
#pragma unroll
            for (int i = 0; i < 4; i++) mx[i] += __shfl_xor_sync(~0u, mx[i], 2);
#pragma unroll
            for (int i = 0; i < 4; i++) {
              const int m = i >> 1, hh = i & 1;
              const float inv = rcp(mx[i]);
              const uint32_t t = pack2(va[i] * inv, vb[i] * inv);
              const uint32_t pa = e ? t << 16 : t & 0xFFFFu, pb = e ? t & 0xFFFF0000u : t >> 16;
              pf[m][hh][hh + 1] = pa; pf[m][hh][hh] = sel ? pb : 0u; pf[m][hh][hh + 2] = sel ? 0u : pb; pf[m][hh][3 - 3 * hh] = 0u;
            }
#pragma unroll
            for (int m = 0; m < 2; m++) {
              float o[4][4];
#pragma unroll
              for (int j = 0; j < 4; j++) o[j][0] = o[j][1] = o[j][2] = o[j][3] = 0.f;
#pragma unroll
              for (int i = 0; i < 4; i++) {
                const int kk = i >> 1, jj = 2 * (i & 1);
                mma16816(o[jj], pf[m][0][2 * kk], pf[m][1][2 * kk], pf[m][0][2 * kk + 1], pf[m][1][2 * kk + 1], vf[m][i][0], vf[m][i][1]);
                mma16816(o[jj + 1], pf[m][0][2 * kk], pf[m][1][2 * kk], pf[m][0][2 * kk + 1], pf[m][1][2 * kk + 1], vf[m][i][2], vf[m][i][3]);
              }
              const float of[16] = {o[0][0], o[0][1], o[0][2], o[0][3], o[1][0], o[1][1], o[1][2], o[1][3], o[2][0], o[2][1], o[2][2], o[2][3], o[3][0], o[3][1], o[3][2], o[3][3]};
              put_o(h, m, of, 1.f, 1.f);
            }
            bar_arrive(NB_SIG + 2 * h + wg, 160);
            if (h == 0) {
              if (PERHEAD) conv_kv(1);
              norm_tile(1, 0, q[0][0]); pack_b(1, 1, q[0][1]);
              if (WGBAR) bar_sync(wg ? NB_KV : NB_SC, 128); else bar_sync(NB_SC, 256);
            }
          }
        } else {
          auto conv_h = [&](int gi, int m, uint32_t (&t)[8]) {
            pack_h(gi, m, t);
            float d0[4] = {0.f, 0.f, 0.f, 0.f}, d1[4] = {0.f, 0.f, 0.f, 0.f};
            if (gi == 2) {
              mma16816h(d0, t[0], t[1], t[2], t[3], t[0], t[2]); mma16816h(d1, t[0], t[1], t[2], t[3], t[1], t[3]);
              mma16816h(d0, t[4], t[5], t[6], t[7], t[4], t[6]); mma16816h(d1, t[4], t[5], t[6], t[7], t[5], t[7]);
            } else {
#pragma unroll
              for (int i = 0; i < 8; i += 2) { mma1688h(d0, t[i], t[i + 1], t[i]); mma1688h(d1, t[i], t[i + 1], t[i + 1]); }
            }
            return f16_class(__reduce_max_sync(~0u, max(max(__float_as_int(d0[0]), __float_as_int(d0[1])), max(__float_as_int(d1[2]), __float_as_int(d1[3])))), K_LO);
          };
          uint32_t tk[8], tv[8];
          scale(2, 0, 1.f);
          uint32_t kn = conv_h(2, 0, tk);
          norm_tile(4, 0, tv);
          put_kv(0, 1, 0, tv);
          put_kn(0, 0, kn);
          if (kn == NOT_F16) pack_b(2, 0, tk);
          put_kv(0, 0, 0, tk);
          fence_async_smem();
          bar_arrive(NB_KV, 288);
          mbar_wait(sb + B_QF + 24, 1);
          scale(3, 0, 1.f); scale(0, 0, QSCALE); scale(1, 0, QSCALE);
          kn = conv_h(3, 0, tk);
#pragma unroll
          for (int i = 0; i < 4; i++) qn[i >> 1][i & 1] = conv_h(i >> 1, i & 1, q[i >> 1][i & 1]);
          norm_tile(5, 0, tv);
          if (max(max(max(qn[0][0], qn[0][1]), max(qn[1][0], qn[1][1])), kn) == NOT_F16) {
#pragma unroll
            for (int i = 0; i < 4; i++) if (qn[i >> 1][i & 1] == NOT_F16) pack_b(i >> 1, i & 1, q[i >> 1][i & 1]);
            if (kn == NOT_F16) pack_b(3, 0, tk);
          }
          fence_regs(tv);
          const bool elected = w == 0 && lane == 0;
          const uint64_t kd0 = mkdesc(sb + T0, 16, 512, 2);
          const uint64_t vd0 = mkdesc(sb + T0 + 16384, ONES - (T0 + 16384), 512, 2);
          constexpr uint64_t VSTEP = 64 - (64ull << 16);
          constexpr int RPC = NQ / 16;
          float o[2][20], SA[2][NQ / 2];
          uint32_t SB[2][NQB / 4], PA[4], PB[4];
          auto qka = [&](int b, int k, uint64_t d, int h = 0) { QK_A(SA[b], q[h][0][4 * k], q[h][0][4 * k + 1], q[h][0][4 * k + 2], q[h][0][4 * k + 3], d + 2 * k, k ? 1 : zero); };
          auto qkb = [&](int b, int k, uint64_t d, int h = 0) { QK_B(SB[b], q[h][1][4 * k], q[h][1][4 * k + 1], q[h][1][4 * k + 2], q[h][1][4 * k + 3], d + 2 * k, k ? 1 : zero); };
          auto pv = [&](int m, const uint32_t (&Px)[4], uint64_t vd, int keep = 1) { wgmma_m64n40k16_rs_tb(o[m], Px[0], Px[1], Px[2], Px[3], vd, keep); };
          auto clear = [&]() {
#pragma unroll
            for (int i = 0; i < 4; i++) PA[i] = PB[i] = zero;
            wg_fence();
            wgmma_m64n40k16_rs_tb_z(o[0], PA[0], PA[1], PA[2], PA[3], vd0, 0); wgmma_m64n40k16_rs_tb_z(o[1], PB[0], PB[1], PB[2], PB[3], vd0 + VSTEP, 0);
          };
          mbar_wait(sb + B_TF, 0);
          clear();
#pragma unroll
          for (int b = 1; b >= 0; b--) {
            wgmma_m64n32k16_rs_nb_z_h(SA[b], q[0][0][0], q[0][0][1], q[0][0][2], q[0][0][3], kd0 + 128 * b, 0);
            wgmma_m64n32k16_rs_nb_z_hh(SB[b], q[0][1][0], q[0][1][1], q[0][1][2], q[0][1][3], kd0 + 128 * b, 0);
          }
          qka(0, 1, kd0); qkb(0, 1, kd0); wg_commit();
          put_kv(1, 1, 0, tv); put_kv(1, 0, 0, tk); put_kn(1, 0, kn);
          fence_async_smem();
          bar_arrive(NB_KV + 12, 288);
          wg_wait<0>();
          fence_regs(SA[0]); fence_regs(SB[0]); fence_regs(SA[1]); fence_regs(SB[1]); fence_regs(o[0]); fence_regs(o[1]);
#pragma unroll 1
          for (int pass = 0; pass < 2; pass++) {
            constexpr int IPS = 16 / NRB, NC = NRB / RPC, RPB = NQB / 16, RPM = RPB - (OB & 15) > RPC - (OA & 15) ? RPB - (OB & 15) : RPC - (OA & 15);
            uint32_t kc = (uint32_t)kd0, vc = (uint32_t)vd0, vp = (uint32_t)(vd0 + VSTEP);
#pragma unroll 1
            for (int it = 1; it <= 8 * IPS; it++) {
              const uint32_t sn = (it / IPS) & 3, un = it % IPS, par = (it / (4 * IPS)) & 1;
              const uint32_t kn = it < 8 * IPS ? (uint32_t)kd0 + sn * 2048 + un * (NRB * 64) : kc;
              const uint64_t hi = kd0 & 0xFFFFFFFF00000000ull, kd = hi | kc, vd = hi | vc, kdn = hi | kn, vdp = hi | vp;
              kc = kn; vp = vc + (uint32_t)(NRB * VSTEP); vc = (uint32_t)vd0 + (sn * 32 + un * NRB) * (uint32_t)VSTEP;
              bool landed = false;
#pragma unroll
              for (int r = 0; r < NRB; r++) {
                const int c = r / RPC, ro = r % RPC, cn = c + 1, cb = r / RPB, rb = r % RPB;
                if (r == NRB - RPM && !landed) mbar_wait(sb + B_TF + 8 * sn, par);
                wg_fence();
                const uint64_t kx = cn < NC ? kd + cn * NQ * 4 : kdn, vx = (r ? vd : vdp) + (r - 1) * VSTEP;
#pragma unroll
                for (int k = 0; k < 2; k++) {
                  if (ro == ((OA >> (4 * k)) & 15)) qka(cn & 1, k, kx);
                  if (rb == ((OB >> (4 * k)) & 15)) qkb((cb + 1) & 1, k, cb + 1 < NRB / RPB ? kd + (cb + 1) * NQB * 4 : kdn);
                }
                if ((ro == RPC - 1 && (OA >> 4) == ro) || (rb == RPB - 1 && (OB >> 4) == rb) || (LAG & 1)) wg_commit();
                const int keep = r || !OSD ? 1 : it - 1;
                if (LAG & 8) { pv(1, PB, vx, keep); pv(0, PA, vx, keep); } else { pv(0, PA, vx, keep); pv(1, PB, vx, keep); }
                wg_commit();
                if (r == NRB - RPM - 2) landed = mbar_test(sb + B_TF + 8 * sn, par) || it == 8 * IPS;
#pragma unroll
                for (int i = 0; i < 4; i++) {
                  if (LAG & 16) PB[i] = exp2_h2(SB[cb & 1][4 * rb + i], zero);
                  PA[i] = pack2(ex2(SA[c & 1][8 * ro + 2 * i]), ex2(SA[c & 1][8 * ro + 2 * i + 1]));
                  if (!(LAG & 16)) PB[i] = exp2_h2(SB[cb & 1][4 * rb + i], zero);
                }
                if (r == NRB - 1) wg_wait<0>(); else if (ro == RPC - 1 || rb == RPB - 1 || !(LAG & 2) || ((LAG & 4) && (ro & 1))) wg_wait<1>();
                if (ro == RPC - 1) fence_regs(SA[cn & 1]);
                if (rb == RPB - 1) fence_regs(SB[(cb + 1) & 1]);
                if (r == RPC && elected && un == 1 % IPS && it > 1) mbar_arrive(sb + B_TE + 8 * ((sn + (IPS > 1 ? 3 : 2)) & 3));
              }
            }
            int badm = 0;
            if (pass == 0) mbar_wait(sb + B_TF, 0);
            wg_fence();
            pv(0, PA, vd0 + 111 * VSTEP); pv(1, PB, vd0 + 111 * VSTEP); wg_commit();
            qka(0, 0, kd0, 1); qkb(0, 0, kd0, 1); qka(0, 1, kd0, 1); qkb(0, 1, kd0, 1); wg_commit();
            if (pass == 0) bar_sync(NB_KN + wg, 160);
            const float kmax = *(volatile float*)(smem + KMAX + 4 * pass);
            wg_wait<1>(); fence_regs(o[0]); fence_regs(o[1]);
            if (w == 0) e_arrive(sb + B_TE + 8 * 3);
#pragma unroll
            for (int m = 0; m < 2; m++) {
              if (ONECOL) { o[m][16] = __shfl_sync(~0u, o[m][16], 0, 4); o[m][18] = __shfl_sync(~0u, o[m][18], 0, 4); }
              const float of[16] = {o[m][0], o[m][1], o[m][2], o[m][3], o[m][4], o[m][5], o[m][6], o[m][7], o[m][8], o[m][9], o[m][10], o[m][11], o[m][12], o[m][13], o[m][14], o[m][15]};
              const uint32_t chk = put_o(pass, m, of, rcp(o[m][16]), rcp(o[m][18]));
              const bool bad = !(__uint_as_float(qn[0][m]) * kmax <= (m ? 0.875f * 0.875f : 112.f * 112.f)) || !(fminf(o[m][16], o[m][18]) >= 9.3e-10f) ||
                               !(o[m][16] + o[m][18] <= 3e38f) || ((chk + 0x00800080u) & 0x80008000u);
              badm |= __any_sync(~0u, bad) << m;
            }
            wg_wait<0>(); fence_regs(SA[0]); fence_regs(SB[0]);
            if (badm) {
#pragma unroll 1
              for (int m = 0; m < 2; m++) if ((badm >> m) & 1) {
                uint32_t qq[8]; float res[20];
#pragma unroll
                for (int i = 0; i < 8; i++) { qq[i] = m ? q[0][1][i] : q[0][0][i]; if ((m ? qn[0][1] : qn[0][0]) != NOT_F16) qq[i] = h2_to_bf2(qq[i]); }
                attn_slow(qq, m ? 128.f : 1.f, 2 * (cta_id() & 15) + pass, g_kn + ((l >> 1) * 128 + (cta_id() & 15) * 8) * 32 + 16 * pass, res, lane_id());
                const float of[16] = {res[0], res[1], res[2], res[3], res[4], res[5], res[6], res[7], res[8], res[9], res[10], res[11], res[12], res[13], res[14], res[15]};
                put_o(pass, m, of, rcp(res[16]), rcp(res[18]));
              }
            }
            bar_arrive(NB_SIG + 2 * pass + wg, 160);
            qn[0][0] = qn[1][0]; qn[0][1] = qn[1][1];
#pragma unroll
            for (int m = 0; m < 2; m++)
#pragma unroll
              for (int i = 0; i < 8; i++) q[0][m][i] = q[1][m][i];
            if (!OSD) {
#pragma unroll
              for (int i = 0; i < 20; i++) o[0][i] = o[1][i] = 0.f;
              fence_regs(o[0]); fence_regs(o[1]);
            }
#pragma unroll
            for (int i = 0; i < 4; i++) PA[i] = PB[i] = zero;
          }
        }
      }
      {
        float acc[64];
#pragma unroll
        for (int i = 0; i < 64; i++) acc[i] = 0.f;
        fence_regs(acc);
        uint32_t s = PPEEL, lap = 0;
#pragma unroll 1
        for (int kt = PPEEL; kt < 16; kt++) {
          mbar_wait(sb + B_PF + 8 * s, ((s < 4 ? l : 0) + lap) & 1);
          const uint64_t da = mkdesc(sb + pslot_a(s, l) + wg * 8192, 16, 1024, 1), db = mkdesc(sb + pslot_b(s, l), 8192, 1024, 1);
          wg_fence();
#pragma unroll
          for (int k = 0; k < 4; k++) wgmma_m64n128k16_ss_tb(acc, da + k * 2, db + k * 128, 1);
          wg_commit();
          wg_wait<1>();
          if (kt > 0 && w == 0) e_arrive_both(sb + B_PE + 8 * (s ? s - 1 : 5));
          if (++s == 6) { s = 0; lap++; }
        }
        IDS();
        const int g = lane >> 2, qd = lane & 3;
        const int r0 = wg * 64 + w * 16;
        const uint32_t r = r0 + (lane & 7) + ((lane >> 3) & 1) * 8;
        uint32_t x[8][4];
        mbar_wait(sb + B_RF, l & 1);
#pragma unroll
        for (int jj = 0; jj < 8; jj++) ldsm4(sb + ((l & 1) ? RES : 0) + (jj >> 2) * 16384 + r * 128 + ((((2 * jj + (lane >> 4)) & 7) ^ (r & 7)) << 4), x[jj]);
        wg_wait<0>();
        fence_regs(acc);
        bar_sync(NB_SC, 256);
        if (w == 0) e_arrive_both(sb + B_PE + 8 * 3);
        const CUtensorMap* mo = &prm.m[l == 3 ? M_OUT : M_XST];
#pragma unroll
        for (int jj = 0; jj < 8; jj++) {
#pragma unroll
          for (int i = 0; i < 4; i++) x[jj][i] = add_bf16x2(x[jj][i], pack2(acc[8 * jj + 2 * i], acc[8 * jj + 2 * i + 1]));
          stsm4(sb + (jj >> 2) * QSTG + po * 16384 + r * 128 + ((((2 * jj + (lane >> 4)) & 7) ^ (r & 7)) << 4), x[jj][0], x[jj][1], x[jj][2], x[jj][3]);
          if ((jj & 3) == 3) { fence_async_smem(); __syncwarp(); tma_st(mo, pn * 128 + (jj >> 2) * 64, pm * 128 + r0, sb + (jj >> 2) * QSTG + po * 16384 + r0 * 128); }
        }
        bulk_commit();
        if (l < 3) {
          bar_arrive(NB_X, 288);
          float s1[4] = {0.f, 0.f, 0.f, 0.f}, s2[4][4];
#pragma unroll
          for (int i = 0; i < 16; i++) s2[i >> 2][i & 3] = 0.f;
#pragma unroll
          for (int jj = 0; jj < 8; jj++) {
            mma16816(s1, x[jj][0], x[jj][1], x[jj][2], x[jj][3], 0x3f803f80u, 0x3f803f80u);
#pragma unroll
            for (int i = 0; i < 4; i++) mma1688(s2[i], x[jj][i & 2], x[jj][i | 1], x[jj][i]);
          }
          if (qd == (g >> 1)) {
            float2* sp = g_stats + pn * 2048 + pm * 128 + r0 + g;
            sp[0] = make_float2(s1[0], (g & 1) ? s2[0][1] + s2[2][1] : s2[0][0] + s2[2][0]);
            sp[8] = make_float2(s1[2], (g & 1) ? s2[1][3] + s2[3][3] : s2[1][2] + s2[3][2]);
          }
        }
        bulk_wait_n<0>();
        if (l < 3) bar_arrive(NB_X0, 320 + 32 * XLATE);
      }
    }
  }
  asm volatile("barrier.cluster.arrive.relaxed.aligned;\nbarrier.cluster.wait.aligned;" ::: "memory");
}

typedef CUresult (*EncodeFn)(CUtensorMap*, CUtensorMapDataType, cuuint32_t, void*, const cuuint64_t*, const cuuint64_t*, const cuuint32_t*,
                             const cuuint32_t*, CUtensorMapInterleave, CUtensorMapSwizzle, CUtensorMapL2promotion, CUtensorMapFloatOOBfill);

static void make_map(EncodeFn fn, CUtensorMap* m, const void* ptr, int rank, const uint64_t* dims, const uint64_t* strides, const uint32_t* box, CUtensorMapSwizzle sw) {
  cuuint64_t d[5], st[4];
  cuuint32_t bx[5], es[5];
  for (int i = 0; i < rank; i++) { d[i] = dims[i]; bx[i] = box[i]; es[i] = 1; if (i) st[i - 1] = strides[i - 1] * 2; }
  fn(m, CU_TENSOR_MAP_DATA_TYPE_BFLOAT16, rank, (void*)ptr, d, st, bx, es, CU_TENSOR_MAP_INTERLEAVE_NONE, sw,
     CU_TENSOR_MAP_L2_PROMOTION_L2_128B, CU_TENSOR_MAP_FLOAT_OOB_FILL_NONE);
}
static void map2(EncodeFn fn, CUtensorMap* m, const void* ptr, uint64_t inner, uint64_t outer, uint32_t bi, uint32_t bo, CUtensorMapSwizzle sw) {
  const uint64_t d[2] = {inner, outer}, st[1] = {inner};
  const uint32_t bx[2] = {bi, bo};
  make_map(fn, m, ptr, 2, d, st, bx, sw);
}

extern "C" void kernel_launch(void* const* d_in, const int* in_sizes, int n_in, void* d_out, int out_size) {
  (void)in_sizes; (void)n_in; (void)out_size;
  static EncodeFn enc = nullptr;
  static void *xs, *os, *kk, *vv, *ep;
  if (!enc) {
    void* p = nullptr;
    cudaDriverEntryPointQueryResult qr;
    cudaGetDriverEntryPoint("cuTensorMapEncodeTiled", &p, cudaEnableDefault, &qr);
    enc = (EncodeFn)p;
    cudaGetSymbolAddress(&xs, g_xs); cudaGetSymbolAddress(&os, g_os); cudaGetSymbolAddress(&kk, g_k); cudaGetSymbolAddress(&vv, g_v); cudaGetSymbolAddress(&ep, g_epoch);
    cudaFuncSetAttribute(fused_kernel, cudaFuncAttributeMaxDynamicSharedMemorySize, SMEM_BYTES);
  }
  Params prm;
  const CUtensorMapSwizzle S128 = CU_TENSOR_MAP_SWIZZLE_128B, S64 = CU_TENSOR_MAP_SWIZZLE_64B;
  map2(enc, &prm.m[M_X0A], d_in[0], 1024, 2048, 64, 256, S128);
  map2(enc, &prm.m[M_XSA], xs, 1024, 2048, 64, 256, S128);
  for (int t = 0; t < 2; t++) {
    const uint64_t d3[3] = {1024, 1024, 3}, s3[2] = {3072, 1024};
    const uint32_t b3[3] = {64, 64, 3};
    make_map(enc, &prm.m[M_WQA + t], d_in[1 + 3 * t], 3, d3, s3, b3, S128);
    const uint64_t d5[5] = {64, 32, 2, 16, 16}, s5[4] = {1024, 32 * 1024, 64 * 1024, 64};
    const uint32_t b5[5] = {64, 32, 1, 2, 2};
    make_map(enc, &prm.m[M_WOA + t], d_in[2 + 3 * t], 5, d5, s5, b5, S128);
    const uint64_t dr[3] = {64, 2048, 16}, sr[2] = {1024, 64};
    const uint32_t br[3] = {64, 128, 2};
    make_map(enc, &prm.m[M_X0R + t], t ? xs : d_in[0], 3, dr, sr, br, S128);
  }
  map2(enc, &prm.m[M_OS], os, 1024, 2048, 64, 64, S128);
  map2(enc, &prm.m[M_K], kk, 32, 65536, 32, 256, S64);
  map2(enc, &prm.m[M_V], vv, 32, 65536, 32, 256, S64);
  map2(enc, &prm.m[M_K4], kk, 32, 65536, 32, 64, S64);
  map2(enc, &prm.m[M_V4], vv, 32, 65536, 32, 64, S64);
  map2(enc, &prm.m[M_XSO], xs, 1024, 2048, 64, 128, S128);
  map2(enc, &prm.m[M_X0H], d_in[0], 1024, 2048, 64, 128, S128);
  map2(enc, &prm.m[M_XST], xs, 1024, 2048, 64, 16, S128);
  map2(enc, &prm.m[M_OUT], d_out, 1024, 2048, 64, 16, S128);
  prm.x0 = (const bf16*)d_in[0];
  prm.wq[0] = (const bf16*)d_in[1]; prm.wq[1] = (const bf16*)d_in[4];
  prm.wo[0] = (const bf16*)d_in[2]; prm.wo[1] = (const bf16*)d_in[5];
  prm.epoch = (uint32_t*)ep;
  prm.zero = 0;
  for (int i = 0; i < 128; i++) prm.map[i] = remap(i);
  fused_kernel<<<128, 384, SMEM_BYTES>>>(prm);
}
```

```cpp
#include <cuda_runtime.h>
#include <cuda_bf16.h>
#include <cuda.h>
#include <stdint.h>

typedef __nv_bfloat16 bf16;

__device__ __forceinline__ void wgmma_m64n192k16_ss_tb(float (&d)[96], uint64_t da, uint64_t db, int scale_d) {
  asm volatile("{\n.reg .pred p;\nsetp.ne.b32 p, %98, 0;\n"
    "wgmma.mma_async.sync.aligned.m64n192k16.f32.bf16.bf16 "
    "{%0, %1, %2, %3, %4, %5, %6, %7, %8, %9, %10, %11, %12, %13, %14, %15, "
    "%16, %17, %18, %19, %20, %21, %22, %23, %24, %25, %26, %27, %28, %29, %30, %31, "
    "%32, %33, %34, %35, %36, %37, %38, %39, %40, %41, %42, %43, %44, %45, %46, %47, "
    "%48, %49, %50, %51, %52, %53, %54, %55, %56, %57, %58, %59, %60, %61, %62, %63, "
    "%64, %65, %66, %67, %68, %69, %70, %71, %72, %73, %74, %75, %76, %77, %78, %79, "
    "%80, %81, %82, %83, %84, %85, %86, %87, %88, %89, %90, %91, %92, %93, %94, %95}, "
    "%96, %97, p, 1, 1, 0, 1;\n}\n"
    : "+f"(d[0]), "+f"(d[1]), "+f"(d[2]), "+f"(d[3]), "+f"(d[4]), "+f"(d[5]), "+f"(d[6]), "+f"(d[7]),
      "+f"(d[8]), "+f"(d[9]), "+f"(d[10]), "+f"(d[11]), "+f"(d[12]), "+f"(d[13]), "+f"(d[14]), "+f"(d[15]),
      "+f"(d[16]), "+f"(d[17]), "+f"(d[18]), "+f"(d[19]), "+f"(d[20]), "+f"(d[21]), "+f"(d[22]), "+f"(d[23]),
      "+f"(d[24]), "+f"(d[25]), "+f"(d[26]), "+f"(d[27]), "+f"(d[28]), "+f"(d[29]), "+f"(d[30]), "+f"(d[31]),
      "+f"(d[32]), "+f"(d[33]), "+f"(d[34]), "+f"(d[35]), "+f"(d[36]), "+f"(d[37]), "+f"(d[38]), "+f"(d[39]),
      "+f"(d[40]), "+f"(d[41]), "+f"(d[42]), "+f"(d[43]), "+f"(d[44]), "+f"(d[45]), "+f"(d[46]), "+f"(d[47]),
      "+f"(d[48]), "+f"(d[49]), "+f"(d[50]), "+f"(d[51]), "+f"(d[52]), "+f"(d[53]), "+f"(d[54]), "+f"(d[55]),
      "+f"(d[56]), "+f"(d[57]), "+f"(d[58]), "+f"(d[59]), "+f"(d[60]), "+f"(d[61]), "+f"(d[62]), "+f"(d[63]),
      "+f"(d[64]), "+f"(d[65]), "+f"(d[66]), "+f"(d[67]), "+f"(d[68]), "+f"(d[69]), "+f"(d[70]), "+f"(d[71]),
      "+f"(d[72]), "+f"(d[73]), "+f"(d[74]), "+f"(d[75]), "+f"(d[76]), "+f"(d[77]), "+f"(d[78]), "+f"(d[79]),
      "+f"(d[80]), "+f"(d[81]), "+f"(d[82]), "+f"(d[83]), "+f"(d[84]), "+f"(d[85]), "+f"(d[86]), "+f"(d[87]),
      "+f"(d[88]), "+f"(d[89]), "+f"(d[90]), "+f"(d[91]), "+f"(d[92]), "+f"(d[93]), "+f"(d[94]), "+f"(d[95])
    : "l"(da), "l"(db), "r"(scale_d));
}

__device__ __forceinline__ void wgmma_m64n128k16_ss_tb(float (&d)[64], uint64_t da, uint64_t db, int scale_d) {
  asm volatile("{\n.reg .pred p;\nsetp.ne.b32 p, %66, 0;\n"
    "wgmma.mma_async.sync.aligned.m64n128k16.f32.bf16.bf16 "
    "{%0, %1, %2, %3, %4, %5, %6, %7, %8, %9, %10, %11, %12, %13, %14, %15, "
    "%16, %17, %18, %19, %20, %21, %22, %23, %24, %25, %26, %27, %28, %29, %30, %31, "
    "%32, %33, %34, %35, %36, %37, %38, %39, %40, %41, %42, %43, %44, %45, %46, %47, "
    "%48, %49, %50, %51, %52, %53, %54, %55, %56, %57, %58, %59, %60, %61, %62, %63}, "
    "%64, %65, p, 1, 1, 0, 1;\n}\n"
    : "+f"(d[0]), "+f"(d[1]), "+f"(d[2]), "+f"(d[3]), "+f"(d[4]), "+f"(d[5]), "+f"(d[6]), "+f"(d[7]),
      "+f"(d[8]), "+f"(d[9]), "+f"(d[10]), "+f"(d[11]), "+f"(d[12]), "+f"(d[13]), "+f"(d[14]), "+f"(d[15]),
      "+f"(d[16]), "+f"(d[17]), "+f"(d[18]), "+f"(d[19]), "+f"(d[20]), "+f"(d[21]), "+f"(d[22]), "+f"(d[23]),
      "+f"(d[24]), "+f"(d[25]), "+f"(d[26]), "+f"(d[27]), "+f"(d[28]), "+f"(d[29]), "+f"(d[30]), "+f"(d[31]),
      "+f"(d[32]), "+f"(d[33]), "+f"(d[34]), "+f"(d[35]), "+f"(d[36]), "+f"(d[37]), "+f"(d[38]), "+f"(d[39]),
      "+f"(d[40]), "+f"(d[41]), "+f"(d[42]), "+f"(d[43]), "+f"(d[44]), "+f"(d[45]), "+f"(d[46]), "+f"(d[47]),
      "+f"(d[48]), "+f"(d[49]), "+f"(d[50]), "+f"(d[51]), "+f"(d[52]), "+f"(d[53]), "+f"(d[54]), "+f"(d[55]),
      "+f"(d[56]), "+f"(d[57]), "+f"(d[58]), "+f"(d[59]), "+f"(d[60]), "+f"(d[61]), "+f"(d[62]), "+f"(d[63])
    : "l"(da), "l"(db), "r"(scale_d));
}

__device__ __forceinline__ void wgmma_m64n32k16_rs_nb_h(float (&d)[16], uint32_t a0, uint32_t a1, uint32_t a2, uint32_t a3, uint64_t db, int scale_d) {
  asm volatile("{\n.reg .pred p;\nsetp.ne.b32 p, %21, 0;\n"
    "wgmma.mma_async.sync.aligned.m64n32k16.f32.f16.f16 "
    "{%0, %1, %2, %3, %4, %5, %6, %7, %8, %9, %10, %11, %12, %13, %14, %15}, "
    "{%16, %17, %18, %19}, %20, p, 1, 1, 0;\n}\n"
    : "+f"(d[0]), "+f"(d[1]), "+f"(d[2]), "+f"(d[3]), "+f"(d[4]), "+f"(d[5]), "+f"(d[6]), "+f"(d[7]),
      "+f"(d[8]), "+f"(d[9]), "+f"(d[10]), "+f"(d[11]), "+f"(d[12]), "+f"(d[13]), "+f"(d[14]), "+f"(d[15])
    : "r"(a0), "r"(a1), "r"(a2), "r"(a3), "l"(db), "r"(scale_d));
}

__device__ __forceinline__ void wgmma_m64n32k16_rs_nb_hh(uint32_t (&d)[8], uint32_t a0, uint32_t a1, uint32_t a2, uint32_t a3, uint64_t db, int scale_d) {
  asm volatile("{\n.reg .pred p;\nsetp.ne.b32 p, %13, 0;\n"
    "wgmma.mma_async.sync.aligned.m64n32k16.f16.f16.f16 "
    "{%0, %1, %2, %3, %4, %5, %6, %7}, "
    "{%8, %9, %10, %11}, %12, p, 1, 1, 0;\n}\n"
    : "+r"(d[0]), "+r"(d[1]), "+r"(d[2]), "+r"(d[3]), "+r"(d[4]), "+r"(d[5]), "+r"(d[6]), "+r"(d[7])
    : "r"(a0), "r"(a1), "r"(a2), "r"(a3), "l"(db), "r"(scale_d));
}

__device__ __forceinline__ void wgmma_m64n64k16_rs_nb_h(float (&d)[32], uint32_t a0, uint32_t a1, uint32_t a2, uint32_t a3, uint64_t db, int scale_d) {
  asm volatile("{\n.reg .pred p;\nsetp.ne.b32 p, %37, 0;\n"
    "wgmma.mma_async.sync.aligned.m64n64k16.f32.f16.f16 "
    "{%0, %1, %2, %3, %4, %5, %6, %7, %8, %9, %10, %11, %12, %13, %14, %15, "
    "%16, %17, %18, %19, %20, %21, %22, %23, %24, %25, %26, %27, %28, %29, %30, %31}, "
    "{%32, %33, %34, %35}, %36, p, 1, 1, 0;\n}\n"
    : "+f"(d[0]), "+f"(d[1]), "+f"(d[2]), "+f"(d[3]), "+f"(d[4]), "+f"(d[5]), "+f"(d[6]), "+f"(d[7]),
      "+f"(d[8]), "+f"(d[9]), "+f"(d[10]), "+f"(d[11]), "+f"(d[12]), "+f"(d[13]), "+f"(d[14]), "+f"(d[15]),
      "+f"(d[16]), "+f"(d[17]), "+f"(d[18]), "+f"(d[19]), "+f"(d[20]), "+f"(d[21]), "+f"(d[22]), "+f"(d[23]),
      "+f"(d[24]), "+f"(d[25]), "+f"(d[26]), "+f"(d[27]), "+f"(d[28]), "+f"(d[29]), "+f"(d[30]), "+f"(d[31])
    : "r"(a0), "r"(a1), "r"(a2), "r"(a3), "l"(db), "r"(scale_d));
}

__device__ __forceinline__ void wgmma_m64n64k16_rs_nb_hh(uint32_t (&d)[16], uint32_t a0, uint32_t a1, uint32_t a2, uint32_t a3, uint64_t db, int scale_d) {
  asm volatile("{\n.reg .pred p;\nsetp.ne.b32 p, %21, 0;\n"
    "wgmma.mma_async.sync.aligned.m64n64k16.f16.f16.f16 "
    "{%0, %1, %2, %3, %4, %5, %6, %7, %8, %9, %10, %11, %12, %13, %14, %15}, "
    "{%16, %17, %18, %19}, %20, p, 1, 1, 0;\n}\n"
    : "+r"(d[0]), "+r"(d[1]), "+r"(d[2]), "+r"(d[3]), "+r"(d[4]), "+r"(d[5]), "+r"(d[6]), "+r"(d[7]),
      "+r"(d[8]), "+r"(d[9]), "+r"(d[10]), "+r"(d[11]), "+r"(d[12]), "+r"(d[13]), "+r"(d[14]), "+r"(d[15])
    : "r"(a0), "r"(a1), "r"(a2), "r"(a3), "l"(db), "r"(scale_d));
}

__device__ __forceinline__ void wgmma_m64n40k16_rs_tb(float (&d)[20], uint32_t a0, uint32_t a1, uint32_t a2, uint32_t a3, uint64_t db, int scale_d) {
  asm volatile("{\n.reg .pred p;\nsetp.ne.b32 p, %25, 0;\n"
    "wgmma.mma_async.sync.aligned.m64n40k16.f32.bf16.bf16 "
    "{%0, %1, %2, %3, %4, %5, %6, %7, %8, %9, %10, %11, %12, %13, %14, %15, "
    "%16, %17, %18, %19}, "
    "{%20, %21, %22, %23}, %24, p, 1, 1, 1;\n}\n"
    : "+f"(d[0]), "+f"(d[1]), "+f"(d[2]), "+f"(d[3]), "+f"(d[4]), "+f"(d[5]), "+f"(d[6]), "+f"(d[7]),
      "+f"(d[8]), "+f"(d[9]), "+f"(d[10]), "+f"(d[11]), "+f"(d[12]), "+f"(d[13]), "+f"(d[14]), "+f"(d[15]),
      "+f"(d[16]), "+f"(d[17]), "+f"(d[18]), "+f"(d[19])
    : "r"(a0), "r"(a1), "r"(a2), "r"(a3), "l"(db), "r"(scale_d));
}

__device__ __forceinline__ void wgmma_m64n40k16_rs_tb_z(float (&d)[20], uint32_t a0, uint32_t a1, uint32_t a2, uint32_t a3, uint64_t db, int scale_d) {
  asm volatile("{\n.reg .pred p;\nsetp.ne.b32 p, %25, 0;\n"
    "wgmma.mma_async.sync.aligned.m64n40k16.f32.bf16.bf16 "
    "{%0, %1, %2, %3, %4, %5, %6, %7, %8, %9, %10, %11, %12, %13, %14, %15, "
    "%16, %17, %18, %19}, "
    "{%20, %21, %22, %23}, %24, p, 1, 1, 1;\n}\n"
    : "=f"(d[0]), "=f"(d[1]), "=f"(d[2]), "=f"(d[3]), "=f"(d[4]), "=f"(d[5]), "=f"(d[6]), "=f"(d[7]),
      "=f"(d[8]), "=f"(d[9]), "=f"(d[10]), "=f"(d[11]), "=f"(d[12]), "=f"(d[13]), "=f"(d[14]), "=f"(d[15]),
      "=f"(d[16]), "=f"(d[17]), "=f"(d[18]), "=f"(d[19])
    : "r"(a0), "r"(a1), "r"(a2), "r"(a3), "l"(db), "r"(scale_d));
}

__device__ __forceinline__ void wgmma_m64n32k16_rs_nb_z_h(float (&d)[16], uint32_t a0, uint32_t a1, uint32_t a2, uint32_t a3, uint64_t db, int scale_d) {
  asm volatile("{\n.reg .pred p;\nsetp.ne.b32 p, %21, 0;\n"
    "wgmma.mma_async.sync.aligned.m64n32k16.f32.f16.f16 "
    "{%0, %1, %2, %3, %4, %5, %6, %7, %8, %9, %10, %11, %12, %13, %14, %15}, "
    "{%16, %17, %18, %19}, %20, p, 1, 1, 0;\n}\n"
    : "=f"(d[0]), "=f"(d[1]), "=f"(d[2]), "=f"(d[3]), "=f"(d[4]), "=f"(d[5]), "=f"(d[6]), "=f"(d[7]),
      "=f"(d[8]), "=f"(d[9]), "=f"(d[10]), "=f"(d[11]), "=f"(d[12]), "=f"(d[13]), "=f"(d[14]), "=f"(d[15])
    : "r"(a0), "r"(a1), "r"(a2), "r"(a3), "l"(db), "r"(scale_d));
}

__device__ __forceinline__ void wgmma_m64n32k16_rs_nb_z_hh(uint32_t (&d)[8], uint32_t a0, uint32_t a1, uint32_t a2, uint32_t a3, uint64_t db, int scale_d) {
  asm volatile("{\n.reg .pred p;\nsetp.ne.b32 p, %13, 0;\n"
    "wgmma.mma_async.sync.aligned.m64n32k16.f16.f16.f16 "
    "{%0, %1, %2, %3, %4, %5, %6, %7}, "
    "{%8, %9, %10, %11}, %12, p, 1, 1, 0;\n}\n"
    : "=r"(d[0]), "=r"(d[1]), "=r"(d[2]), "=r"(d[3]), "=r"(d[4]), "=r"(d[5]), "=r"(d[6]), "=r"(d[7])
    : "r"(a0), "r"(a1), "r"(a2), "r"(a3), "l"(db), "r"(scale_d));
}

__device__ __forceinline__ void wgmma_m64n128k16_ss_tb_z(float (&d)[64], uint64_t da, uint64_t db, int scale_d) {
  asm volatile("{\n.reg .pred p;\nsetp.ne.b32 p, %66, 0;\n"
    "wgmma.mma_async.sync.aligned.m64n128k16.f32.bf16.bf16 "
    "{%0, %1, %2, %3, %4, %5, %6, %7, %8, %9, %10, %11, %12, %13, %14, %15, "
    "%16, %17, %18, %19, %20, %21, %22, %23, %24, %25, %26, %27, %28, %29, %30, %31, "
    "%32, %33, %34, %35, %36, %37, %38, %39, %40, %41, %42, %43, %44, %45, %46, %47, "
    "%48, %49, %50, %51, %52, %53, %54, %55, %56, %57, %58, %59, %60, %61, %62, %63}, "
    "%64, %65, p, 1, 1, 0, 1;\n}\n"
    : "=f"(d[0]), "=f"(d[1]), "=f"(d[2]), "=f"(d[3]), "=f"(d[4]), "=f"(d[5]), "=f"(d[6]), "=f"(d[7]),
      "=f"(d[8]), "=f"(d[9]), "=f"(d[10]), "=f"(d[11]), "=f"(d[12]), "=f"(d[13]), "=f"(d[14]), "=f"(d[15]),
      "=f"(d[16]), "=f"(d[17]), "=f"(d[18]), "=f"(d[19]), "=f"(d[20]), "=f"(d[21]), "=f"(d[22]), "=f"(d[23]),
      "=f"(d[24]), "=f"(d[25]), "=f"(d[26]), "=f"(d[27]), "=f"(d[28]), "=f"(d[29]), "=f"(d[30]), "=f"(d[31]),
      "=f"(d[32]), "=f"(d[33]), "=f"(d[34]), "=f"(d[35]), "=f"(d[36]), "=f"(d[37]), "=f"(d[38]), "=f"(d[39]),
      "=f"(d[40]), "=f"(d[41]), "=f"(d[42]), "=f"(d[43]), "=f"(d[44]), "=f"(d[45]), "=f"(d[46]), "=f"(d[47]),
      "=f"(d[48]), "=f"(d[49]), "=f"(d[50]), "=f"(d[51]), "=f"(d[52]), "=f"(d[53]), "=f"(d[54]), "=f"(d[55]),
      "=f"(d[56]), "=f"(d[57]), "=f"(d[58]), "=f"(d[59]), "=f"(d[60]), "=f"(d[61]), "=f"(d[62]), "=f"(d[63])
    : "l"(da), "l"(db), "r"(scale_d));
}

#define DEVINL __device__ __forceinline__
#define PSLEEP 0
#define XLATE 1
#define PLATE 1
#define HINT 4000
#define MWL mbar_wait_long
DEVINL void pin(uint32_t z) { asm volatile("{\n.reg .pred p;\nsetp.ne.u32 p, %0, 0;\nPIN:\n@p bra.uni PIN;\n}" ::"r"(z) : "memory"); }
DEVINL void wg_fence() { asm volatile("wgmma.fence.sync.aligned;" ::: "memory"); }
DEVINL void wg_commit() { asm volatile("wgmma.commit_group.sync.aligned;" ::: "memory"); }
template <int N> DEVINL void wg_wait() { asm volatile("wgmma.wait_group.sync.aligned %0;" ::"n"(N) : "memory"); }
DEVINL uint64_t mkdesc(uint32_t addr, uint32_t lbo, uint32_t sbo, int sw) {
  return (uint64_t)((addr & 0x3FFFF) >> 4) | ((uint64_t)(lbo >> 4) << 16) | ((uint64_t)(sbo >> 4) << 32) | ((uint64_t)sw << 62);
}
DEVINL void mbar_arrive(uint32_t bar) { asm volatile("mbarrier.arrive.shared::cta.b64 _, [%0];" ::"r"(bar) : "memory"); }
DEVINL bool mbar_try(uint32_t bar, uint32_t parity) {
  uint32_t ok;
  asm volatile("{\n.reg .pred p;\nmbarrier.try_wait.parity.shared::cta.b64 p, [%1], %2;\nselp.u32 %0, 1, 0, p;\n}" : "=r"(ok) : "r"(bar), "r"(parity) : "memory");
  return ok;
}
DEVINL bool mbar_test(uint32_t bar, uint32_t parity) {
  uint32_t ok;
  asm volatile("{\n.reg .pred p;\nmbarrier.test_wait.parity.shared::cta.b64 p, [%1], %2;\nselp.u32 %0, 1, 0, p;\n}" : "=r"(ok) : "r"(bar), "r"(parity) : "memory");
  return ok;
}
DEVINL void mbar_hint(uint32_t bar, uint32_t parity) {
#pragma unroll 1
  for (uint32_t n = 0; n < 16u; n++) if (mbar_try(bar, parity)) break;
}
DEVINL void mbar_wait(uint32_t bar, uint32_t parity) {
#pragma unroll 1
  for (uint32_t n = 0; n < 100000u; n++) if (mbar_try(bar, parity)) break;
}
DEVINL void mbar_wait_long(uint32_t bar, uint32_t parity) {
#pragma unroll 1
  for (uint32_t n = 0; n < 100000u; n++) {
    uint32_t ok;
    asm volatile("{\n.reg .pred p;\nmbarrier.try_wait.parity.shared::cta.b64 p, [%1], %2, %3;\nselp.u32 %0, 1, 0, p;\n}" : "=r"(ok) : "r"(bar), "r"(parity), "r"(HINT) : "memory");
    if (ok) break;
  }
}
#define EL(txt) "{\n.reg .pred pe;\nelect.sync _|pe, 0xffffffff;\n@pe " txt "\n}"
DEVINL void e_expect_tx(uint32_t bar, uint32_t bytes) { asm volatile(EL("mbarrier.arrive.expect_tx.shared::cta.b64 _, [%0], %1;") ::"r"(bar), "r"(bytes) : "memory"); }
DEVINL void e_init(uint32_t bar, uint32_t cnt) { asm volatile(EL("mbarrier.init.shared::cta.b64 [%0], %1;") ::"r"(bar), "r"(cnt) : "memory"); }
DEVINL void e_arrive(uint32_t bar) { asm volatile(EL("mbarrier.arrive.shared::cta.b64 _, [%0];") ::"r"(bar) : "memory"); }
DEVINL void e_red(uint32_t* p) { asm volatile(EL("red.release.gpu.global.add.u32 [%0], 1;") ::"l"(p) : "memory"); }
DEVINL void e_red_relaxed(uint32_t* p) { asm volatile(EL("red.relaxed.gpu.global.add.u32 [%0], 1;") ::"l"(p) : "memory"); }
DEVINL void tma_ld(uint32_t dst, const CUtensorMap* m, int c0, int c1, uint32_t bar) {
  asm volatile(EL("cp.async.bulk.tensor.2d.shared::cluster.global.mbarrier::complete_tx::bytes [%0], [%1, {%3, %4}], [%2];")
               ::"r"(dst), "l"(m), "r"(bar), "r"(c0), "r"(c1) : "memory");
}
DEVINL void tma_ld3(uint32_t dst, const CUtensorMap* m, int c0, int c1, int c2, uint32_t bar) {
  asm volatile(EL("cp.async.bulk.tensor.3d.shared::cluster.global.mbarrier::complete_tx::bytes [%0], [%1, {%3, %4, %5}], [%2];")
               ::"r"(dst), "l"(m), "r"(bar), "r"(c0), "r"(c1), "r"(c2) : "memory");
}
DEVINL void tma_ld5(uint32_t dst, const CUtensorMap* m, int c2, int c3, int c4, uint32_t bar) {
  asm volatile(EL("cp.async.bulk.tensor.5d.shared::cluster.global.mbarrier::complete_tx::bytes [%0], [%1, {0, 0, %3, %4, %5}], [%2];")
               ::"r"(dst), "l"(m), "r"(bar), "r"(c2), "r"(c3), "r"(c4) : "memory");
}
DEVINL void tma_ld_mc(uint32_t dst, const CUtensorMap* m, int c0, int c1, uint32_t bar) {
  asm volatile(EL("cp.async.bulk.tensor.2d.shared::cluster.global.mbarrier::complete_tx::bytes.multicast::cluster [%0], [%1, {%3, %4}], [%2], %5;")
               ::"r"(dst), "l"(m), "r"(bar), "r"(c0), "r"(c1), "h"((uint16_t)3) : "memory");
}
DEVINL void e_arrive_both(uint32_t bar) {
  asm volatile("{\n.reg .pred pe;\n.reg .b32 r0, r1;\nelect.sync _|pe, 0xffffffff;\nmapa.shared::cluster.u32 r0, %0, 0;\nmapa.shared::cluster.u32 r1, %0, 1;\n"
               "@pe mbarrier.arrive.shared::cluster.b64 _, [r0];\n@pe mbarrier.arrive.shared::cluster.b64 _, [r1];\n}" ::"r"(bar) : "memory");
}
DEVINL void push_peer(uint32_t dst, uint32_t src, uint32_t bar, uint32_t peer) {
  asm volatile("{\n.reg .pred pe;\n.reg .b32 d, b;\nelect.sync _|pe, 0xffffffff;\nmapa.shared::cluster.u32 d, %0, %3;\nmapa.shared::cluster.u32 b, %2, %3;\n"
               "@pe cp.async.bulk.shared::cluster.shared::cta.mbarrier::complete_tx::bytes [d], [%1], 16384, [b];\n}" ::"r"(dst), "r"(src), "r"(bar), "r"(peer) : "memory");
}
DEVINL void tma_st(const CUtensorMap* m, int c0, int c1, uint32_t src) {
  asm volatile(EL("cp.async.bulk.tensor.2d.global.shared::cta.bulk_group [%0, {%2, %3}], [%1];") ::"l"(m), "r"(src), "r"(c0), "r"(c1) : "memory");
}
DEVINL void bulk_commit() { asm volatile("cp.async.bulk.commit_group;" ::: "memory"); }
template <int N> DEVINL void bulk_wait_n() { asm volatile("cp.async.bulk.wait_group %0;\nbar.warp.sync 0xffffffff;" ::"n"(N) : "memory"); }
DEVINL void l2_prefetch(const void* g, uint32_t bytes) { asm volatile(EL("cp.async.bulk.prefetch.L2.global [%0], %1;") ::"l"(g), "r"(bytes) : "memory"); }
DEVINL void fence_async_smem() { asm volatile("fence.proxy.async.shared::cta;" ::: "memory"); }
DEVINL void fence_async_gl() { asm volatile("fence.proxy.async.global;" ::: "memory"); }
DEVINL void cluster_wait() { asm volatile("barrier.cluster.wait.aligned;" ::: "memory"); }
DEVINL void bar_sync(int id, int n) { asm volatile("bar.sync %0, %1;" ::"r"(id), "r"(n) : "memory"); }
DEVINL void bar_arrive(int id, int n) { asm volatile("bar.arrive %0, %1;" ::"r"(id), "r"(n) : "memory"); }
DEVINL uint32_t ld_acquire(const uint32_t* p) { uint32_t v; asm volatile("ld.acquire.gpu.global.u32 %0, [%1];" : "=r"(v) : "l"(p) : "memory"); return v; }
DEVINL void watch(const uint32_t* p, uint32_t target, uint32_t all, uint32_t tag, uint32_t slot) {
  uint32_t seen = 0;
#pragma unroll 1
  for (uint32_t n = 0; n < 200000u && seen != all; n++) {
    const uint32_t m = __ballot_sync(~0u, (int)(ld_acquire(p) - target) >= 0) & all;
    if (m != seen) { seen = m; asm volatile("st.release.cta.shared.u32 [%0], %1;" ::"r"(slot), "r"(tag << 16 | m) : "memory"); }
  }
}
template <bool RELAXED = false> DEVINL void await_bit(uint32_t slot, uint32_t tag, int j, uint32_t& rdy) {
  if ((rdy >> j) & 1) return;
#pragma unroll 1
  for (uint32_t n = 0; n < 8000000u; n++) {
    uint32_t v;
    asm volatile("ld.acquire.cta.shared.u32 %0, [%1];" : "=r"(v) : "r"(slot) : "memory");
    if ((v >> 16) == tag && ((v >> j) & 1)) { rdy = v; break; }
    if (RELAXED) __nanosleep(200); else if (PSLEEP) __nanosleep(PSLEEP);
  }
  asm volatile("fence.proxy.async.global;" ::: "memory");
}
DEVINL void poll_ge(const uint32_t* p, uint32_t target) {
#pragma unroll 1
  for (uint32_t n = 0; n < 200000u; n++) if (__all_sync(~0u, (int)(ld_acquire(p) - target) >= 0)) break;
}
DEVINL int lane_id() { int v; asm volatile("mov.u32 %0, %%laneid;" : "=r"(v)); return v; }
__host__ DEVINL int remap(int v) {
  const int c = v >> 1, u = c - 36, r = (u * 37) >> 8;
  const int L = max(c - 4 + max(r + 1, 0), (c - 4) >> 31 & (32 + 8 * c));
  return 2 * L + (v & 1);
}
DEVINL int block_id() { int v; asm volatile("mov.u32 %0, %%ctaid.x;" : "=r"(v)); return v; }
#define cta_id() prm.map[block_id()]
#define IDS() const int lane = lane_id(), b = cta_id(), bm = b >> 4, bn = b & 15, rank = b & 1, pm = 2 * bm + (bn >> 3), pn = bn & 7, po = pm & 1; \
  (void)lane; (void)bm; (void)bn; (void)rank; (void)pm; (void)pn; (void)po
DEVINL void st_tagged(unsigned long long* p, uint32_t v, uint32_t tag) {
  asm volatile("{\n.reg .b64 t;\nmov.b64 t, {%1, %2};\nst.relaxed.gpu.global.b64 [%0], t;\n}" ::"l"(p), "r"(v), "r"(tag) : "memory");
}
DEVINL float ex2(float x) { float y; asm("ex2.approx.ftz.f32 %0, %1;" : "=f"(y) : "f"(x)); return y; }
DEVINL float rcp(float x) { float y; asm("rcp.approx.ftz.f32 %0, %1;" : "=f"(y) : "f"(x)); return y; }
DEVINL uint32_t pack2(float lo, float hi) { uint32_t r; asm("cvt.rn.bf16x2.f32 %0, %1, %2;" : "=r"(r) : "f"(hi), "f"(lo)); return r; }
DEVINL float bf_lo(uint32_t w) { return __uint_as_float(w << 16); }
DEVINL float bf_hi(uint32_t w) { return __uint_as_float(w & 0xFFFF0000u); }
DEVINL float bf_round(float x) { return bf_lo(pack2(x, 0.f)); }
DEVINL uint32_t add_bf16x2(uint32_t a, uint32_t b) { uint32_t r; asm("add.rn.bf16x2 %0, %1, %2;" : "=r"(r) : "r"(a), "r"(b)); return r; }
DEVINL uint32_t max_bf2(uint32_t a, uint32_t b) { uint32_t r; asm("max.bf16x2 %0, %1, %2;" : "=r"(r) : "r"(a), "r"(b)); return r; }
DEVINL uint32_t scale_bf2(uint32_t a) {
  uint32_t r;
  asm("{\n.reg .b32 t;\nmul.rn.bf16x2 t, %1, %3;\nfma.rn.bf16x2 %0, %1, %2, t;\n}" : "=r"(r) : "r"(a), "r"(0x3E353E35u), "r"(0x379E379Eu));
  return r;
}
DEVINL void stsm4(uint32_t addr, uint32_t a, uint32_t b, uint32_t c, uint32_t d) {
  asm volatile("stmatrix.sync.aligned.m8n8.x4.shared.b16 [%0], {%1, %2, %3, %4};" ::"r"(addr), "r"(a), "r"(b), "r"(c), "r"(d) : "memory");
}
DEVINL void ldsm4(uint32_t addr, uint32_t (&r)[4]) {
  asm volatile("ldmatrix.sync.aligned.m8n8.x4.shared.b16 {%0, %1, %2, %3}, [%4];" : "=r"(r[0]), "=r"(r[1]), "=r"(r[2]), "=r"(r[3]) : "r"(addr) : "memory");
}
DEVINL void ldsm4t(uint32_t addr, uint32_t (&r)[4]) {
  asm volatile("ldmatrix.sync.aligned.m8n8.x4.trans.shared.b16 {%0, %1, %2, %3}, [%4];" : "=r"(r[0]), "=r"(r[1]), "=r"(r[2]), "=r"(r[3]) : "r"(addr) : "memory");
}
DEVINL void sts128(uint32_t addr, uint32_t a, uint32_t b, uint32_t c, uint32_t d) {
  asm volatile("st.shared.v4.b32 [%0], {%1, %2, %3, %4};" ::"r"(addr), "r"(a), "r"(b), "r"(c), "r"(d) : "memory");
}
DEVINL float4 lds128f(uint32_t addr) { float4 v; asm volatile("ld.shared.v4.f32 {%0, %1, %2, %3}, [%4];" : "=f"(v.x), "=f"(v.y), "=f"(v.z), "=f"(v.w) : "r"(addr) : "memory"); return v; }
DEVINL float lds32f(uint32_t addr) { float v; asm volatile("ld.shared.f32 %0, [%1];" : "=f"(v) : "r"(addr) : "memory"); return v; }
DEVINL float2 lds64f(uint32_t addr) { float2 v; asm volatile("ld.shared.v2.f32 {%0, %1}, [%2];" : "=f"(v.x), "=f"(v.y) : "r"(addr) : "memory"); return v; }
DEVINL void mma16816(float (&d)[4], uint32_t a0, uint32_t a1, uint32_t a2, uint32_t a3, uint32_t b0, uint32_t b1) {
  asm("mma.sync.aligned.m16n8k16.row.col.f32.bf16.bf16.f32 {%0, %1, %2, %3}, {%4, %5, %6, %7}, {%8, %9}, {%0, %1, %2, %3};"
               : "+f"(d[0]), "+f"(d[1]), "+f"(d[2]), "+f"(d[3]) : "r"(a0), "r"(a1), "r"(a2), "r"(a3), "r"(b0), "r"(b1));
}
DEVINL void mma1688(float (&d)[4], uint32_t a0, uint32_t a1, uint32_t b0) {
  asm("mma.sync.aligned.m16n8k8.row.col.f32.bf16.bf16.f32 {%0, %1, %2, %3}, {%4, %5}, {%6}, {%0, %1, %2, %3};"
               : "+f"(d[0]), "+f"(d[1]), "+f"(d[2]), "+f"(d[3]) : "r"(a0), "r"(a1), "r"(b0));
}
DEVINL void mma1688h(float (&d)[4], uint32_t a0, uint32_t a1, uint32_t b0) {
  asm("mma.sync.aligned.m16n8k8.row.col.f32.f16.f16.f32 {%0, %1, %2, %3}, {%4, %5}, {%6}, {%0, %1, %2, %3};"
               : "+f"(d[0]), "+f"(d[1]), "+f"(d[2]), "+f"(d[3]) : "r"(a0), "r"(a1), "r"(b0));
}
DEVINL void mma16816h(float (&d)[4], uint32_t a0, uint32_t a1, uint32_t a2, uint32_t a3, uint32_t b0, uint32_t b1) {
  asm("mma.sync.aligned.m16n8k16.row.col.f32.f16.f16.f32 {%0, %1, %2, %3}, {%4, %5, %6, %7}, {%8, %9}, {%0, %1, %2, %3};"
               : "+f"(d[0]), "+f"(d[1]), "+f"(d[2]), "+f"(d[3]) : "r"(a0), "r"(a1), "r"(a2), "r"(a3), "r"(b0), "r"(b1));
}
template <int N> DEVINL void fence_regs(uint32_t (&d)[N]) {
#pragma unroll
  for (int i = 0; i < N; i++) asm volatile("" : "+r"(d[i])::"memory");
}
template <int N> DEVINL void fence_regs(float (&d)[N]) {
#pragma unroll
  for (int i = 0; i < N; i++) asm volatile("" : "+f"(d[i])::"memory");
}

__device__ __align__(1024) bf16 g_xs[2048 * 1024];
__device__ __align__(1024) bf16 g_os[2048 * 1024];
__device__ __align__(1024) bf16 g_k[32 * 2048 * 32];
__device__ __align__(1024) bf16 g_v[32 * 2048 * 32];
__device__ __align__(128) float2 g_stats[8 * 2048];
__device__ __align__(16) float g_csp[2 * 16 * 8 * 192];
__device__ __align__(128) float g_kn[2 * 128 * 32];
__device__ unsigned long long g_halo[2 * 128 * 32 * 32];
__device__ __align__(128) uint32_t g_cnt[256 * 32];
__device__ uint32_t g_epoch;

DEVINL uint32_t* cnt_x(int l, int bm) { return g_cnt + (l * 8 + bm) * 32; }
DEVINL uint32_t* cnt_o(int l, int pm, int h) { return g_cnt + (32 + (l * 16 + pm) * 2 + h) * 32; }
DEVINL uint32_t* cnt_kv(int lb, int bn) { return g_cnt + (160 + lb * 16 + bn) * 32; }
DEVINL uint32_t* cnt_ad(int bn) { return g_cnt + (192 + bn) * 32; }
DEVINL uint32_t* cnt_cs(int t, int bn) { return g_cnt + (208 + t * 16 + bn) * 32; }

DEVINL int qord(int i, int l, int pn) { return l == 0 ? i : i < 4 ? ((2 * pn) ^ (i & 2)) + (i & 1) : i - 4 < 2 * (pn & 6) ? i - 4 : i; }
struct Params {
  CUtensorMap m[17];
  const bf16* x0;
  const bf16* wq[2];
  const bf16* wo[2];
  uint32_t* epoch;
  uint32_t zero;
  int map[128];
};
enum { M_X0A = 0, M_XSA, M_WQA, M_WQB, M_WOA, M_WOB, M_OS, M_K, M_V, M_X0R, M_XSR, M_XSO, M_OUT, M_XST, M_X0H, M_K4, M_V4, M_COUNT };

constexpr uint32_t QSTG = 57344;
constexpr uint32_t T0 = 65536, TSTG = 32768;
constexpr uint32_t ONES = 229376;
constexpr uint32_t PSTG = 32768, RES = 196608;
constexpr uint32_t ASC = 17408;
constexpr uint32_t RSTD = 229376, MEAN = 230400, COLS = 230912, KMAX = 231680, B_QD = 231688, BARS = 232192, SMEM_BYTES = 232448;
constexpr uint32_t B_QF = BARS, B_QE = BARS + 32, B_TF = BARS + 64, B_TE = BARS + 96, B_PF = BARS + 128, B_PE = BARS + 176,
                   B_RF = BARS + 224, W_X = BARS + 232, W_O = BARS + 236, B_QL = BARS + 240, B_PA = BARS + 248;
enum { NB_ST = 1, NB_KV = 2  , NB_DONE = 3, NB_SC = 4, NB_SIG = 5  , NB_KN = 9  , NB_X = 11, NB_HALO = 12  , NB_X0 = 15 };

DEVINL uint32_t pslot_b(uint32_t s, int l) { return ((((l & 1) ? 0x320415u : 0x468795u) >> (4 * s)) & 15) * 16384u; }
DEVINL uint32_t pslot_a(uint32_t s, int l) { return ((((l & 1) ? 0xBA7896u : 0x32DCBAu) >> (4 * s)) & 15) * 16384u; }

#define G1 2
#define G2 0
#define G3 2
#define KC (11 + 2 * wg)
#define NA2 2
#define RESI 12
#define PERHEAD 1
#define PFETCH 0
#define PFW 3
#define PFI 8
#define H1ST 4
#define H1RED 5
#define WGBAR 0
#define NRB 16
#define LEAHI 2
#define ONECOL 0
#define OSD 1
#define PPEEL 0
#define HUNR 0
#define NQ 32
#define OA 0x10
#define OB 0x10
#define LAG 2
#define NQB NQ
#define QK_A wgmma_m64n32k16_rs_nb_h
#define QK_B wgmma_m64n32k16_rs_nb_hh
constexpr float QSCALE = 0.17677669529663687f * 1.4426950408889634f;

DEVINL uint32_t hfma2(uint32_t a, uint32_t b, uint32_t c) { uint32_t r; asm("fma.rn.f16x2 %0, %1, %2, %3;" : "=r"(r) : "r"(a), "r"(b), "r"(c)); return r; }
DEVINL uint32_t pack2h(float lo, float hi) { uint32_t r; asm("cvt.rn.f16x2.f32 %0, %1, %2;" : "=r"(r) : "f"(hi), "f"(lo)); return r; }
DEVINL uint32_t h2_to_bf2(uint32_t h) {
  float a, b;
  asm("{\n.reg .b16 l, h;\nmov.b32 {l, h}, %2;\ncvt.f32.f16 %0, l;\ncvt.f32.f16 %1, h;\n}" : "=f"(a), "=f"(b) : "r"(h));
  return pack2(a, b);
}
DEVINL uint32_t exp2_h2(uint32_t s, uint32_t zero) {
  const uint32_t r = hfma2(s, 0x00800080u, 0x007E007Eu);
  const uint32_t g = hfma2(hfma2(r, 0xF800F800u, 0x33FD33FDu), 0x44004400u, s);
  return (LEAHI == 2 ? __funnelshift_l(r, r, 7) : LEAHI ? __funnelshift_l(zero, r, 7) : r * 128u) + hfma2(hfma2(g, g, 0x0DE10DE1u), g, 0x00300030u);
}
constexpr uint32_t NOT_F16 = 0x7FC00000u, K_LO = 0x35000000u  ;
DEVINL uint32_t f16_class(uint32_t norm2, uint32_t lo) { return norm2 - lo > 0x4E800000u - lo ? NOT_F16 : norm2; }

DEVINL void attn_slow(const uint32_t (&q)[8], float up, int head, const float* kn, float (&res)[20], int lane) {
  const int g = lane >> 2, qd = lane & 3;
  const bf16* kb = g_k + (size_t)head * 2048 * 32;
  const bf16* vb = g_v + (size_t)head * 2048 * 32;
  float o[4][4], m0 = -INFINITY, m1 = -INFINITY, l0 = 0.f, l1 = 0.f;
#pragma unroll
  for (int j = 0; j < 4; j++) { o[j][0] = o[j][1] = o[j][2] = o[j][3] = 0.f; }
#pragma unroll 1
  for (int k0 = 0; k0 < 2048; k0 += 16) {
    float s[2][4];
    const bool kh = __float_as_uint(__ldcg(kn + (k0 >> 8) * 32 + ((k0 >> 6) & 1) * 8 + ((k0 >> 7) & 1) * 4 + ((k0 >> 4) & 3))) != NOT_F16;
#pragma unroll
    for (int nt = 0; nt < 2; nt++) {
      s[nt][0] = s[nt][1] = s[nt][2] = s[nt][3] = 0.f;
      const uint32_t* kp = (const uint32_t*)(kb + (size_t)(k0 + nt * 8 + g) * 32) + qd;
      uint32_t kf[4];
#pragma unroll
      for (int i = 0; i < 4; i++) { kf[i] = __ldcg(kp + 4 * i); if (kh) kf[i] = h2_to_bf2(kf[i]); }
      mma16816(s[nt], q[0], q[1], q[2], q[3], kf[0], kf[1]);
      mma16816(s[nt], q[4], q[5], q[6], q[7], kf[2], kf[3]);
      s[nt][0] *= up; s[nt][1] *= up; s[nt][2] *= up; s[nt][3] *= up;
    }
    float a0 = fmaxf(fmaxf(s[0][0], s[0][1]), fmaxf(s[1][0], s[1][1]));
    float a1 = fmaxf(fmaxf(s[0][2], s[0][3]), fmaxf(s[1][2], s[1][3]));
    a0 = fmaxf(a0, __shfl_xor_sync(~0u, a0, 1)); a0 = fmaxf(a0, __shfl_xor_sync(~0u, a0, 2));
    a1 = fmaxf(a1, __shfl_xor_sync(~0u, a1, 1)); a1 = fmaxf(a1, __shfl_xor_sync(~0u, a1, 2));
    const float n0 = fmaxf(m0, a0), n1 = fmaxf(m1, a1);
    const float c0 = (m0 == n0) ? 1.f : ex2(m0 - n0), c1 = (m1 == n1) ? 1.f : ex2(m1 - n1);
    m0 = n0; m1 = n1;
    const uint32_t p0 = pack2(ex2(s[0][0] - n0), ex2(s[0][1] - n0)), p1 = pack2(ex2(s[0][2] - n1), ex2(s[0][3] - n1));
    const uint32_t p2 = pack2(ex2(s[1][0] - n0), ex2(s[1][1] - n0)), p3 = pack2(ex2(s[1][2] - n1), ex2(s[1][3] - n1));
    l0 = l0 * c0 + bf_lo(p0) + bf_hi(p0) + bf_lo(p2) + bf_hi(p2);
    l1 = l1 * c1 + bf_lo(p1) + bf_hi(p1) + bf_lo(p3) + bf_hi(p3);
#pragma unroll
    for (int j = 0; j < 4; j++) {
      o[j][0] *= c0; o[j][1] *= c0; o[j][2] *= c1; o[j][3] *= c1;
      const unsigned short* vp = (const unsigned short*)(vb + (size_t)(k0 + 2 * qd) * 32 + j * 8 + g);
      const uint32_t b0 = (uint32_t)__ldcg(vp) | ((uint32_t)__ldcg(vp + 32) << 16);
      const uint32_t b1 = (uint32_t)__ldcg(vp + 256) | ((uint32_t)__ldcg(vp + 288) << 16);
      mma16816(o[j], p0, p1, p2, p3, b0, b1);
    }
  }
  l0 += __shfl_xor_sync(~0u, l0, 1); l0 += __shfl_xor_sync(~0u, l0, 2);
  l1 += __shfl_xor_sync(~0u, l1, 1); l1 += __shfl_xor_sync(~0u, l1, 2);
#pragma unroll
  for (int j = 0; j < 4; j++) { res[4 * j] = o[j][0]; res[4 * j + 1] = o[j][1]; res[4 * j + 2] = o[j][2]; res[4 * j + 3] = o[j][3]; }
  res[16] = l0; res[18] = l1;
}

__global__ void __cluster_dims__(2, 1, 1) __launch_bounds__(384, 1) fused_kernel(const __grid_constant__ Params prm) {
  extern __shared__ __align__(1024) char smem[];
  const uint32_t sb = (uint32_t)__cvta_generic_to_shared(smem);
  const int tid = threadIdx.x;
  const int wid = __shfl_sync(0xffffffffu, tid >> 5, 0), wg = wid >> 2, w = wid & 3;
  const int bm = remap(blockIdx.x) >> 4, bn = remap(blockIdx.x) & 15;
  auto first_tile = [&](int kt) {
    e_expect_tx(sb + B_QF + 8 * kt, QSTG);
    tma_ld(sb + kt * QSTG, &prm.m[M_X0A], kt * 64, bm * 256, sb + B_QF + 8 * kt);
    tma_ld3(sb + kt * QSTG + 32768, &prm.m[M_WQA], bn * 64, kt * 64, 0, sb + B_QF + 8 * kt);
  };
  if (wid == 8) {
    e_init(sb + B_QF, 1);
    asm volatile("fence.mbarrier_init.release.cluster;" ::: "memory");
    first_tile(0);
  }
  if (wid < 8) {
#pragma unroll
    for (int i = 0; i < 4; i++) {
      const uint32_t cnt = (uint32_t)((i == 0 ? 0x14112140 : i == 1 ? 0x04112141 : i == 2 ? 0x14412141 : 0x24412141) >> (4 * wid)) & 7;
      if (cnt) e_init(sb + BARS + 32 * wid + 8 * i, cnt);
    }
    if (wid == 0 || wid == 7) e_init(sb + B_QD + (wid & 1) * 8, 1);
    if (tid == 255) *(uint2*)(smem + W_X) = make_uint2(0u, 0u);
    asm volatile("fence.mbarrier_init.release.cluster;" ::: "memory");
  }
  const uint32_t epoch = *(volatile uint32_t*)prm.epoch;
  __syncthreads();
  asm volatile("barrier.cluster.arrive.relaxed.aligned;" ::: "memory");

  if (wg == 2) {
    asm volatile("setmaxnreg.dec.sync.aligned.u32 56;");
    const uint32_t ep1 = epoch + 1;
    if (w == 0) {
      first_tile(1);
      mbar_wait(sb + B_QF, 0);
      first_tile(2); first_tile(3);
#pragma unroll 1
      for (int kt = 4; kt < 16; kt++) l2_prefetch(prm.wq[0] + kt * 196608 + blockIdx.x * 1536, 3072);
      cluster_wait();
#pragma unroll 1
      for (int l = 0; l < 4; l++) {
        IDS();
        const CUtensorMap* mw = &prm.m[M_WQA + (l & 1)];
        const CUtensorMap* mh = &prm.m[l == 0 ? M_X0H : M_XSO];
        const CUtensorMap* mo = &prm.m[M_WOA + (l & 1)];
        auto q_b = [&](int i) {
          const int s = i & 3;
          mbar_wait(sb + B_QE + 8 * s, ((i >> 2) & 1) ^ 1);
          e_expect_tx(sb + B_QF + 8 * s, QSTG);
          tma_ld3(sb + s * QSTG + 32768, mw, bn * 64, qord(i, l, pn) * 64, 0, sb + B_QF + 8 * s);
        };
        uint32_t rdy = l ? 0u : ~0u;
        auto q_a = [&](int i) {
          const int kt = qord(i, l, pn);
          await_bit(sb + W_X, l, kt >> 1, rdy);
          tma_ld_mc(sb + (i & 3) * QSTG + rank * 16384, mh, kt * 64, bm * 256 + rank * 128, sb + B_QF + 8 * (i & 3));
        };
        if (l > 0) {
#pragma unroll 1
          for (int i = 0; i < 4; i++) {
            const int kt = qord(i, l, pn);
            await_bit(sb + W_X, l, kt >> 1, rdy);
            e_expect_tx(sb + B_QF + 8 * i, 16384);
            tma_ld(sb + i * QSTG + (po ^ 1) * 16384, &prm.m[M_XSO], kt * 64, (pm ^ 1) * 128, sb + B_QF + 8 * i);
          }
        }
#pragma unroll 1
        for (int i = 4; i < 16; i++) {
          q_b(i); q_a(i);
          if (l == 0 && (PFW & 1) && i >= PFI && i < PFI + 4) l2_prefetch(prm.wq[1] + (blockIdx.x * 4 + i - PFI) * 6144, 12288);
          if (l < 2 && (PFW & 2) && i == PFI + 4) l2_prefetch(prm.wo[l] + blockIdx.x * 8192, 16384);
        }
        if (l & 1) {
          if (l == 3) poll_ge(cnt_ad(bn), ep1 * 16);
          const int krow = 2 * bn * 2048 + bm * 256;
          uint32_t* kvc = cnt_kv(l >> 1, bn);
#pragma unroll 1
          for (int m = 1; m >= 0; m--) {
            bar_sync(m ? NB_ST : NB_KV, 288);
#pragma unroll
            for (int i = 0; i < 4; i++) tma_st(&prm.m[M_K4 + (i >> 1)], 0, krow + (i & 1) * 128 + m * 64, sb + T0 + i * 8192 + m * 4096);
            if (m) {
              sts128(sb + ONES + lane * 32, 0x3f803f80u, 0x3f803f80u, 0x3f803f80u, 0x3f803f80u);
              sts128(sb + ONES + lane * 32 + 16, 0x3f803f80u, 0x3f803f80u, 0x3f803f80u, 0x3f803f80u);
              fence_async_smem();
              __syncwarp();
            }
          }
          e_arrive(sb + B_TF);
          bulk_commit(); bulk_wait_n<0>();
          e_red(kvc + bm);
          bar_sync(NB_KV + 12, 288);
          uint32_t seen = 0;
#pragma unroll 1
          for (int it = 1; it < 16; it++) {
            const int s = it & 3, blk = it;
            if (it == H1ST) { tma_st(&prm.m[M_K], 0, krow + 2048, sb); tma_st(&prm.m[M_V], 0, krow + 2048, sb + 16384); bulk_commit(); }
            if (it == H1RED) { bulk_wait_n<0>(); e_red(kvc + bm); }
            if (it == 12) { e_expect_tx(sb + B_RF, 32768); tma_ld3(sb + RES, &prm.m[M_XSR], 0, pm * 128, 2 * pn, sb + B_RF); }
            if (it == 2 || it == 3) mbar_wait(sb + B_TF + 8 * (it - 1), 0);
            MWL(sb + B_TE + 8 * s, ((it >> 2) & 1) ^ 1);
            if (it < 8) {
#pragma unroll 1
              for (uint32_t n = 0; n < 200000u && !((seen >> it) & 1); n++)
                seen = __ballot_sync(~0u, (int)(ld_acquire(kvc + ((bm + lane) & 7)) - (ep1 * 2 - 1)) >= 0);
              fence_async_gl();
            } else if (it == 8) { poll_ge(kvc + (lane & 7), ep1 * 2); fence_async_gl(); bar_arrive(NB_HALO, 64); }
            else if (it == 15) bar_arrive(NB_HALO + 1, 64);
            const int row = (2 * bn + (it >> 3)) * 2048 + ((bm + blk) & 7) * 256;
            e_expect_tx(sb + B_TF + 8 * s, 32768);
            tma_ld(sb + T0 + s * TSTG, &prm.m[M_K], 0, row, sb + B_TF + 8 * s);
            tma_ld(sb + T0 + s * TSTG + 16384, &prm.m[M_V], 0, row, sb + B_TF + 8 * s);
          }
        }
        auto p_b = [&](int i, uint32_t s, uint32_t par) {
          mbar_wait(sb + B_PE + 8 * s, par ^ 1);
          e_expect_tx(sb + B_PF + 8 * s, PSTG);
          tma_ld5(sb + pslot_b(s, l), mo, i >> 3, 2 * (i & 7), 2 * pn, sb + B_PF + 8 * s);
        };
        auto p_a = [&](int i, uint32_t s) {
          await_bit(sb + W_O, l + 1, i, rdy);
          tma_ld_mc(sb + pslot_a(s, l) + rank * 8192, &prm.m[M_OS], i * 64, pm * 128 + rank * 64, sb + B_PF + 8 * s);
        };
        auto p_a2 = [&](int i) {
          await_bit(sb + W_O, l + 1, i, rdy);
          tma_ld(sb + pslot_a(i, l), &prm.m[M_OS], i * 64, pm * 128, sb + B_PF + 8 * i);
          tma_ld(sb + pslot_a(i, l) + 8192, &prm.m[M_OS], i * 64, pm * 128 + 64, sb + B_PF + 8 * i);
        };
        rdy = 0;
        if (l & 1) {
#pragma unroll 1
          for (int u = 0; u < 6; u++) { const int i = (0x205413 >> (4 * u)) & 7; if (u == 4) MWL(sb + B_TE, 1); p_b(i, i, i < 4 ? 1 : 0); }
#pragma unroll 1
          for (int u = 0; u < 6; u++) {
            const int i = (0x542130 >> (4 * u)) & 7;
            if (!(u & 1)) MWL(sb + B_TE + 8 + 4 * u, 1);
            p_a2(i);
          }
        } else {
#pragma unroll 1
          for (int u = 0; u < 5; u++) { const int i = (0x32140 >> (4 * u)) & 7; if (!(u & 5)) mbar_wait(sb + B_QE + 8 + 4 * u, 1); p_b(i, i, 0); }
          mbar_wait(sb + B_QE + 24, 1);
          if (PLATE) bar_sync(NB_KN, 96);
#pragma unroll 1
          for (int i = 0; i < 4; i++) { if (i < NA2) p_a2(i); else p_a(i, i); }
          bar_sync(NB_DONE, 96);
          e_arrive_both(sb + B_PA);
          p_b(5, 5, 0);
          mbar_wait(sb + B_PA, (l >> 1) & 1);
          p_a(4, 4); p_a(5, 5);
        }
        uint32_t s = 0, lap = 1;
#pragma unroll 1
        for (int i = 6; i < 16; i++) {
          if (i == RESI && !(l & 1)) { e_expect_tx(sb + B_RF, 32768); tma_ld3(sb, &prm.m[l == 0 ? M_X0R : M_XSR], 0, pm * 128, 2 * pn, sb + B_RF); }
          p_b(i, s, ((s < 4 ? l : 0) + lap) & 1);
          p_a(i, s);
          if (++s == 6) { s = 0; lap++; }
        }
        const CUtensorMap* mn = &prm.m[M_WQA + ((l + 1) & 1)];
        if (l < 3) {
          mbar_wait(sb + B_PE + 8 * 4, 1); mbar_wait(sb + B_PE + 8 * 5, 1);
          tma_ld3(sb + 32768, mn, bn * 64, 2 * pn * 64, 0, sb + B_QL);
          mbar_wait(sb + B_PE + 8 * 0, l & 1);
          tma_ld3(sb + QSTG + 32768, mn, bn * 64, (2 * pn + 1) * 64, 0, sb + B_QL);
          mbar_wait(sb + B_PE + 8 * 1, l & 1);
          e_expect_tx(sb + B_QD, 40960);
          tma_ld3(sb + 2 * QSTG + 32768, mn, bn * 64, ((2 * pn) ^ 2) * 64, 0, sb + B_QD);
          bar_sync(NB_X, 288);
          e_expect_tx(sb + B_QL, 49152);
          e_expect_tx(sb + B_QD + 8, 40960);
          tma_ld3(sb + 3 * QSTG + 32768, mn, bn * 64, (((2 * pn) ^ 2) + 1) * 64, 0, sb + B_QD + 8);
        }
      }
      if (blockIdx.x == 0 && lane_id() == 0) *(volatile uint32_t*)prm.epoch = ep1;
    } else {
      const int hw = w - 1;
      if (hw == 1 && lane_id() < M_COUNT) asm volatile("prefetch.tensormap [%0];" ::"l"(&prm.m[lane_id()]) : "memory");
      cluster_wait();
      mbar_wait(sb + B_QF, 0);
#pragma unroll 1
      for (int l = 0; l < 4; l++) {
        IDS();
        if (hw == 2 && l > 0) watch(cnt_x(l, bm) + (lane & 7), ep1 * 2, 0xFFu, l, sb + W_X);
        if (l == 0) {
#pragma unroll 1
          for (int r = 2 * hw; r < 16; r += 6) {
            const uint4* p = (const uint4*)(prm.x0 + (size_t)(b * 16 + r) * 1024) + lane;
            float s1[2] = {0.f, 0.f}, s2[2] = {0.f, 0.f};
#pragma unroll
            for (int i = 0; i < 8; i++) {
              const uint4 v = __ldg(p + 32 * i);
              const uint32_t u[4] = {v.x, v.y, v.z, v.w};
#pragma unroll
              for (int k = 0; k < 4; k++) { const float a = bf_lo(u[k]), c = bf_hi(u[k]); s1[i >> 2] += a + c; s2[i >> 2] = fmaf(a, a, fmaf(c, c, s2[i >> 2])); }
            }
#pragma unroll
            for (int o = 16; o; o >>= 1)
#pragma unroll
              for (int rr = 0; rr < 2; rr++) { s1[rr] += __shfl_xor_sync(~0u, s1[rr], o); s2[rr] += __shfl_xor_sync(~0u, s2[rr], o); }
            if (lane == 0) *(float4*)&g_stats[b * 16 + r] = make_float4(s1[0], s2[0], s1[1], s2[1]);
          }
        }
        if (l == 1) { uint32_t rdy = 0; await_bit<true>(sb + W_X, 1, pn, rdy); mbar_hint(sb + B_QF + 8, 0); }
        if (l < 2) {
          float cs[8];
#pragma unroll
          for (int i = 0; i < 8; i++) cs[i] = 0.f;
          const uint4* wp = (const uint4*)(prm.wq[l] + (size_t)(bm * 128 + (lane >> 3)) * 3072 + hw * 1024 + bn * 64) + (lane & 7);
#pragma unroll 8
          for (int i = 0; i < 32; i++) {
            const uint4 v = __ldg(wp + (size_t)i * 4 * 384);
            cs[0] += bf_lo(v.x); cs[1] += bf_hi(v.x); cs[2] += bf_lo(v.y); cs[3] += bf_hi(v.y);
            cs[4] += bf_lo(v.z); cs[5] += bf_hi(v.z); cs[6] += bf_lo(v.w); cs[7] += bf_hi(v.w);
          }
#pragma unroll
          for (int i = 0; i < 8; i++) { cs[i] += __shfl_xor_sync(~0u, cs[i], 8); cs[i] += __shfl_xor_sync(~0u, cs[i], 16); }
          if (lane < 8) {
            float4* d = (float4*)(g_csp + ((l * 16 + bn) * 8 + bm) * 192 + hw * 64 + lane * 8);
            d[0] = make_float4(cs[0], cs[1], cs[2], cs[3]); d[1] = make_float4(cs[4], cs[5], cs[6], cs[7]);
          }
          __syncwarp();
          asm volatile("fence.acq_rel.gpu;" ::: "memory");
          e_red_relaxed(cnt_cs(l, bn));
          if (l == 0) e_red_relaxed(cnt_x(0, bm) + pn);
          poll_ge(lane < 8 && l == 0 ? cnt_x(0, bm) + lane : cnt_cs(l, bn), ep1 * (lane < 8 && l == 0 ? 6 : 24));
        }
        if (l > 0) {
          uint32_t rdy = 0;
#pragma unroll 1
          for (int j = 0; j < 8; j++) await_bit<true>(sb + W_X, l, j, rdy);
        }
#pragma unroll 1
        for (int it = hw * 32 + lane; it < 176; it += 96) {
          const bool rows = it < 128;
          const float4* p = rows ? (const float4*)(g_stats + bm * 256) + it : (const float4*)(g_csp + ((l & 1) * 16 + bn) * 8 * 192) + (it - 128);
          const int stride = rows ? 1024 : 48, np = rows && l == 0 ? 1 : 8;
          float4 a = make_float4(0.f, 0.f, 0.f, 0.f);
#pragma unroll
          for (int k = 0; k < 8; k++) if (k < np) { const float4 v = __ldcg(p + k * stride); a.x += v.x; a.y += v.y; a.z += v.z; a.w += v.w; }
          if (rows) {
            const float m0 = a.x * (1.f / 1024.f), m1 = a.z * (1.f / 1024.f);
            const float v0 = fmaxf(a.y * (1.f / 1024.f) - m0 * m0, 0.f), v1 = fmaxf(a.w * (1.f / 1024.f) - m1 * m1, 0.f);
            const float r0 = __fdividef(1.f, bf_round(sqrtf(bf_round(bf_round(v0) + 1e-5f)))), r1 = __fdividef(1.f, bf_round(sqrtf(bf_round(bf_round(v1) + 1e-5f))));
            *(float2*)(smem + RSTD + it * 8) = make_float2(r0, r1);
            *(uint32_t*)(smem + MEAN + it * 4) = pack2(-m0, -m1);
          } else {
            float2* d = (float2*)(smem + COLS) + ((it - 128) >> 2) * 8 + (it & 1) * 4 + ((it >> 1) & 1);
            d[0] = make_float2(a.y, a.x); d[2] = make_float2(a.w, a.z);
          }
        }
        __syncwarp();
        if (lane == 0) asm volatile("red.release.cta.shared.add.u32 [%0], 0x100;" ::"r"(sb + W_X) : "memory");
        if (hw == 2) {
          if (!(l & 1)) {
            bar_sync(NB_ST, 288);
            const volatile unsigned long long* hp = g_halo + ((size_t)(l >> 1) * 128 + b - 16) * 1024 + lane;
#pragma unroll 1
            for (int h = 0; h < 2; h++) {
              uint32_t t[16];
#pragma unroll
              for (int i = 0; i < 16; i++) t[i] = 0;
#pragma unroll 1
              for (uint32_t n = bm ? 0 : 100000u; n < 100000u; n++) {
                uint32_t miss = 0;
#pragma unroll
                for (int i = 0; i < 16; i++) {
                  const unsigned long long v = hp[h * 512 + i * 32];
                  t[i] = (uint32_t)v; miss |= (uint32_t)(v >> 32) ^ ep1;
                }
                if (__all_sync(~0u, !miss)) break;
              }
              const uint32_t r = (lane & 7) + ((lane >> 3) & 1) * 8, rv = lane >> 2;
#pragma unroll
              for (int jj = 0; jj < 2; jj++) stsm4(sb + 2 * h * ASC + r * 64 + (((2 * jj + (lane >> 4)) ^ ((r >> 1) & 3)) << 4), t[4 * jj], t[4 * jj + 1], t[4 * jj + 2], t[4 * jj + 3]);
              const uint32_t ad = sb + (2 * h + 1) * ASC + rv * 64 + (((lane & 3) ^ ((rv >> 1) & 3)) << 4);
              sts128(ad, t[8], t[10], t[12], t[14]); sts128(ad + 512, t[9], t[11], t[13], t[15]);
              bar_arrive(NB_HALO + h, 64);
            }
          } else {
            bar_sync(NB_HALO, 64);
            const uint4* kp = (const uint4*)(g_kn + ((l >> 1) * 128 + bn * 8) * 32) + 2 * lane;
            const uint4 v = __ldcg(kp), u = __ldcg(kp + 1);
            const uint32_t mx = max(max(max(v.x, v.y), max(v.z, v.w)), max(max(u.x, u.y), max(u.z, u.w)));
            const uint32_t m0 = __reduce_max_sync(~0u, (lane & 2) ? 0u : mx), m1 = __reduce_max_sync(~0u, (lane & 2) ? mx : 0u);
            if (lane == 0) *(uint2*)(smem + KMAX) = make_uint2(m0, m1);
            __syncwarp();
            bar_arrive(NB_KN, 160); bar_arrive(NB_KN + 1, 160);
            bar_sync(NB_HALO + 1, 64);
            watch(cnt_o(l, pm, 0) + (lane & 7), ep1 * 2, 0xFFu, l + 1, sb + W_O);
          }
        } else {
          bar_sync(NB_SIG + 2 * hw, 160); bar_sync(NB_SIG + 2 * hw + 1, 160);
          if (!(l & 1)) bar_arrive(NB_DONE, 96);
          if (hw == (l & 1)) bar_arrive((l & 1) ? NB_DONE : NB_KN, (l & 1) ? 64 : 64 + 32 * PLATE);
          asm volatile("fence.acq_rel.gpu;" ::: "memory");
          e_red_relaxed(cnt_o(l, 2 * bm, hw) + (bn >> 1));
          e_red_relaxed(cnt_o(l, 2 * bm + 1, hw) + (bn >> 1));
          if (hw == 1 && l == 1) { e_red_relaxed(cnt_ad(bn)); e_red_relaxed(cnt_ad(bn)); }
        }
        if (hw == 2) { bar_sync((l & 1) ? NB_DONE : NB_KN, (l & 1) ? 64 : 64 + 32 * PLATE); watch(cnt_o(l, pm, (lane >> 3) & 1) + (lane & 7), ep1 * 2, 0xFFFFu, l + 1, sb + W_O); }
        if (hw < 2 + XLATE && l < 3) {
          bar_sync(NB_X0, 320 + 32 * XLATE);
          if (hw == 0) {
            e_red(cnt_x(l + 1, bm) + pn);
          } else if (hw == 1) {
            mbar_wait(sb + B_PE + 8 * 3, l & 1);
            push_peer(sb + 2 * QSTG + po * 16384, sb + po * 16384, sb + B_QD, rank ^ 1);
            push_peer(sb + 3 * QSTG + po * 16384, sb + QSTG + po * 16384, sb + B_QD + 8, rank ^ 1);
          }
        }
      }
    }
  } else {
    asm volatile("setmaxnreg.inc.sync.aligned.u32 224;");
    const uint32_t zero = prm.zero;
    cluster_wait();
    const uint32_t ep1 = __shfl_sync(~0u, epoch + 1, 0);
#pragma unroll 1
    for (int l = 0; l < 4; l++) {
      {
        float acc[2][96];
#pragma unroll
        for (int i = 0; i < 96; i++) { acc[0][i] = 0.f; acc[1][i] = 0.f; }
        fence_regs(acc[0]); fence_regs(acc[1]);
        const bool early = l > 0 && wg == ((cta_id() >> 3) & 1);
#pragma unroll 1
        for (int kt = 0; kt < 14; kt++) {
          const int s = kt & 3;
          if (l > 0 && kt < 4 && kt != 1) mbar_wait(sb + (kt ? B_QD - 16 + 8 * kt : B_QL), (l + 1) & 1);
          if (!(early && kt < 4)) mbar_wait(sb + B_QF + 8 * s, (kt >> 2) & 1);
          const uint64_t da = mkdesc(sb + s * QSTG + wg * 16384, 16, 1024, 1), db = mkdesc(sb + s * QSTG + 32768, 8192, 1024, 1);
          wg_fence();
#pragma unroll
          for (int k = 0; k < 4; k++)
#pragma unroll
            for (int m = 0; m < 2; m++) wgmma_m64n192k16_ss_tb(acc[m], da + m * 512 + k * 2, db + k * 128, 1);
          wg_commit();
          wg_wait<1>();
          if (early && kt < 5) {
#pragma unroll 1
            for (int i = kt == 3 ? 0 : 3; i < kt; i++) { mbar_wait(sb + B_QF + 8 * i, 0); if (w == 0) e_arrive_both(sb + B_QE + 8 * i); }
          } else if (kt > 0 && w == 0) e_arrive_both(sb + B_QE + 8 * ((kt - 1) & 3));
          if (kt == KC) {
#pragma unroll 1
            for (uint32_t n = 0; n < 4000000u; n++) {
              uint32_t v;
              asm volatile("ld.acquire.cta.shared.u32 %0, [%1];" : "=r"(v) : "r"(sb + W_X) : "memory");
              if ((v >> 8) == (uint32_t)(l * 256 + 3)) break;
            }
            const int lane = lane_id();
            float nm[4];
#pragma unroll
            for (int i = 0; i < 4; i++) nm[i] = bf_lo(*(volatile unsigned short*)(smem + MEAN + (wg * 128 + w * 16 + (lane >> 2) + (i >> 1) * 64 + (i & 1) * 8) * 2));
            wg_wait<0>();
            fence_regs(acc[0]); fence_regs(acc[1]);
#pragma unroll
            for (int j = 0; j < 12; j++) {
              const float4 c = lds128f(sb + COLS + j * 64 + (lane & 3) * 16);
#pragma unroll
              for (int m = 0; m < 2; m++) {
                float* a = &acc[m][8 * j];
                a[0] = fmaf(nm[2 * m], c.y, a[0]); a[1] = fmaf(nm[2 * m], c.x, a[1]); a[2] = fmaf(nm[2 * m + 1], c.y, a[2]); a[3] = fmaf(nm[2 * m + 1], c.x, a[3]);
                a[4] = fmaf(nm[2 * m], c.w, a[4]); a[5] = fmaf(nm[2 * m], c.z, a[5]); a[6] = fmaf(nm[2 * m + 1], c.w, a[6]); a[7] = fmaf(nm[2 * m + 1], c.z, a[7]);
              }
            }
            fence_regs(acc[0]); fence_regs(acc[1]);
          }
        }
        auto part = [&](int s, int m, int k0, int k1) {
          const uint64_t da = mkdesc(sb + s * QSTG + wg * 16384 + m * 8192, 16, 1024, 1), db = mkdesc(sb + s * QSTG + 32768, 8192, 1024, 1);
          pin(zero);
          wg_fence();
#pragma unroll
          for (int k = k0; k < k1; k++) wgmma_m64n192k16_ss_tb(acc[m], da + k * 2, db + k * 128, 1);
          wg_commit();
          pin(zero);
        };
        mbar_wait(sb + B_QF + 16, 1);
        part(2, 1, 0, 4);
        wg_wait<1>();
        if (w == 0) e_arrive_both(sb + B_QE + 8);
        if (!(l & 1)) bar_arrive(NB_ST, 288);
        mbar_wait(sb + B_QF + 24, 1);
        part(3, 1, 0, 4);
        part(2, 0, 0, G1);
        IDS();
        const int g = lane >> 2, qd = lane & 3;
        float rs[2][2];
#pragma unroll
        for (int i = 0; i < 4; i++) rs[i >> 1][i & 1] = lds32f(sb + RSTD + (wg * 128 + w * 16 + g + (i >> 1) * 64 + (i & 1) * 8) * 4);
        auto scale = [&](int gi, int m, float sc) {
          const float r0 = rs[m][0] * sc, r1 = rs[m][1] * sc;
#pragma unroll
          for (int i = 0; i < 16; i++) acc[m][16 * gi + i] *= (i & 2) ? r1 : r0;
        };
        auto pack_b = [&](int gi, int m, uint32_t (&t)[8]) {
#pragma unroll
          for (int i = 0; i < 8; i++) t[i] = pack2(acc[m][16 * gi + 2 * i], acc[m][16 * gi + 2 * i + 1]);
        };
        auto norm_tile = [&](int gi, int m, uint32_t (&t)[8]) { scale(gi, m, 1.f); pack_b(gi, m, t); };
        auto pack_h = [&](int gi, int m, uint32_t (&t)[8]) {
#pragma unroll
          for (int i = 0; i < 8; i++) t[i] = pack2h(acc[m][16 * gi + 2 * i], acc[m][16 * gi + 2 * i + 1]);
        };
        uint32_t q[2][2][8], qn[2][2];
        const uint32_t srow = (lane & 7) + ((lane >> 3) & 1) * 8;
        const uint32_t row0 = wg * 128 + w * 16;
        auto put_kv = [&](int h, int v, int m, const uint32_t (&t)[8]) {
          const uint32_t base = sb + ((l & 1) ? (h ? 0 : T0) + v * 16384 : (2 * h + v) * ASC + 1024) + (row0 + m * 64) * 64;
          if (!v) {
#pragma unroll
            for (int jj = 0; jj < 2; jj++) stsm4(base + srow * 64 + (((2 * jj + (lane >> 4)) ^ ((srow >> 1) & 3)) << 4), t[4 * jj], t[4 * jj + 1], t[4 * jj + 2], t[4 * jj + 3]);
          } else {
            const uint32_t ad = base + g * 64 + ((qd ^ (g >> 1)) << 4);
            sts128(ad, t[0], t[2], t[4], t[6]); sts128(ad + 512, t[1], t[3], t[5], t[7]);
          }
        };
        auto send_halo = [&](int h, int v, const uint32_t (&t)[8]) {
          unsigned long long* hp = g_halo + ((size_t)(l >> 1) * 128 + b) * 1024 + h * 512 + v * 256 + lane;
#pragma unroll
          for (int i = 0; i < 8; i++) st_tagged(hp + i * 32, t[i], ep1);
        };
        auto put_kn = [&](int h, int m, uint32_t kn) {
          if (lane == 0) g_kn[((l >> 1) * 128 + bn * 8 + bm) * 32 + 16 * h + 8 * m + wg * 4 + w] = __uint_as_float(kn);
        };
        auto conv_tile1 = [&](int h) {
          uint32_t t[8], tv[8], kn = NOT_F16;
          norm_tile(4 + h, 1, tv);
          put_kv(h, 1, 1, tv);
          scale(2 + h, 1, 1.f);
          if (h == 0) { if (G1 < 4) part(2, 0, G1, 4); if (G2) part(3, 0, 0, G2); } else if (G3 < 4) part(3, 0, G3, 4);
          if (l & 1) {
            float n[2] = {0.f, 0.f};
#pragma unroll
            for (int i = 0; i < 16; i++) n[(i >> 1) & 1] = fmaf(acc[1][32 + 16 * h + i], acc[1][32 + 16 * h + i], n[(i >> 1) & 1]);
            const float a = ((qd & 1) ? n[1] : n[0]) + __shfl_xor_sync(~0u, (qd & 1) ? n[0] : n[1], 1);
            scale(h, 1, QSCALE / 128.f);
            kn = f16_class(__reduce_max_sync(~0u, __float_as_uint(a + __shfl_xor_sync(~0u, a, 2))), K_LO);
            put_kn(h, 1, kn);
          } else scale(h, 1, 1.f);
          if (kn == NOT_F16) pack_b(2 + h, 1, t); else pack_h(2 + h, 1, t);
          put_kv(h, 0, 1, t);
          if (!(l & 1) && row0 == 176 && bm < 7) { send_halo(h, 0, t); send_halo(h, 1, tv); }
        };
        mbar_wait(sb + B_QE + 8, 1);
        wg_wait<1>();
        fence_regs(acc[1]);
        conv_tile1(0);
        if (G2 < G3) part(3, 0, G2, G3);
        if (l & 1) { fence_async_smem(); bar_arrive(NB_ST, 288); }
        conv_tile1(1);
        if (WGBAR && !(l & 1) && row0 == 48) bar_arrive(NB_KV + 12, 64);
        wg_wait<(G2 > 0) + (G2 < G3) + (G3 < 4)>();
        if (w == 0) e_arrive_both(sb + B_QE + 16);
        wg_wait<0>();
        fence_regs(acc[0]);
        if (w == 0) e_arrive_both(sb + B_QE + 24);
        bf16* const op0 = [&] { IDS(); return g_os + (size_t)(bm * 256 + row0 + (lane >> 2)) * 1024 + bn * 32 + (lane & 3) * 8; }();
        auto put_o = [&](int h, int m, const float (&o)[16], float i0, float i1) {
          bf16* op = op0 + m * 65536 + h * 512;
          const uint4 a = make_uint4(pack2(o[0] * i0, o[1] * i0), pack2(o[4] * i0, o[5] * i0), pack2(o[8] * i0, o[9] * i0), pack2(o[12] * i0, o[13] * i0));
          const uint4 c = make_uint4(pack2(o[2] * i1, o[3] * i1), pack2(o[6] * i1, o[7] * i1), pack2(o[10] * i1, o[11] * i1), pack2(o[14] * i1, o[15] * i1));
          *(uint4*)op = a; *(uint4*)(op + 8 * 1024) = c;
          const uint32_t hi = __vimax3_u16x2(__vimax3_u16x2(a.x, a.y, a.z), __vimax3_u16x2(a.w, c.x, c.y), __vmaxu2(c.z, c.w));
          const uint32_t lo = __vimax3_s16x2(__vimax3_s16x2(a.x, a.y, a.z), __vimax3_s16x2(a.w, c.x, c.y), __vmaxs2(c.z, c.w));
          return __vmaxu2(hi & 0x7FFF7FFFu, lo & 0x7FFF7FFFu);
        };
        if (!(l & 1)) {
          auto conv_kv = [&](int h) {
            uint32_t t[8];
            norm_tile(2 + h, 0, t); put_kv(h, 0, 0, t);
            norm_tile(4 + h, 0, t); put_kv(h, 1, 0, t);
          };
          conv_kv(0);
          if (!PERHEAD) conv_kv(1);
          norm_tile(0, 0, q[0][0]); pack_b(0, 1, q[0][1]);
          bar_sync(NB_SC, 256);
          const bool e = g & 1, sel = 2 * qd + (g & 1) >= g + 2, first = bm == 0 && row0 == 0;
          const uint32_t pm_a = e ? 0x1044 : 0x4410, pm_b = e ? 0x3244 : 0x4432, pm_lo = sel ? pm_b : 0x4444, pm_hi = sel ? 0x4444 : pm_b;
          const uint32_t ka = sb + (row0 + (lane & 7)) * 64 + (((lane >> 3) ^ ((lane >> 1) & 3)) << 4);
          const uint32_t va0 = sb + ASC + (row0 + srow) * 64 + (((lane >> 4) ^ ((lane >> 1) & 3)) << 4);
#pragma unroll 1
          for (int h = 0; h < 2; h++) {
            if (row0 == 0) bar_sync(NB_HALO + h, 64);
            float s[2][4][4];
            uint32_t vf[2][4][4], pf[2][2][4];
#pragma unroll
            for (int m = 0; m < 2; m++)
#pragma unroll
              for (int nt = 0; nt < 4; nt++) {
                uint32_t kf[4];
                ldsm4(ka + h * (2 * ASC) + (m * 64 + 8 * nt) * 64, kf);
                s[m][nt][0] = s[m][nt][1] = s[m][nt][2] = s[m][nt][3] = 0.f;
                mma16816(s[m][nt], q[0][m][0], q[0][m][1], q[0][m][2], q[0][m][3], kf[0], kf[1]);
                mma16816(s[m][nt], q[0][m][4], q[0][m][5], q[0][m][6], q[0][m][7], kf[2], kf[3]);
              }
#pragma unroll
            for (int m = 0; m < 2; m++)
#pragma unroll
              for (int i = 0; i < 4; i++) {
                ldsm4t(((va0 + h * (2 * ASC)) ^ (32 * (i & 1))) + (m * 64 + 16 * (i >> 1)) * 64, vf[m][i]);
              }
            float va[4], vb[4], mx[4];
            uint32_t ua[2], ub[2], um[2];
#pragma unroll
            for (int m = 0; m < 2; m++) {
              float a[2], c[2];
#pragma unroll
              for (int hh = 0; hh < 2; hh++) {
                a[hh] = e ? s[m][hh + 1][2 * hh + 1] : s[m][hh + 1][2 * hh];
                const float lo = e ? s[m][hh][2 * hh + 1] : s[m][hh][2 * hh], hi = e ? s[m][hh + 2][2 * hh + 1] : s[m][hh + 2][2 * hh];
                c[hh] = sel ? lo : hi;
              }
              ua[m] = scale_bf2(pack2(a[0], a[1])); ub[m] = scale_bf2(pack2(c[0], c[1]));
              if (m == 0) { ua[0] = first ? (ua[0] & 0xFFFF0000u) | 0xFF80u : ua[0]; ub[0] = first && sel ? 0xFF80FF80u : ub[0]; }
              um[m] = max_bf2(ua[m], ub[m]);
            }
#pragma unroll
            for (int m = 0; m < 2; m++) um[m] = max_bf2(um[m], __shfl_xor_sync(~0u, um[m], 1));
#pragma unroll
            for (int m = 0; m < 2; m++) um[m] = max_bf2(um[m], __shfl_xor_sync(~0u, um[m], 2));
#pragma unroll
            for (int i = 0; i < 4; i++) {
              const int m = i >> 1;
              const float top = (i & 1) ? bf_hi(um[m]) : bf_lo(um[m]);
              va[i] = ex2((((i & 1) ? bf_hi(ua[m]) : bf_lo(ua[m])) - top) * 1.4426950408889634f);
              vb[i] = ex2((((i & 1) ? bf_hi(ub[m]) : bf_lo(ub[m])) - top) * 1.4426950408889634f);
              mx[i] = va[i] + vb[i];
            }
#pragma unroll
            for (int i = 0; i < 4; i++) mx[i] += __shfl_xor_sync(~0u, mx[i], 1);
#pragma unroll
            for (int i = 0; i < 4; i++) mx[i] += __shfl_xor_sync(~0u, mx[i], 2);
#pragma unroll
            for (int i = 0; i < 4; i++) {
              const int m = i >> 1, hh = i & 1;
              const float inv = rcp(mx[i]);
              const uint32_t t = pack2(va[i] * inv, vb[i] * inv);
              pf[m][hh][hh + 1] = __byte_perm(t, 0, pm_a); pf[m][hh][hh] = __byte_perm(t, 0, pm_lo); pf[m][hh][hh + 2] = __byte_perm(t, 0, pm_hi); pf[m][hh][3 - 3 * hh] = t & zero;
            }
#pragma unroll
            for (int m = 0; m < 2; m++) {
              float o[4][4];
#pragma unroll
              for (int j = 0; j < 4; j++) o[j][0] = o[j][1] = o[j][2] = o[j][3] = 0.f;
#pragma unroll
              for (int i = 0; i < 4; i++) {
                const int kk = i >> 1, jj = 2 * (i & 1);
                mma16816(o[jj], pf[m][0][2 * kk], pf[m][1][2 * kk], pf[m][0][2 * kk + 1], pf[m][1][2 * kk + 1], vf[m][i][0], vf[m][i][1]);
                mma16816(o[jj + 1], pf[m][0][2 * kk], pf[m][1][2 * kk], pf[m][0][2 * kk + 1], pf[m][1][2 * kk + 1], vf[m][i][2], vf[m][i][3]);
              }
              const float of[16] = {o[0][0], o[0][1], o[0][2], o[0][3], o[1][0], o[1][1], o[1][2], o[1][3], o[2][0], o[2][1], o[2][2], o[2][3], o[3][0], o[3][1], o[3][2], o[3][3]};
              put_o(h, m, of, 1.f, 1.f);
            }
            bar_arrive(NB_SIG + 2 * h + wg, 160);
            if (h == 0) {
              if (HUNR) mbar_wait(sb + B_QF + 24, 1);
              if (PERHEAD) conv_kv(1);
              norm_tile(1, 0, q[0][0]); pack_b(1, 1, q[0][1]);
              if (WGBAR) bar_sync(wg ? NB_KV : NB_SC, 128); else bar_sync(NB_SC, 256);
            }
          }
        } else {
          auto conv_h = [&](int gi, int m, uint32_t (&t)[8]) {
            pack_h(gi, m, t);
            float d0[4] = {0.f, 0.f, 0.f, 0.f}, d1[4] = {0.f, 0.f, 0.f, 0.f};
            if (gi == 2) {
              mma16816h(d0, t[0], t[1], t[2], t[3], t[0], t[2]); mma16816h(d1, t[0], t[1], t[2], t[3], t[1], t[3]);
              mma16816h(d0, t[4], t[5], t[6], t[7], t[4], t[6]); mma16816h(d1, t[4], t[5], t[6], t[7], t[5], t[7]);
            } else {
#pragma unroll
              for (int i = 0; i < 8; i += 2) { mma1688h(d0, t[i], t[i + 1], t[i]); mma1688h(d1, t[i], t[i + 1], t[i + 1]); }
            }
            return f16_class(__reduce_max_sync(~0u, max(max(__float_as_int(d0[0]), __float_as_int(d0[1])), max(__float_as_int(d1[2]), __float_as_int(d1[3])))), K_LO);
          };
          uint32_t tk[8], tv[8];
          scale(2, 0, 1.f);
          uint32_t kn = conv_h(2, 0, tk);
          norm_tile(4, 0, tv);
          put_kv(0, 1, 0, tv);
          put_kn(0, 0, kn);
          if (kn == NOT_F16) pack_b(2, 0, tk);
          put_kv(0, 0, 0, tk);
          fence_async_smem();
          bar_arrive(NB_KV, 288);
          mbar_wait(sb + B_QF + 24, 1);
          scale(3, 0, 1.f); scale(0, 0, QSCALE); scale(1, 0, QSCALE);
          kn = conv_h(3, 0, tk);
#pragma unroll
          for (int i = 0; i < 4; i++) qn[i >> 1][i & 1] = conv_h(i >> 1, i & 1, q[i >> 1][i & 1]);
          norm_tile(5, 0, tv);
          if (max(max(max(qn[0][0], qn[0][1]), max(qn[1][0], qn[1][1])), kn) == NOT_F16) {
#pragma unroll
            for (int i = 0; i < 4; i++) if (qn[i >> 1][i & 1] == NOT_F16) pack_b(i >> 1, i & 1, q[i >> 1][i & 1]);
            if (kn == NOT_F16) pack_b(3, 0, tk);
          }
          fence_regs(tv);
          const bool elected = w == 0 && lane == 0;
          const uint64_t kd0 = mkdesc(sb + T0, 16, 512, 2);
          const uint64_t vd0 = mkdesc(sb + T0 + 16384, ONES - (T0 + 16384), 512, 2);
          constexpr uint64_t VSTEP = 64 - (64ull << 16);
          constexpr int RPC = NQ / 16;
          float o[2][20], SA[2][NQ / 2];
          uint32_t SB[2][NQB / 4], PA[4], PB[4];
          auto qka = [&](int b, int k, uint64_t d, int h = 0) { QK_A(SA[b], q[h][0][4 * k], q[h][0][4 * k + 1], q[h][0][4 * k + 2], q[h][0][4 * k + 3], d + 2 * k, k ? 1 : zero); };
          auto qkb = [&](int b, int k, uint64_t d, int h = 0) { QK_B(SB[b], q[h][1][4 * k], q[h][1][4 * k + 1], q[h][1][4 * k + 2], q[h][1][4 * k + 3], d + 2 * k, k ? 1 : zero); };
          auto pv = [&](int m, const uint32_t (&Px)[4], uint64_t vd, int keep = 1) { wgmma_m64n40k16_rs_tb(o[m], Px[0], Px[1], Px[2], Px[3], vd, keep); };
          auto clear = [&]() {
#pragma unroll
            for (int i = 0; i < 4; i++) PA[i] = PB[i] = zero;
            wg_fence();
            wgmma_m64n40k16_rs_tb_z(o[0], PA[0], PA[1], PA[2], PA[3], vd0, 0); wgmma_m64n40k16_rs_tb_z(o[1], PB[0], PB[1], PB[2], PB[3], vd0 + VSTEP, 0);
          };
          mbar_wait(sb + B_TF, 0);
          clear();
#pragma unroll
          for (int b = 1; b >= 0; b--) {
            wgmma_m64n32k16_rs_nb_z_h(SA[b], q[0][0][0], q[0][0][1], q[0][0][2], q[0][0][3], kd0 + 128 * b, 0);
            wgmma_m64n32k16_rs_nb_z_hh(SB[b], q[0][1][0], q[0][1][1], q[0][1][2], q[0][1][3], kd0 + 128 * b, 0);
          }
          qka(0, 1, kd0); qkb(0, 1, kd0); wg_commit();
          put_kv(1, 1, 0, tv); put_kv(1, 0, 0, tk); put_kn(1, 0, kn);
          fence_async_smem();
          bar_arrive(NB_KV + 12, 288);
          wg_wait<0>();
          fence_regs(SA[0]); fence_regs(SB[0]); fence_regs(SA[1]); fence_regs(SB[1]); fence_regs(o[0]); fence_regs(o[1]);
#pragma unroll 1
          for (int pass = 0; pass < 2; pass++) {
            constexpr int IPS = 16 / NRB, NC = NRB / RPC, RPB = NQB / 16, RPM = RPB - (OB & 15) > RPC - (OA & 15) ? RPB - (OB & 15) : RPC - (OA & 15);
            uint32_t kc = (uint32_t)kd0, vc = (uint32_t)vd0, vp = (uint32_t)(vd0 + VSTEP);
#pragma unroll 1
            for (int it = 1; it <= 8 * IPS; it++) {
              const uint32_t sn = (it / IPS) & 3, un = it % IPS, par = (it / (4 * IPS)) & 1;
              const uint32_t kn = it < 8 * IPS ? (uint32_t)kd0 + sn * 2048 + un * (NRB * 64) : kc;
              const uint64_t hi = kd0 & 0xFFFFFFFF00000000ull, kd = hi | kc, vd = hi | vc, kdn = hi | kn, vdp = hi | vp;
              kc = kn; vp = vc + (uint32_t)(NRB * VSTEP); vc = (uint32_t)vd0 + (sn * 32 + un * NRB) * (uint32_t)VSTEP;
              bool landed = false;
#pragma unroll
              for (int r = 0; r < NRB; r++) {
                const int c = r / RPC, ro = r % RPC, cn = c + 1, cb = r / RPB, rb = r % RPB;
                if (r == NRB - RPM && !landed) mbar_wait(sb + B_TF + 8 * sn, par);
                wg_fence();
                const uint64_t kx = cn < NC ? kd + cn * NQ * 4 : kdn, vx = (r ? vd : vdp) + (r - 1) * VSTEP;
#pragma unroll
                for (int k = 0; k < 2; k++) {
                  if (ro == ((OA >> (4 * k)) & 15)) qka(cn & 1, k, kx);
                  if (rb == ((OB >> (4 * k)) & 15)) qkb((cb + 1) & 1, k, cb + 1 < NRB / RPB ? kd + (cb + 1) * NQB * 4 : kdn);
                }
                if ((ro == RPC - 1 && (OA >> 4) == ro) || (rb == RPB - 1 && (OB >> 4) == rb) || (LAG & 1)) wg_commit();
                const int keep = r || !OSD ? 1 : it - 1;
                if (LAG & 8) { pv(1, PB, vx, keep); pv(0, PA, vx, keep); } else { pv(0, PA, vx, keep); pv(1, PB, vx, keep); }
                wg_commit();
                if (r == NRB - RPM - 2) landed = mbar_test(sb + B_TF + 8 * sn, par) || it == 8 * IPS;
#pragma unroll
                for (int i = 0; i < 4; i++) {
                  if (LAG & 16) PB[i] = exp2_h2(SB[cb & 1][4 * rb + i], zero);
                  PA[i] = pack2(ex2(SA[c & 1][8 * ro + 2 * i]), ex2(SA[c & 1][8 * ro + 2 * i + 1]));
                  if (!(LAG & 16)) PB[i] = exp2_h2(SB[cb & 1][4 * rb + i], zero);
                }
                if (r == NRB - 1) wg_wait<0>(); else if (ro == RPC - 1 || rb == RPB - 1 || !(LAG & 2) || ((LAG & 4) && (ro & 1))) wg_wait<1>();
                if (ro == RPC - 1) fence_regs(SA[cn & 1]);
                if (rb == RPB - 1) fence_regs(SB[(cb + 1) & 1]);
                if (r == RPC && elected && un == 1 % IPS && it > 1) mbar_arrive(sb + B_TE + 8 * ((sn + (IPS > 1 ? 3 : 2)) & 3));
              }
            }
            int badm = 0;
            if (pass == 0) mbar_wait(sb + B_TF, 0);
            wg_fence();
            pv(0, PA, vd0 + 111 * VSTEP); pv(1, PB, vd0 + 111 * VSTEP); wg_commit();
            qka(0, 0, kd0, 1); qkb(0, 0, kd0, 1); qka(0, 1, kd0, 1); qkb(0, 1, kd0, 1); wg_commit();
            if (pass == 0) bar_sync(NB_KN + wg, 160);
            const float kmax = *(volatile float*)(smem + KMAX + 4 * pass);
            wg_wait<1>(); fence_regs(o[0]); fence_regs(o[1]);
            if (w == 0) e_arrive(sb + B_TE + 8 * 3);
#pragma unroll
            for (int m = 0; m < 2; m++) {
              if (ONECOL) { o[m][16] = __shfl_sync(~0u, o[m][16], 0, 4); o[m][18] = __shfl_sync(~0u, o[m][18], 0, 4); }
              const float of[16] = {o[m][0], o[m][1], o[m][2], o[m][3], o[m][4], o[m][5], o[m][6], o[m][7], o[m][8], o[m][9], o[m][10], o[m][11], o[m][12], o[m][13], o[m][14], o[m][15]};
              const uint32_t chk = put_o(pass, m, of, rcp(o[m][16]), rcp(o[m][18]));
              const bool bad = !(__uint_as_float(qn[0][m]) * kmax <= (m ? 0.875f * 0.875f : 112.f * 112.f)) || !(fminf(o[m][16], o[m][18]) >= 9.3e-10f) ||
                               !(o[m][16] + o[m][18] <= 3e38f) || ((chk + 0x00800080u) & 0x80008000u);
              badm |= __any_sync(~0u, bad) << m;
            }
            wg_wait<0>(); fence_regs(SA[0]); fence_regs(SB[0]);
            if (badm) {
#pragma unroll 1
              for (int m = 0; m < 2; m++) if ((badm >> m) & 1) {
                uint32_t qq[8]; float res[20];
#pragma unroll
                for (int i = 0; i < 8; i++) { qq[i] = m ? q[0][1][i] : q[0][0][i]; if ((m ? qn[0][1] : qn[0][0]) != NOT_F16) qq[i] = h2_to_bf2(qq[i]); }
                attn_slow(qq, m ? 128.f : 1.f, 2 * (cta_id() & 15) + pass, g_kn + ((l >> 1) * 128 + (cta_id() & 15) * 8) * 32 + 16 * pass, res, lane_id());
                const float of[16] = {res[0], res[1], res[2], res[3], res[4], res[5], res[6], res[7], res[8], res[9], res[10], res[11], res[12], res[13], res[14], res[15]};
                put_o(pass, m, of, rcp(res[16]), rcp(res[18]));
              }
            }
            bar_arrive(NB_SIG + 2 * pass + wg, 160);
            qn[0][0] = qn[1][0]; qn[0][1] = qn[1][1];
#pragma unroll
            for (int m = 0; m < 2; m++)
#pragma unroll
              for (int i = 0; i < 8; i++) q[0][m][i] = q[1][m][i];
            if (!OSD) {
#pragma unroll
              for (int i = 0; i < 20; i++) o[0][i] = o[1][i] = 0.f;
              fence_regs(o[0]); fence_regs(o[1]);
            }
#pragma unroll
            for (int i = 0; i < 4; i++) PA[i] = PB[i] = zero;
          }
        }
      }
      {
        float acc[64];
#pragma unroll
        for (int i = 0; i < 64; i++) acc[i] = 0.f;
        fence_regs(acc);
        uint32_t s = PPEEL, lap = 0;
#pragma unroll 1
        for (int kt = PPEEL; kt < 16; kt++) {
          mbar_wait(sb + B_PF + 8 * s, ((s < 4 ? l : 0) + lap) & 1);
          const uint64_t da = mkdesc(sb + pslot_a(s, l) + wg * 8192, 16, 1024, 1), db = mkdesc(sb + pslot_b(s, l), 8192, 1024, 1);
          wg_fence();
#pragma unroll
          for (int k = 0; k < 4; k++) wgmma_m64n128k16_ss_tb(acc, da + k * 2, db + k * 128, 1);
          wg_commit();
          wg_wait<1>();
          if (kt > 0 && w == 0) e_arrive_both(sb + B_PE + 8 * (s ? s - 1 : 5));
          if (++s == 6) { s = 0; lap++; }
        }
        IDS();
        const int g = lane >> 2, qd = lane & 3;
        const int r0 = wg * 64 + w * 16;
        const uint32_t r = r0 + (lane & 7) + ((lane >> 3) & 1) * 8;
        uint32_t x[8][4];
        mbar_wait(sb + B_RF, l & 1);
#pragma unroll
        for (int jj = 0; jj < 8; jj++) ldsm4(sb + ((l & 1) ? RES : 0) + (jj >> 2) * 16384 + r * 128 + ((((2 * jj + (lane >> 4)) & 7) ^ (r & 7)) << 4), x[jj]);
        wg_wait<0>();
        fence_regs(acc);
        bar_sync(NB_SC, 256);
        if (w == 0) e_arrive_both(sb + B_PE + 8 * 3);
        const CUtensorMap* mo = &prm.m[l == 3 ? M_OUT : M_XST];
#pragma unroll
        for (int jj = 0; jj < 8; jj++) {
#pragma unroll
          for (int i = 0; i < 4; i++) x[jj][i] = add_bf16x2(x[jj][i], pack2(acc[8 * jj + 2 * i], acc[8 * jj + 2 * i + 1]));
          stsm4(sb + (jj >> 2) * QSTG + po * 16384 + r * 128 + ((((2 * jj + (lane >> 4)) & 7) ^ (r & 7)) << 4), x[jj][0], x[jj][1], x[jj][2], x[jj][3]);
          if ((jj & 3) == 3) { fence_async_smem(); __syncwarp(); tma_st(mo, pn * 128 + (jj >> 2) * 64, pm * 128 + r0, sb + (jj >> 2) * QSTG + po * 16384 + r0 * 128); }
        }
        bulk_commit();
        if (l < 3) {
          bar_arrive(NB_X, 288);
          float s1[4] = {0.f, 0.f, 0.f, 0.f}, s2[4][4];
#pragma unroll
          for (int i = 0; i < 16; i++) s2[i >> 2][i & 3] = 0.f;
#pragma unroll
          for (int jj = 0; jj < 8; jj++) {
            mma16816(s1, x[jj][0], x[jj][1], x[jj][2], x[jj][3], 0x3f803f80u, 0x3f803f80u);
#pragma unroll
            for (int i = 0; i < 4; i++) mma1688(s2[i], x[jj][i & 2], x[jj][i | 1], x[jj][i]);
          }
          if (qd == (g >> 1)) {
            float2* sp = g_stats + pn * 2048 + pm * 128 + r0 + g;
            sp[0] = make_float2(s1[0], (g & 1) ? s2[0][1] + s2[2][1] : s2[0][0] + s2[2][0]);
            sp[8] = make_float2(s1[2], (g & 1) ? s2[1][3] + s2[3][3] : s2[1][2] + s2[3][2]);
          }
        }
        bulk_wait_n<0>();
        if (l < 3) bar_arrive(NB_X0, 320 + 32 * XLATE);
      }
    }
  }
  asm volatile("barrier.cluster.arrive.relaxed.aligned;\nbarrier.cluster.wait.aligned;" ::: "memory");
}

typedef CUresult (*EncodeFn)(CUtensorMap*, CUtensorMapDataType, cuuint32_t, void*, const cuuint64_t*, const cuuint64_t*, const cuuint32_t*,
                             const cuuint32_t*, CUtensorMapInterleave, CUtensorMapSwizzle, CUtensorMapL2promotion, CUtensorMapFloatOOBfill);

static void make_map(EncodeFn fn, CUtensorMap* m, const void* ptr, int rank, const uint64_t* dims, const uint64_t* strides, const uint32_t* box, CUtensorMapSwizzle sw) {
  cuuint64_t d[5], st[4];
  cuuint32_t bx[5], es[5];
  for (int i = 0; i < rank; i++) { d[i] = dims[i]; bx[i] = box[i]; es[i] = 1; if (i) st[i - 1] = strides[i - 1] * 2; }
  fn(m, CU_TENSOR_MAP_DATA_TYPE_BFLOAT16, rank, (void*)ptr, d, st, bx, es, CU_TENSOR_MAP_INTERLEAVE_NONE, sw,
     CU_TENSOR_MAP_L2_PROMOTION_L2_128B, CU_TENSOR_MAP_FLOAT_OOB_FILL_NONE);
}
static void map2(EncodeFn fn, CUtensorMap* m, const void* ptr, uint64_t inner, uint64_t outer, uint32_t bi, uint32_t bo, CUtensorMapSwizzle sw) {
  const uint64_t d[2] = {inner, outer}, st[1] = {inner};
  const uint32_t bx[2] = {bi, bo};
  make_map(fn, m, ptr, 2, d, st, bx, sw);
}

extern "C" void kernel_launch(void* const* d_in, const int* in_sizes, int n_in, void* d_out, int out_size) {
  (void)in_sizes; (void)n_in; (void)out_size;
  static EncodeFn enc = nullptr;
  static void *xs, *os, *kk, *vv, *ep;
  if (!enc) {
    void* p = nullptr;
    cudaDriverEntryPointQueryResult qr;
    cudaGetDriverEntryPoint("cuTensorMapEncodeTiled", &p, cudaEnableDefault, &qr);
    enc = (EncodeFn)p;
    cudaGetSymbolAddress(&xs, g_xs); cudaGetSymbolAddress(&os, g_os); cudaGetSymbolAddress(&kk, g_k); cudaGetSymbolAddress(&vv, g_v); cudaGetSymbolAddress(&ep, g_epoch);
    cudaFuncSetAttribute(fused_kernel, cudaFuncAttributeMaxDynamicSharedMemorySize, SMEM_BYTES);
  }
  Params prm;
  const CUtensorMapSwizzle S128 = CU_TENSOR_MAP_SWIZZLE_128B, S64 = CU_TENSOR_MAP_SWIZZLE_64B;
  map2(enc, &prm.m[M_X0A], d_in[0], 1024, 2048, 64, 256, S128);
  map2(enc, &prm.m[M_XSA], xs, 1024, 2048, 64, 256, S128);
  for (int t = 0; t < 2; t++) {
    const uint64_t d3[3] = {1024, 1024, 3}, s3[2] = {3072, 1024};
    const uint32_t b3[3] = {64, 64, 3};
    make_map(enc, &prm.m[M_WQA + t], d_in[1 + 3 * t], 3, d3, s3, b3, S128);
    const uint64_t d5[5] = {64, 32, 2, 16, 16}, s5[4] = {1024, 32 * 1024, 64 * 1024, 64};
    const uint32_t b5[5] = {64, 32, 1, 2, 2};
    make_map(enc, &prm.m[M_WOA + t], d_in[2 + 3 * t], 5, d5, s5, b5, S128);
    const uint64_t dr[3] = {64, 2048, 16}, sr[2] = {1024, 64};
    const uint32_t br[3] = {64, 128, 2};
    make_map(enc, &prm.m[M_X0R + t], t ? xs : d_in[0], 3, dr, sr, br, S128);
  }
  map2(enc, &prm.m[M_OS], os, 1024, 2048, 64, 64, S128);
  map2(enc, &prm.m[M_K], kk, 32, 65536, 32, 256, S64);
  map2(enc, &prm.m[M_V], vv, 32, 65536, 32, 256, S64);
  map2(enc, &prm.m[M_K4], kk, 32, 65536, 32, 64, S64);
  map2(enc, &prm.m[M_V4], vv, 32, 65536, 32, 64, S64);
  map2(enc, &prm.m[M_XSO], xs, 1024, 2048, 64, 128, S128);
  map2(enc, &prm.m[M_X0H], d_in[0], 1024, 2048, 64, 128, S128);
  map2(enc, &prm.m[M_XST], xs, 1024, 2048, 64, 16, S128);
  map2(enc, &prm.m[M_OUT], d_out, 1024, 2048, 64, 16, S128);
  prm.x0 = (const bf16*)d_in[0];
  prm.wq[0] = (const bf16*)d_in[1]; prm.wq[1] = (const bf16*)d_in[4];
  prm.wo[0] = (const bf16*)d_in[2]; prm.wo[1] = (const bf16*)d_in[5];
  prm.epoch = (uint32_t*)ep;
  prm.zero = 0;
  for (int i = 0; i < 128; i++) prm.map[i] = remap(i);
  fused_kernel<<<128, 384, SMEM_BYTES>>>(prm);
}
```

```cpp
#include <cuda_runtime.h>
#include <cuda_bf16.h>
#include <cuda.h>
#include <stdint.h>

typedef __nv_bfloat16 bf16;

__device__ __forceinline__ void wgmma_m64n192k16_ss_tb(float (&d)[96], uint64_t da, uint64_t db, int scale_d) {
  asm volatile("{\n.reg .pred p;\nsetp.ne.b32 p, %98, 0;\n"
    "wgmma.mma_async.sync.aligned.m64n192k16.f32.bf16.bf16 "
    "{%0, %1, %2, %3, %4, %5, %6, %7, %8, %9, %10, %11, %12, %13, %14, %15, "
    "%16, %17, %18, %19, %20, %21, %22, %23, %24, %25, %26, %27, %28, %29, %30, %31, "
    "%32, %33, %34, %35, %36, %37, %38, %39, %40, %41, %42, %43, %44, %45, %46, %47, "
    "%48, %49, %50, %51, %52, %53, %54, %55, %56, %57, %58, %59, %60, %61, %62, %63, "
    "%64, %65, %66, %67, %68, %69, %70, %71, %72, %73, %74, %75, %76, %77, %78, %79, "
    "%80, %81, %82, %83, %84, %85, %86, %87, %88, %89, %90, %91, %92, %93, %94, %95}, "
    "%96, %97, p, 1, 1, 0, 1;\n}\n"
    : "+f"(d[0]), "+f"(d[1]), "+f"(d[2]), "+f"(d[3]), "+f"(d[4]), "+f"(d[5]), "+f"(d[6]), "+f"(d[7]),
      "+f"(d[8]), "+f"(d[9]), "+f"(d[10]), "+f"(d[11]), "+f"(d[12]), "+f"(d[13]), "+f"(d[14]), "+f"(d[15]),
      "+f"(d[16]), "+f"(d[17]), "+f"(d[18]), "+f"(d[19]), "+f"(d[20]), "+f"(d[21]), "+f"(d[22]), "+f"(d[23]),
      "+f"(d[24]), "+f"(d[25]), "+f"(d[26]), "+f"(d[27]), "+f"(d[28]), "+f"(d[29]), "+f"(d[30]), "+f"(d[31]),
      "+f"(d[32]), "+f"(d[33]), "+f"(d[34]), "+f"(d[35]), "+f"(d[36]), "+f"(d[37]), "+f"(d[38]), "+f"(d[39]),
      "+f"(d[40]), "+f"(d[41]), "+f"(d[42]), "+f"(d[43]), "+f"(d[44]), "+f"(d[45]), "+f"(d[46]), "+f"(d[47]),
      "+f"(d[48]), "+f"(d[49]), "+f"(d[50]), "+f"(d[51]), "+f"(d[52]), "+f"(d[53]), "+f"(d[54]), "+f"(d[55]),
      "+f"(d[56]), "+f"(d[57]), "+f"(d[58]), "+f"(d[59]), "+f"(d[60]), "+f"(d[61]), "+f"(d[62]), "+f"(d[63]),
      "+f"(d[64]), "+f"(d[65]), "+f"(d[66]), "+f"(d[67]), "+f"(d[68]), "+f"(d[69]), "+f"(d[70]), "+f"(d[71]),
      "+f"(d[72]), "+f"(d[73]), "+f"(d[74]), "+f"(d[75]), "+f"(d[76]), "+f"(d[77]), "+f"(d[78]), "+f"(d[79]),
      "+f"(d[80]), "+f"(d[81]), "+f"(d[82]), "+f"(d[83]), "+f"(d[84]), "+f"(d[85]), "+f"(d[86]), "+f"(d[87]),
      "+f"(d[88]), "+f"(d[89]), "+f"(d[90]), "+f"(d[91]), "+f"(d[92]), "+f"(d[93]), "+f"(d[94]), "+f"(d[95])
    : "l"(da), "l"(db), "r"(scale_d));
}

__device__ __forceinline__ void wgmma_m64n128k16_ss_tb(float (&d)[64], uint64_t da, uint64_t db, int scale_d) {
  asm volatile("{\n.reg .pred p;\nsetp.ne.b32 p, %66, 0;\n"
    "wgmma.mma_async.sync.aligned.m64n128k16.f32.bf16.bf16 "
    "{%0, %1, %2, %3, %4, %5, %6, %7, %8, %9, %10, %11, %12, %13, %14, %15, "
    "%16, %17, %18, %19, %20, %21, %22, %23, %24, %25, %26, %27, %28, %29, %30, %31, "
    "%32, %33, %34, %35, %36, %37, %38, %39, %40, %41, %42, %43, %44, %45, %46, %47, "
    "%48, %49, %50, %51, %52, %53, %54, %55, %56, %57, %58, %59, %60, %61, %62, %63}, "
    "%64, %65, p, 1, 1, 0, 1;\n}\n"
    : "+f"(d[0]), "+f"(d[1]), "+f"(d[2]), "+f"(d[3]), "+f"(d[4]), "+f"(d[5]), "+f"(d[6]), "+f"(d[7]),
      "+f"(d[8]), "+f"(d[9]), "+f"(d[10]), "+f"(d[11]), "+f"(d[12]), "+f"(d[13]), "+f"(d[14]), "+f"(d[15]),
      "+f"(d[16]), "+f"(d[17]), "+f"(d[18]), "+f"(d[19]), "+f"(d[20]), "+f"(d[21]), "+f"(d[22]), "+f"(d[23]),
      "+f"(d[24]), "+f"(d[25]), "+f"(d[26]), "+f"(d[27]), "+f"(d[28]), "+f"(d[29]), "+f"(d[30]), "+f"(d[31]),
      "+f"(d[32]), "+f"(d[33]), "+f"(d[34]), "+f"(d[35]), "+f"(d[36]), "+f"(d[37]), "+f"(d[38]), "+f"(d[39]),
      "+f"(d[40]), "+f"(d[41]), "+f"(d[42]), "+f"(d[43]), "+f"(d[44]), "+f"(d[45]), "+f"(d[46]), "+f"(d[47]),
      "+f"(d[48]), "+f"(d[49]), "+f"(d[50]), "+f"(d[51]), "+f"(d[52]), "+f"(d[53]), "+f"(d[54]), "+f"(d[55]),
      "+f"(d[56]), "+f"(d[57]), "+f"(d[58]), "+f"(d[59]), "+f"(d[60]), "+f"(d[61]), "+f"(d[62]), "+f"(d[63])
    : "l"(da), "l"(db), "r"(scale_d));
}

__device__ __forceinline__ void wgmma_m64n32k16_rs_nb_h(float (&d)[16], uint32_t a0, uint32_t a1, uint32_t a2, uint32_t a3, uint64_t db, int scale_d) {
  asm volatile("{\n.reg .pred p;\nsetp.ne.b32 p, %21, 0;\n"
    "wgmma.mma_async.sync.aligned.m64n32k16.f32.f16.f16 "
    "{%0, %1, %2, %3, %4, %5, %6, %7, %8, %9, %10, %11, %12, %13, %14, %15}, "
    "{%16, %17, %18, %19}, %20, p, 1, 1, 0;\n}\n"
    : "+f"(d[0]), "+f"(d[1]), "+f"(d[2]), "+f"(d[3]), "+f"(d[4]), "+f"(d[5]), "+f"(d[6]), "+f"(d[7]),
      "+f"(d[8]), "+f"(d[9]), "+f"(d[10]), "+f"(d[11]), "+f"(d[12]), "+f"(d[13]), "+f"(d[14]), "+f"(d[15])
    : "r"(a0), "r"(a1), "r"(a2), "r"(a3), "l"(db), "r"(scale_d));
}

__device__ __forceinline__ void wgmma_m64n32k16_rs_nb_hh(uint32_t (&d)[8], uint32_t a0, uint32_t a1, uint32_t a2, uint32_t a3, uint64_t db, int scale_d) {
  asm volatile("{\n.reg .pred p;\nsetp.ne.b32 p, %13, 0;\n"
    "wgmma.mma_async.sync.aligned.m64n32k16.f16.f16.f16 "
    "{%0, %1, %2, %3, %4, %5, %6, %7}, "
    "{%8, %9, %10, %11}, %12, p, 1, 1, 0;\n}\n"
    : "+r"(d[0]), "+r"(d[1]), "+r"(d[2]), "+r"(d[3]), "+r"(d[4]), "+r"(d[5]), "+r"(d[6]), "+r"(d[7])
    : "r"(a0), "r"(a1), "r"(a2), "r"(a3), "l"(db), "r"(scale_d));
}

__device__ __forceinline__ void wgmma_m64n40k16_rs_tb(float (&d)[20], uint32_t a0, uint32_t a1, uint32_t a2, uint32_t a3, uint64_t db, int scale_d) {
  asm volatile("{\n.reg .pred p;\nsetp.ne.b32 p, %25, 0;\n"
    "wgmma.mma_async.sync.aligned.m64n40k16.f32.bf16.bf16 "
    "{%0, %1, %2, %3, %4, %5, %6, %7, %8, %9, %10, %11, %12, %13, %14, %15, "
    "%16, %17, %18, %19}, "
    "{%20, %21, %22, %23}, %24, p, 1, 1, 1;\n}\n"
    : "+f"(d[0]), "+f"(d[1]), "+f"(d[2]), "+f"(d[3]), "+f"(d[4]), "+f"(d[5]), "+f"(d[6]), "+f"(d[7]),
      "+f"(d[8]), "+f"(d[9]), "+f"(d[10]), "+f"(d[11]), "+f"(d[12]), "+f"(d[13]), "+f"(d[14]), "+f"(d[15]),
      "+f"(d[16]), "+f"(d[17]), "+f"(d[18]), "+f"(d[19])
    : "r"(a0), "r"(a1), "r"(a2), "r"(a3), "l"(db), "r"(scale_d));
}

__device__ __forceinline__ void wgmma_m64n40k16_rs_tb_z(float (&d)[20], uint32_t a0, uint32_t a1, uint32_t a2, uint32_t a3, uint64_t db, int scale_d) {
  asm volatile("{\n.reg .pred p;\nsetp.ne.b32 p, %25, 0;\n"
    "wgmma.mma_async.sync.aligned.m64n40k16.f32.bf16.bf16 "
    "{%0, %1, %2, %3, %4, %5, %6, %7, %8, %9, %10, %11, %12, %13, %14, %15, "
    "%16, %17, %18, %19}, "
    "{%20, %21, %22, %23}, %24, p, 1, 1, 1;\n}\n"
    : "=f"(d[0]), "=f"(d[1]), "=f"(d[2]), "=f"(d[3]), "=f"(d[4]), "=f"(d[5]), "=f"(d[6]), "=f"(d[7]),
      "=f"(d[8]), "=f"(d[9]), "=f"(d[10]), "=f"(d[11]), "=f"(d[12]), "=f"(d[13]), "=f"(d[14]), "=f"(d[15]),
      "=f"(d[16]), "=f"(d[17]), "=f"(d[18]), "=f"(d[19])
    : "r"(a0), "r"(a1), "r"(a2), "r"(a3), "l"(db), "r"(scale_d));
}

__device__ __forceinline__ void wgmma_m64n32k16_rs_nb_z_h(float (&d)[16], uint32_t a0, uint32_t a1, uint32_t a2, uint32_t a3, uint64_t db, int scale_d) {
  asm volatile("{\n.reg .pred p;\nsetp.ne.b32 p, %21, 0;\n"
    "wgmma.mma_async.sync.aligned.m64n32k16.f32.f16.f16 "
    "{%0, %1, %2, %3, %4, %5, %6, %7, %8, %9, %10, %11, %12, %13, %14, %15}, "
    "{%16, %17, %18, %19}, %20, p, 1, 1, 0;\n}\n"
    : "=f"(d[0]), "=f"(d[1]), "=f"(d[2]), "=f"(d[3]), "=f"(d[4]), "=f"(d[5]), "=f"(d[6]), "=f"(d[7]),
      "=f"(d[8]), "=f"(d[9]), "=f"(d[10]), "=f"(d[11]), "=f"(d[12]), "=f"(d[13]), "=f"(d[14]), "=f"(d[15])
    : "r"(a0), "r"(a1), "r"(a2), "r"(a3), "l"(db), "r"(scale_d));
}

__device__ __forceinline__ void wgmma_m64n32k16_rs_nb_z_hh(uint32_t (&d)[8], uint32_t a0, uint32_t a1, uint32_t a2, uint32_t a3, uint64_t db, int scale_d) {
  asm volatile("{\n.reg .pred p;\nsetp.ne.b32 p, %13, 0;\n"
    "wgmma.mma_async.sync.aligned.m64n32k16.f16.f16.f16 "
    "{%0, %1, %2, %3, %4, %5, %6, %7}, "
    "{%8, %9, %10, %11}, %12, p, 1, 1, 0;\n}\n"
    : "=r"(d[0]), "=r"(d[1]), "=r"(d[2]), "=r"(d[3]), "=r"(d[4]), "=r"(d[5]), "=r"(d[6]), "=r"(d[7])
    : "r"(a0), "r"(a1), "r"(a2), "r"(a3), "l"(db), "r"(scale_d));
}

#define DEVINL __device__ __forceinline__
DEVINL void wg_fence() { asm volatile("wgmma.fence.sync.aligned;" ::: "memory"); }
DEVINL void wg_commit() { asm volatile("wgmma.commit_group.sync.aligned;" ::: "memory"); }
template <int N> DEVINL void wg_wait() { asm volatile("wgmma.wait_group.sync.aligned %0;" ::"n"(N) : "memory"); }
DEVINL uint64_t mkdesc(uint32_t addr, uint32_t lbo, uint32_t sbo, int sw) {
  return (uint64_t)((addr & 0x3FFFF) >> 4) | ((uint64_t)(lbo >> 4) << 16) | ((uint64_t)(sbo >> 4) << 32) | ((uint64_t)sw << 62);
}
DEVINL void mbar_arrive(uint32_t bar) { asm volatile("mbarrier.arrive.shared::cta.b64 _, [%0];" ::"r"(bar) : "memory"); }
DEVINL bool mbar_try(uint32_t bar, uint32_t parity) {
  uint32_t ok;
  asm volatile("{\n.reg .pred p;\nmbarrier.try_wait.parity.shared::cta.b64 p, [%1], %2;\nselp.u32 %0, 1, 0, p;\n}" : "=r"(ok) : "r"(bar), "r"(parity) : "memory");
  return ok;
}
DEVINL bool mbar_test(uint32_t bar, uint32_t parity) {
  uint32_t ok;
  asm volatile("{\n.reg .pred p;\nmbarrier.test_wait.parity.shared::cta.b64 p, [%1], %2;\nselp.u32 %0, 1, 0, p;\n}" : "=r"(ok) : "r"(bar), "r"(parity) : "memory");
  return ok;
}
DEVINL void mbar_hint(uint32_t bar, uint32_t parity) {
#pragma unroll 1
  for (uint32_t n = 0; n < 16u; n++) if (mbar_try(bar, parity)) break;
}
DEVINL void mbar_wait(uint32_t bar, uint32_t parity) {
#pragma unroll 1
  for (uint32_t n = 0; n < 100000u; n++) if (mbar_try(bar, parity)) break;
}
DEVINL void mbar_wait_long(uint32_t bar, uint32_t parity) {
#pragma unroll 1
  for (uint32_t n = 0; n < 100000u; n++) {
    uint32_t ok;
    asm volatile("{\n.reg .pred p;\nmbarrier.try_wait.parity.shared::cta.b64 p, [%1], %2, %3;\nselp.u32 %0, 1, 0, p;\n}" : "=r"(ok) : "r"(bar), "r"(parity), "r"(4000) : "memory");
    if (ok) break;
  }
}
#define EL(txt) "{\n.reg .pred pe;\nelect.sync _|pe, 0xffffffff;\n@pe " txt "\n}"
DEVINL void e_expect_tx(uint32_t bar, uint32_t bytes) { asm volatile(EL("mbarrier.arrive.expect_tx.shared::cta.b64 _, [%0], %1;") ::"r"(bar), "r"(bytes) : "memory"); }
DEVINL void e_init(uint32_t bar, uint32_t cnt) { asm volatile(EL("mbarrier.init.shared::cta.b64 [%0], %1;") ::"r"(bar), "r"(cnt) : "memory"); }
DEVINL void e_arrive(uint32_t bar) { asm volatile(EL("mbarrier.arrive.shared::cta.b64 _, [%0];") ::"r"(bar) : "memory"); }
DEVINL void e_red(uint32_t* p) { asm volatile(EL("red.release.gpu.global.add.u32 [%0], 1;") ::"l"(p) : "memory"); }
DEVINL void e_red_relaxed(uint32_t* p) { asm volatile(EL("red.relaxed.gpu.global.add.u32 [%0], 1;") ::"l"(p) : "memory"); }
DEVINL void tma_ld(uint32_t dst, const CUtensorMap* m, int c0, int c1, uint32_t bar) {
  asm volatile(EL("cp.async.bulk.tensor.2d.shared::cluster.global.mbarrier::complete_tx::bytes [%0], [%1, {%3, %4}], [%2];")
               ::"r"(dst), "l"(m), "r"(bar), "r"(c0), "r"(c1) : "memory");
}
DEVINL void tma_ld3(uint32_t dst, const CUtensorMap* m, int c0, int c1, int c2, uint32_t bar) {
  asm volatile(EL("cp.async.bulk.tensor.3d.shared::cluster.global.mbarrier::complete_tx::bytes [%0], [%1, {%3, %4, %5}], [%2];")
               ::"r"(dst), "l"(m), "r"(bar), "r"(c0), "r"(c1), "r"(c2) : "memory");
}
DEVINL void tma_ld5(uint32_t dst, const CUtensorMap* m, int c2, int c3, int c4, uint32_t bar) {
  asm volatile(EL("cp.async.bulk.tensor.5d.shared::cluster.global.mbarrier::complete_tx::bytes [%0], [%1, {0, 0, %3, %4, %5}], [%2];")
               ::"r"(dst), "l"(m), "r"(bar), "r"(c2), "r"(c3), "r"(c4) : "memory");
}
DEVINL void tma_ld_mc(uint32_t dst, const CUtensorMap* m, int c0, int c1, uint32_t bar) {
  asm volatile(EL("cp.async.bulk.tensor.2d.shared::cluster.global.mbarrier::complete_tx::bytes.multicast::cluster [%0], [%1, {%3, %4}], [%2], %5;")
               ::"r"(dst), "l"(m), "r"(bar), "r"(c0), "r"(c1), "h"((uint16_t)3) : "memory");
}
DEVINL void e_arrive_both(uint32_t bar) {
  asm volatile("{\n.reg .pred pe;\n.reg .b32 r0, r1;\nelect.sync _|pe, 0xffffffff;\nmapa.shared::cluster.u32 r0, %0, 0;\nmapa.shared::cluster.u32 r1, %0, 1;\n"
               "@pe mbarrier.arrive.shared::cluster.b64 _, [r0];\n@pe mbarrier.arrive.shared::cluster.b64 _, [r1];\n}" ::"r"(bar) : "memory");
}
DEVINL void push_peer(uint32_t dst, uint32_t src, uint32_t bar, uint32_t peer) {
  asm volatile("{\n.reg .pred pe;\n.reg .b32 d, b;\nelect.sync _|pe, 0xffffffff;\nmapa.shared::cluster.u32 d, %0, %3;\nmapa.shared::cluster.u32 b, %2, %3;\n"
               "@pe cp.async.bulk.shared::cluster.shared::cta.mbarrier::complete_tx::bytes [d], [%1], 16384, [b];\n}" ::"r"(dst), "r"(src), "r"(bar), "r"(peer) : "memory");
}
DEVINL void tma_st(const CUtensorMap* m, int c0, int c1, uint32_t src) {
  asm volatile(EL("cp.async.bulk.tensor.2d.global.shared::cta.bulk_group [%0, {%2, %3}], [%1];") ::"l"(m), "r"(src), "r"(c0), "r"(c1) : "memory");
}
DEVINL void bulk_commit() { asm volatile("cp.async.bulk.commit_group;" ::: "memory"); }
template <int N> DEVINL void bulk_wait_n() { asm volatile("cp.async.bulk.wait_group %0;\nbar.warp.sync 0xffffffff;" ::"n"(N) : "memory"); }
DEVINL void l2_prefetch(const void* g, uint32_t bytes) { asm volatile(EL("cp.async.bulk.prefetch.L2.global [%0], %1;") ::"l"(g), "r"(bytes) : "memory"); }
DEVINL void fence_async_smem() { asm volatile("fence.proxy.async.shared::cta;" ::: "memory"); }
DEVINL void fence_async_gl() { asm volatile("fence.proxy.async.global;" ::: "memory"); }
DEVINL void cluster_wait() { asm volatile("barrier.cluster.wait.aligned;" ::: "memory"); }
DEVINL void bar_sync(int id, int n) { asm volatile("bar.sync %0, %1;" ::"r"(id), "r"(n) : "memory"); }
DEVINL void bar_arrive(int id, int n) { asm volatile("bar.arrive %0, %1;" ::"r"(id), "r"(n) : "memory"); }
DEVINL uint32_t ld_acquire(const uint32_t* p) { uint32_t v; asm volatile("ld.acquire.gpu.global.u32 %0, [%1];" : "=r"(v) : "l"(p) : "memory"); return v; }
DEVINL void watch(const uint32_t* p, uint32_t target, uint32_t all, uint32_t tag, uint32_t slot) {
  uint32_t seen = 0;
#pragma unroll 1
  for (uint32_t n = 0; n < 200000u && seen != all; n++) {
    const uint32_t m = __ballot_sync(~0u, (int)(ld_acquire(p) - target) >= 0) & all;
    if (m != seen) { seen = m; asm volatile("st.release.cta.shared.u32 [%0], %1;" ::"r"(slot), "r"(tag << 16 | m) : "memory"); }
  }
}
template <bool RELAXED = false> DEVINL void await_bit(uint32_t slot, uint32_t tag, int j, uint32_t& rdy) {
  if ((rdy >> j) & 1) return;
#pragma unroll 1
  for (uint32_t n = 0; n < 8000000u; n++) {
    uint32_t v;
    asm volatile("ld.acquire.cta.shared.u32 %0, [%1];" : "=r"(v) : "r"(slot) : "memory");
    if ((v >> 16) == tag && ((v >> j) & 1)) { rdy = v; break; }
    if (RELAXED) __nanosleep(200);
  }
  asm volatile("fence.proxy.async.global;" ::: "memory");
}
DEVINL void poll_ge(const uint32_t* p, uint32_t target) {
#pragma unroll 1
  for (uint32_t n = 0; n < 200000u; n++) if (__all_sync(~0u, (int)(ld_acquire(p) - target) >= 0)) break;
}
DEVINL int lane_id() { int v; asm volatile("mov.u32 %0, %%laneid;" : "=r"(v)); return v; }
__host__ DEVINL int remap(int v) {
  const int c = v >> 1, u = c - 36, r = (u * 37) >> 8;
  const int L = max(c - 4 + max(r + 1, 0), (c - 4) >> 31 & (32 + 8 * c));
  return 2 * L + (v & 1);
}
DEVINL int block_id() { int v; asm volatile("mov.u32 %0, %%ctaid.x;" : "=r"(v)); return v; }
#define cta_id() prm.map[block_id()]
#define IDS() const int lane = lane_id(), b = cta_id(), bm = b >> 4, bn = b & 15, rank = b & 1, pm = 2 * bm + (bn >> 3), pn = bn & 7, po = pm & 1; \
  (void)lane; (void)bm; (void)bn; (void)rank; (void)pm; (void)pn; (void)po
DEVINL void st_tagged(unsigned long long* p, uint32_t v, uint32_t tag) {
  asm volatile("{\n.reg .b64 t;\nmov.b64 t, {%1, %2};\nst.relaxed.gpu.global.b64 [%0], t;\n}" ::"l"(p), "r"(v), "r"(tag) : "memory");
}
DEVINL float ex2(float x) { float y; asm("ex2.approx.ftz.f32 %0, %1;" : "=f"(y) : "f"(x)); return y; }
DEVINL float rcp(float x) { float y; asm("rcp.approx.ftz.f32 %0, %1;" : "=f"(y) : "f"(x)); return y; }
DEVINL uint32_t pack2(float lo, float hi) { uint32_t r; asm("cvt.rn.bf16x2.f32 %0, %1, %2;" : "=r"(r) : "f"(hi), "f"(lo)); return r; }
DEVINL float bf_lo(uint32_t w) { return __uint_as_float(w << 16); }
DEVINL float bf_hi(uint32_t w) { return __uint_as_float(w & 0xFFFF0000u); }
DEVINL float bf_round(float x) { return bf_lo(pack2(x, 0.f)); }
DEVINL uint32_t add_bf16x2(uint32_t a, uint32_t b) { uint32_t r; asm("add.rn.bf16x2 %0, %1, %2;" : "=r"(r) : "r"(a), "r"(b)); return r; }
DEVINL uint32_t max_bf2(uint32_t a, uint32_t b) { uint32_t r; asm("max.bf16x2 %0, %1, %2;" : "=r"(r) : "r"(a), "r"(b)); return r; }
DEVINL uint32_t scale_bf2(uint32_t a) {
  uint32_t r;
  asm("{\n.reg .b32 t;\nmul.rn.bf16x2 t, %1, %3;\nfma.rn.bf16x2 %0, %1, %2, t;\n}" : "=r"(r) : "r"(a), "r"(0x3E353E35u), "r"(0x379E379Eu));
  return r;
}
DEVINL void stsm4(uint32_t addr, uint32_t a, uint32_t b, uint32_t c, uint32_t d) {
  asm volatile("stmatrix.sync.aligned.m8n8.x4.shared.b16 [%0], {%1, %2, %3, %4};" ::"r"(addr), "r"(a), "r"(b), "r"(c), "r"(d) : "memory");
}
DEVINL void ldsm4(uint32_t addr, uint32_t (&r)[4]) {
  asm volatile("ldmatrix.sync.aligned.m8n8.x4.shared.b16 {%0, %1, %2, %3}, [%4];" : "=r"(r[0]), "=r"(r[1]), "=r"(r[2]), "=r"(r[3]) : "r"(addr) : "memory");
}
DEVINL void ldsm4t(uint32_t addr, uint32_t (&r)[4]) {
  asm volatile("ldmatrix.sync.aligned.m8n8.x4.trans.shared.b16 {%0, %1, %2, %3}, [%4];" : "=r"(r[0]), "=r"(r[1]), "=r"(r[2]), "=r"(r[3]) : "r"(addr) : "memory");
}
DEVINL void sts128(uint32_t addr, uint32_t a, uint32_t b, uint32_t c, uint32_t d) {
  asm volatile("st.shared.v4.b32 [%0], {%1, %2, %3, %4};" ::"r"(addr), "r"(a), "r"(b), "r"(c), "r"(d) : "memory");
}
DEVINL float4 lds128f(uint32_t addr) { float4 v; asm volatile("ld.shared.v4.f32 {%0, %1, %2, %3}, [%4];" : "=f"(v.x), "=f"(v.y), "=f"(v.z), "=f"(v.w) : "r"(addr) : "memory"); return v; }
DEVINL float lds32f(uint32_t addr) { float v; asm volatile("ld.shared.f32 %0, [%1];" : "=f"(v) : "r"(addr) : "memory"); return v; }
DEVINL float2 lds64f(uint32_t addr) { float2 v; asm volatile("ld.shared.v2.f32 {%0, %1}, [%2];" : "=f"(v.x), "=f"(v.y) : "r"(addr) : "memory"); return v; }
DEVINL void mma16816(float (&d)[4], uint32_t a0, uint32_t a1, uint32_t a2, uint32_t a3, uint32_t b0, uint32_t b1) {
  asm("mma.sync.aligned.m16n8k16.row.col.f32.bf16.bf16.f32 {%0, %1, %2, %3}, {%4, %5, %6, %7}, {%8, %9}, {%0, %1, %2, %3};"
               : "+f"(d[0]), "+f"(d[1]), "+f"(d[2]), "+f"(d[3]) : "r"(a0), "r"(a1), "r"(a2), "r"(a3), "r"(b0), "r"(b1));
}
DEVINL void mma1688(float (&d)[4], uint32_t a0, uint32_t a1, uint32_t b0) {
  asm("mma.sync.aligned.m16n8k8.row.col.f32.bf16.bf16.f32 {%0, %1, %2, %3}, {%4, %5}, {%6}, {%0, %1, %2, %3};"
               : "+f"(d[0]), "+f"(d[1]), "+f"(d[2]), "+f"(d[3]) : "r"(a0), "r"(a1), "r"(b0));
}
DEVINL void mma1688h(float (&d)[4], uint32_t a0, uint32_t a1, uint32_t b0) {
  asm("mma.sync.aligned.m16n8k8.row.col.f32.f16.f16.f32 {%0, %1, %2, %3}, {%4, %5}, {%6}, {%0, %1, %2, %3};"
               : "+f"(d[0]), "+f"(d[1]), "+f"(d[2]), "+f"(d[3]) : "r"(a0), "r"(a1), "r"(b0));
}
DEVINL void mma16816h(float (&d)[4], uint32_t a0, uint32_t a1, uint32_t a2, uint32_t a3, uint32_t b0, uint32_t b1) {
  asm("mma.sync.aligned.m16n8k16.row.col.f32.f16.f16.f32 {%0, %1, %2, %3}, {%4, %5, %6, %7}, {%8, %9}, {%0, %1, %2, %3};"
               : "+f"(d[0]), "+f"(d[1]), "+f"(d[2]), "+f"(d[3]) : "r"(a0), "r"(a1), "r"(a2), "r"(a3), "r"(b0), "r"(b1));
}
template <int N> DEVINL void fence_regs(uint32_t (&d)[N]) {
#pragma unroll
  for (int i = 0; i < N; i++) asm volatile("" : "+r"(d[i])::"memory");
}
template <int N> DEVINL void fence_regs(float (&d)[N]) {
#pragma unroll
  for (int i = 0; i < N; i++) asm volatile("" : "+f"(d[i])::"memory");
}

__device__ __align__(1024) bf16 g_xs[2048 * 1024];
__device__ __align__(1024) bf16 g_os[2048 * 1024];
__device__ __align__(1024) bf16 g_k[32 * 2048 * 32];
__device__ __align__(1024) bf16 g_v[32 * 2048 * 32];
__device__ __align__(128) float2 g_stats[8 * 2048];
__device__ __align__(16) float g_csp[2 * 16 * 8 * 192];
__device__ __align__(128) float g_kn[2 * 128 * 32];
__device__ unsigned long long g_halo[2 * 128 * 32 * 32];
__device__ __align__(128) uint32_t g_cnt[256 * 32];
__device__ uint32_t g_epoch;

DEVINL uint32_t* cnt_x(int l, int bm) { return g_cnt + (l * 8 + bm) * 32; }
DEVINL uint32_t* cnt_o(int l, int pm, int h) { return g_cnt + (32 + (l * 16 + pm) * 2 + h) * 32; }
DEVINL uint32_t* cnt_kv(int lb, int bn) { return g_cnt + (160 + lb * 16 + bn) * 32; }
DEVINL uint32_t* cnt_ad(int bn) { return g_cnt + (192 + bn) * 32; }
DEVINL uint32_t* cnt_cs(int t, int bn) { return g_cnt + (208 + t * 16 + bn) * 32; }

DEVINL int qord(int i, int l, int pn) { return l == 0 ? i : i < 4 ? ((2 * pn) ^ (i & 2)) + (i & 1) : i - 4 < 2 * (pn & 6) ? i - 4 : i; }
DEVINL int pord(int i, int l, int p) { return (l & 1) || i > p ? i : i ? i - 1 : p; }
struct Params {
  CUtensorMap m[17];
  const bf16* x0;
  const bf16* wq[2];
  const bf16* wo[2];
  uint32_t* epoch;
  uint32_t zero;
  int map[128];
};
enum { M_X0A = 0, M_XSA, M_WQA, M_WQB, M_WOA, M_WOB, M_OS, M_K, M_V, M_X0R, M_XSR, M_XSO, M_OUT, M_XST, M_X0H, M_K4, M_V4, M_COUNT };

constexpr uint32_t QSTG = 57344;
constexpr uint32_t T0 = 65536, TSTG = 32768;
constexpr uint32_t ONES = 229376;
constexpr uint32_t PSTG = 32768, RES = 196608;
constexpr uint32_t ASC = 17408;
constexpr uint32_t RSTD = 229376, MEAN = 230400, COLS = 230912, KMAX = 231680, B_QD = 231688, B_OW = 231704, BARS = 232192, SMEM_BYTES = 232448;
constexpr uint32_t B_QF = BARS, B_QE = BARS + 32, B_TF = BARS + 64, B_TE = BARS + 96, B_PF = BARS + 128, B_PE = BARS + 176,
                   B_RF = BARS + 224, W_X = BARS + 232, W_O = BARS + 236, B_QL = BARS + 240, B_PA = BARS + 248;
enum { NB_ST = 1, NB_KV = 2  , NB_DONE = 3, NB_SC = 4, NB_SIG = 5  , NB_KN = 9  , NB_X = 11, NB_HALO = 12  , NB_X0 = 15 };

DEVINL uint32_t pslot_b(uint32_t s, int l) { return ((((l & 1) ? 0x320415u : 0x468795u) >> (4 * s)) & 15) * 16384u; }
DEVINL uint32_t pslot_a(uint32_t s, int l) { return ((((l & 1) ? 0xBA7896u : 0x32DCBAu) >> (4 * s)) & 15) * 16384u; }

constexpr float QSCALE = 0.17677669529663687f * 1.4426950408889634f;

DEVINL uint32_t hfma2(uint32_t a, uint32_t b, uint32_t c) { uint32_t r; asm("fma.rn.f16x2 %0, %1, %2, %3;" : "=r"(r) : "r"(a), "r"(b), "r"(c)); return r; }
DEVINL uint32_t pack2h(float lo, float hi) { uint32_t r; asm("cvt.rn.f16x2.f32 %0, %1, %2;" : "=r"(r) : "f"(hi), "f"(lo)); return r; }
DEVINL uint32_t h2_to_bf2(uint32_t h) {
  float a, b;
  asm("{\n.reg .b16 l, h;\nmov.b32 {l, h}, %2;\ncvt.f32.f16 %0, l;\ncvt.f32.f16 %1, h;\n}" : "=f"(a), "=f"(b) : "r"(h));
  return pack2(a, b);
}
DEVINL uint32_t exp2_h2(uint32_t s) {
  const uint32_t r = hfma2(s, 0x00800080u, 0x007E007Eu);
  const uint32_t g = hfma2(hfma2(r, 0xF800F800u, 0x33FD33FDu), 0x44004400u, s);
  return __funnelshift_l(r, r, 7) + hfma2(hfma2(g, g, 0x0DE10DE1u), g, 0x00300030u);
}
constexpr uint32_t NOT_F16 = 0x7FC00000u, K_LO = 0x35000000u  ;
DEVINL uint32_t f16_class(uint32_t norm2, uint32_t lo) { return norm2 - lo > 0x4E800000u - lo ? NOT_F16 : norm2; }

DEVINL void attn_slow(const uint32_t (&q)[8], float up, int head, const float* kn, float (&res)[20], int lane) {
  const int g = lane >> 2, qd = lane & 3;
  const bf16* kb = g_k + (size_t)head * 2048 * 32;
  const bf16* vb = g_v + (size_t)head * 2048 * 32;
  float o[4][4], m0 = -INFINITY, m1 = -INFINITY, l0 = 0.f, l1 = 0.f;
#pragma unroll
  for (int j = 0; j < 4; j++) { o[j][0] = o[j][1] = o[j][2] = o[j][3] = 0.f; }
#pragma unroll 1
  for (int k0 = 0; k0 < 2048; k0 += 16) {
    float s[2][4];
    const bool kh = __float_as_uint(__ldcg(kn + (k0 >> 8) * 32 + ((k0 >> 6) & 1) * 8 + ((k0 >> 7) & 1) * 4 + ((k0 >> 4) & 3))) != NOT_F16;
#pragma unroll
    for (int nt = 0; nt < 2; nt++) {
      s[nt][0] = s[nt][1] = s[nt][2] = s[nt][3] = 0.f;
      const uint32_t* kp = (const uint32_t*)(kb + (size_t)(k0 + nt * 8 + g) * 32) + qd;
      uint32_t kf[4];
#pragma unroll
      for (int i = 0; i < 4; i++) { kf[i] = __ldcg(kp + 4 * i); if (kh) kf[i] = h2_to_bf2(kf[i]); }
      mma16816(s[nt], q[0], q[1], q[2], q[3], kf[0], kf[1]);
      mma16816(s[nt], q[4], q[5], q[6], q[7], kf[2], kf[3]);
      s[nt][0] *= up; s[nt][1] *= up; s[nt][2] *= up; s[nt][3] *= up;
    }
    float a0 = fmaxf(fmaxf(s[0][0], s[0][1]), fmaxf(s[1][0], s[1][1]));
    float a1 = fmaxf(fmaxf(s[0][2], s[0][3]), fmaxf(s[1][2], s[1][3]));
    a0 = fmaxf(a0, __shfl_xor_sync(~0u, a0, 1)); a0 = fmaxf(a0, __shfl_xor_sync(~0u, a0, 2));
    a1 = fmaxf(a1, __shfl_xor_sync(~0u, a1, 1)); a1 = fmaxf(a1, __shfl_xor_sync(~0u, a1, 2));
    const float n0 = fmaxf(m0, a0), n1 = fmaxf(m1, a1);
    const float c0 = (m0 == n0) ? 1.f : ex2(m0 - n0), c1 = (m1 == n1) ? 1.f : ex2(m1 - n1);
    m0 = n0; m1 = n1;
    const uint32_t p0 = pack2(ex2(s[0][0] - n0), ex2(s[0][1] - n0)), p1 = pack2(ex2(s[0][2] - n1), ex2(s[0][3] - n1));
    const uint32_t p2 = pack2(ex2(s[1][0] - n0), ex2(s[1][1] - n0)), p3 = pack2(ex2(s[1][2] - n1), ex2(s[1][3] - n1));
    l0 = l0 * c0 + bf_lo(p0) + bf_hi(p0) + bf_lo(p2) + bf_hi(p2);
    l1 = l1 * c1 + bf_lo(p1) + bf_hi(p1) + bf_lo(p3) + bf_hi(p3);
#pragma unroll
    for (int j = 0; j < 4; j++) {
      o[j][0] *= c0; o[j][1] *= c0; o[j][2] *= c1; o[j][3] *= c1;
      const unsigned short* vp = (const unsigned short*)(vb + (size_t)(k0 + 2 * qd) * 32 + j * 8 + g);
      const uint32_t b0 = (uint32_t)__ldcg(vp) | ((uint32_t)__ldcg(vp + 32) << 16);
      const uint32_t b1 = (uint32_t)__ldcg(vp + 256) | ((uint32_t)__ldcg(vp + 288) << 16);
      mma16816(o[j], p0, p1, p2, p3, b0, b1);
    }
  }
  l0 += __shfl_xor_sync(~0u, l0, 1); l0 += __shfl_xor_sync(~0u, l0, 2);
  l1 += __shfl_xor_sync(~0u, l1, 1); l1 += __shfl_xor_sync(~0u, l1, 2);
#pragma unroll
  for (int j = 0; j < 4; j++) { res[4 * j] = o[j][0]; res[4 * j + 1] = o[j][1]; res[4 * j + 2] = o[j][2]; res[4 * j + 3] = o[j][3]; }
  res[16] = l0; res[18] = l1;
}

__global__ void __cluster_dims__(2, 1, 1) __launch_bounds__(384, 1) fused_kernel(const __grid_constant__ Params prm) {
  extern __shared__ __align__(1024) char smem[];
  const uint32_t sb = (uint32_t)__cvta_generic_to_shared(smem);
  const int tid = threadIdx.x;
  const int wid = __shfl_sync(0xffffffffu, tid >> 5, 0), wg = wid >> 2, w = wid & 3;
  const int bm = remap(blockIdx.x) >> 4, bn = remap(blockIdx.x) & 15;
  auto first_tile = [&](int kt) {
    e_expect_tx(sb + B_QF + 8 * kt, QSTG);
    tma_ld(sb + kt * QSTG, &prm.m[M_X0A], kt * 64, bm * 256, sb + B_QF + 8 * kt);
    tma_ld3(sb + kt * QSTG + 32768, &prm.m[M_WQA], bn * 64, kt * 64, 0, sb + B_QF + 8 * kt);
  };
  if (wid == 8) {
    e_init(sb + B_QF, 1);
    asm volatile("fence.mbarrier_init.release.cluster;" ::: "memory");
    first_tile(0);
  }
  if (wid < 8) {
#pragma unroll
    for (int i = 0; i < 4; i++) {
      const uint32_t cnt = (uint32_t)((i == 0 ? 0x14112140 : i == 1 ? 0x04112141 : i == 2 ? 0x14412141 : 0x24412141) >> (4 * wid)) & 7;
      if (cnt) e_init(sb + BARS + 32 * wid + 8 * i, cnt);
    }
    if (wid < 3) e_init(sb + B_QD + wid * 8, wid < 2 ? 1 : 2);
    if (tid == 255) *(uint2*)(smem + W_X) = make_uint2(0u, 0u);
    asm volatile("fence.mbarrier_init.release.cluster;" ::: "memory");
  }
  const uint32_t epoch = *(volatile uint32_t*)prm.epoch;
  __syncthreads();
  asm volatile("barrier.cluster.arrive.relaxed.aligned;" ::: "memory");

  if (wg == 2) {
    asm volatile("setmaxnreg.dec.sync.aligned.u32 56;");
    const uint32_t ep1 = epoch + 1;
    if (w == 0) {
      first_tile(1);
      mbar_wait(sb + B_QF, 0);
      first_tile(2); first_tile(3);
#pragma unroll 1
      for (int kt = 4; kt < 16; kt++) l2_prefetch(prm.wq[0] + kt * 196608 + blockIdx.x * 1536, 3072);
      cluster_wait();
#pragma unroll 1
      for (int l = 0; l < 4; l++) {
        IDS();
        const CUtensorMap* mw = &prm.m[M_WQA + (l & 1)];
        const CUtensorMap* mh = &prm.m[l == 0 ? M_X0H : M_XSO];
        const CUtensorMap* mo = &prm.m[M_WOA + (l & 1)];
        auto q_b = [&](int i) {
          const int s = i & 3;
          mbar_wait(sb + B_QE + 8 * s, ((i >> 2) & 1) ^ 1);
          e_expect_tx(sb + B_QF + 8 * s, QSTG);
          tma_ld3(sb + s * QSTG + 32768, mw, bn * 64, qord(i, l, pn) * 64, 0, sb + B_QF + 8 * s);
        };
        uint32_t rdy = l ? 0u : ~0u;
        auto q_a = [&](int i) {
          const int kt = qord(i, l, pn);
          await_bit(sb + W_X, l, kt >> 1, rdy);
          tma_ld_mc(sb + (i & 3) * QSTG + rank * 16384, mh, kt * 64, bm * 256 + rank * 128, sb + B_QF + 8 * (i & 3));
        };
        if (l > 0) {
#pragma unroll 1
          for (int i = 0; i < 4; i++) {
            const int kt = qord(i, l, pn);
            await_bit(sb + W_X, l, kt >> 1, rdy);
            e_expect_tx(sb + B_QF + 8 * i, 16384);
            tma_ld(sb + i * QSTG + (po ^ 1) * 16384, &prm.m[M_XSO], kt * 64, (pm ^ 1) * 128, sb + B_QF + 8 * i);
          }
        }
#pragma unroll 1
        for (int i = 4; i < 16; i++) {
          q_b(i); q_a(i);
          if (l == 0 && i >= 8 && i < 12) l2_prefetch(prm.wq[1] + (blockIdx.x * 4 + i - 8) * 6144, 12288);
          if (l < 2 && i == 12) l2_prefetch(prm.wo[l] + blockIdx.x * 8192, 16384);
        }
        if (l & 1) {
          if (l == 3) poll_ge(cnt_ad(bn), ep1 * 16);
          const int krow = 2 * bn * 2048 + bm * 256;
          uint32_t* kvc = cnt_kv(l >> 1, bn);
#pragma unroll 1
          for (int m = 1; m >= 0; m--) {
            bar_sync(m ? NB_ST : NB_KV, 288);
#pragma unroll
            for (int i = 0; i < 4; i++) tma_st(&prm.m[M_K4 + (i >> 1)], 0, krow + (i & 1) * 128 + m * 64, sb + T0 + i * 8192 + m * 4096);
            if (m) {
              sts128(sb + ONES + lane * 32, 0x3f803f80u, 0x3f803f80u, 0x3f803f80u, 0x3f803f80u);
              sts128(sb + ONES + lane * 32 + 16, 0x3f803f80u, 0x3f803f80u, 0x3f803f80u, 0x3f803f80u);
              fence_async_smem();
              __syncwarp();
            }
          }
          e_arrive(sb + B_TF);
          bulk_commit(); bulk_wait_n<0>();
          e_red(kvc + bm);
          bar_sync(NB_KV + 12, 288);
          uint32_t seen = 0;
#pragma unroll 1
          for (int it = 1; it < 16; it++) {
            const int s = it & 3, blk = it;
            if (it == 4) { tma_st(&prm.m[M_K], 0, krow + 2048, sb); tma_st(&prm.m[M_V], 0, krow + 2048, sb + 16384); bulk_commit(); }
            if (it == 5) { bulk_wait_n<0>(); e_red(kvc + bm); }
            if (it == 12) { e_expect_tx(sb + B_RF, 32768); tma_ld3(sb + RES, &prm.m[M_XSR], 0, pm * 128, 2 * pn, sb + B_RF); }
            if (it == 2 || it == 3) mbar_wait(sb + B_TF + 8 * (it - 1), 0);
            mbar_wait_long(sb + B_TE + 8 * s, ((it >> 2) & 1) ^ 1);
            if (it < 8) {
#pragma unroll 1
              for (uint32_t n = 0; n < 200000u && !((seen >> it) & 1); n++)
                seen = __ballot_sync(~0u, (int)(ld_acquire(kvc + ((bm + lane) & 7)) - (ep1 * 2 - 1)) >= 0);
              fence_async_gl();
            } else if (it == 8) { poll_ge(kvc + (lane & 7), ep1 * 2); fence_async_gl(); bar_arrive(NB_HALO, 64); }
            else if (it == 15) bar_arrive(NB_HALO + 1, 64);
            const int row = (2 * bn + (it >> 3)) * 2048 + ((bm + blk) & 7) * 256;
            e_expect_tx(sb + B_TF + 8 * s, 32768);
            tma_ld(sb + T0 + s * TSTG, &prm.m[M_K], 0, row, sb + B_TF + 8 * s);
            tma_ld(sb + T0 + s * TSTG + 16384, &prm.m[M_V], 0, row, sb + B_TF + 8 * s);
          }
        }
        auto p_b = [&](int i, uint32_t s, uint32_t par) {
          const int kt = pord(i, l, bn >> 1);
          mbar_wait(sb + B_PE + 8 * s, par ^ 1);
          e_expect_tx(sb + B_PF + 8 * s, PSTG);
          tma_ld5(sb + pslot_b(s, l), mo, kt >> 3, 2 * (kt & 7), 2 * pn, sb + B_PF + 8 * s);
        };
        auto p_a = [&](int i, uint32_t s) {
          const int kt = pord(i, l, bn >> 1);
          await_bit(sb + W_O, l + 1, kt, rdy);
          tma_ld_mc(sb + pslot_a(s, l) + rank * 8192, &prm.m[M_OS], kt * 64, pm * 128 + rank * 64, sb + B_PF + 8 * s);
        };
        auto p_a2 = [&](int i) {
          const int kt = pord(i, l, bn >> 1);
          await_bit(sb + W_O, l + 1, kt, rdy);
          tma_ld(sb + pslot_a(i, l), &prm.m[M_OS], kt * 64, pm * 128, sb + B_PF + 8 * i);
          tma_ld(sb + pslot_a(i, l) + 8192, &prm.m[M_OS], kt * 64, pm * 128 + 64, sb + B_PF + 8 * i);
        };
        rdy = 0;
        if (l & 1) {
#pragma unroll 1
          for (int u = 0; u < 6; u++) { const int i = (0x205413 >> (4 * u)) & 7; if (u == 4) mbar_wait_long(sb + B_TE, 1); p_b(i, i, i < 4 ? 1 : 0); }
#pragma unroll 1
          for (int u = 0; u < 6; u++) {
            const int i = (0x542130 >> (4 * u)) & 7;
            if (!(u & 1)) mbar_wait_long(sb + B_TE + 8 + 4 * u, 1);
            p_a2(i);
          }
        } else {
#pragma unroll 1
          for (int u = 0; u < 5; u++) { const int i = (0x32140 >> (4 * u)) & 7; if (!(u & 5)) mbar_wait(sb + B_QE + 8 + 4 * u, 1); p_b(i, i, 0); }
          mbar_wait(sb + B_QE + 24, 1);
          mbar_wait(sb + B_OW, (l >> 1) & 1);
          fence_async_gl();
          rdy = 1u << (bn >> 1);
#pragma unroll 1
          for (int i = 0; i < 4; i++) { p_a(i, i); }
          bar_sync(NB_DONE, 96);
          e_arrive_both(sb + B_PA);
          p_b(5, 5, 0);
          mbar_wait(sb + B_PA, (l >> 1) & 1);
          p_a(4, 4); p_a(5, 5);
        }
        uint32_t s = 0, lap = 1;
#pragma unroll 1
        for (int i = 6; i < 16; i++) {
          if (i == 12 && !(l & 1)) { e_expect_tx(sb + B_RF, 32768); tma_ld3(sb, &prm.m[l == 0 ? M_X0R : M_XSR], 0, pm * 128, 2 * pn, sb + B_RF); }
          p_b(i, s, ((s < 4 ? l : 0) + lap) & 1);
          p_a(i, s);
          if (++s == 6) { s = 0; lap++; }
        }
        const CUtensorMap* mn = &prm.m[M_WQA + ((l + 1) & 1)];
        if (l < 3) {
          mbar_wait(sb + B_PE + 8 * 4, 1); mbar_wait(sb + B_PE + 8 * 5, 1);
          tma_ld3(sb + 32768, mn, bn * 64, 2 * pn * 64, 0, sb + B_QL);
          mbar_wait(sb + B_PE + 8 * 0, l & 1);
          tma_ld3(sb + QSTG + 32768, mn, bn * 64, (2 * pn + 1) * 64, 0, sb + B_QL);
          mbar_wait(sb + B_PE + 8 * 1, l & 1);
          e_expect_tx(sb + B_QD, 40960);
          tma_ld3(sb + 2 * QSTG + 32768, mn, bn * 64, ((2 * pn) ^ 2) * 64, 0, sb + B_QD);
          bar_sync(NB_X, 288);
          e_expect_tx(sb + B_QL, 49152);
          e_expect_tx(sb + B_QD + 8, 40960);
          tma_ld3(sb + 3 * QSTG + 32768, mn, bn * 64, (((2 * pn) ^ 2) + 1) * 64, 0, sb + B_QD + 8);
        }
      }
      if (blockIdx.x == 0 && lane_id() == 0) *(volatile uint32_t*)prm.epoch = ep1;
    } else {
      const int hw = w - 1;
      if (hw == 1 && lane_id() < M_COUNT) asm volatile("prefetch.tensormap [%0];" ::"l"(&prm.m[lane_id()]) : "memory");
      cluster_wait();
      mbar_wait(sb + B_QF, 0);
#pragma unroll 1
      for (int l = 0; l < 4; l++) {
        IDS();
        if (hw == 2 && l > 0) watch(cnt_x(l, bm) + (lane & 7), ep1 * 2, 0xFFu, l, sb + W_X);
        if (l == 0) {
#pragma unroll 1
          for (int r = 2 * hw; r < 16; r += 6) {
            const uint4* p = (const uint4*)(prm.x0 + (size_t)(b * 16 + r) * 1024) + lane;
            float s1[2] = {0.f, 0.f}, s2[2] = {0.f, 0.f};
#pragma unroll
            for (int i = 0; i < 8; i++) {
              const uint4 v = __ldg(p + 32 * i);
              const uint32_t u[4] = {v.x, v.y, v.z, v.w};
#pragma unroll
              for (int k = 0; k < 4; k++) { const float a = bf_lo(u[k]), c = bf_hi(u[k]); s1[i >> 2] += a + c; s2[i >> 2] = fmaf(a, a, fmaf(c, c, s2[i >> 2])); }
            }
#pragma unroll
            for (int o = 16; o; o >>= 1)
#pragma unroll
              for (int rr = 0; rr < 2; rr++) { s1[rr] += __shfl_xor_sync(~0u, s1[rr], o); s2[rr] += __shfl_xor_sync(~0u, s2[rr], o); }
            if (lane == 0) *(float4*)&g_stats[b * 16 + r] = make_float4(s1[0], s2[0], s1[1], s2[1]);
          }
        }
        if (l == 1) { uint32_t rdy = 0; await_bit<true>(sb + W_X, 1, pn, rdy); mbar_hint(sb + B_QF + 8, 0); }
        if (l < 2) {
          float cs[8];
#pragma unroll
          for (int i = 0; i < 8; i++) cs[i] = 0.f;
          const uint4* wp = (const uint4*)(prm.wq[l] + (size_t)(bm * 128 + (lane >> 3)) * 3072 + hw * 1024 + bn * 64) + (lane & 7);
#pragma unroll 8
          for (int i = 0; i < 32; i++) {
            const uint4 v = __ldg(wp + (size_t)i * 4 * 384);
            cs[0] += bf_lo(v.x); cs[1] += bf_hi(v.x); cs[2] += bf_lo(v.y); cs[3] += bf_hi(v.y);
            cs[4] += bf_lo(v.z); cs[5] += bf_hi(v.z); cs[6] += bf_lo(v.w); cs[7] += bf_hi(v.w);
          }
#pragma unroll
          for (int i = 0; i < 8; i++) { cs[i] += __shfl_xor_sync(~0u, cs[i], 8); cs[i] += __shfl_xor_sync(~0u, cs[i], 16); }
          if (lane < 8) {
            float4* d = (float4*)(g_csp + ((l * 16 + bn) * 8 + bm) * 192 + hw * 64 + lane * 8);
            d[0] = make_float4(cs[0], cs[1], cs[2], cs[3]); d[1] = make_float4(cs[4], cs[5], cs[6], cs[7]);
          }
          __syncwarp();
          asm volatile("fence.acq_rel.gpu;" ::: "memory");
          e_red_relaxed(cnt_cs(l, bn));
          if (l == 0) e_red_relaxed(cnt_x(0, bm) + pn);
          poll_ge(lane < 8 && l == 0 ? cnt_x(0, bm) + lane : cnt_cs(l, bn), ep1 * (lane < 8 && l == 0 ? 6 : 24));
        }
        if (l > 0) {
          uint32_t rdy = 0;
#pragma unroll 1
          for (int j = 0; j < 8; j++) await_bit<true>(sb + W_X, l, j, rdy);
        }
#pragma unroll 1
        for (int it = hw * 32 + lane; it < 176; it += 96) {
          const bool rows = it < 128;
          const float4* p = rows ? (const float4*)(g_stats + bm * 256) + it : (const float4*)(g_csp + ((l & 1) * 16 + bn) * 8 * 192) + (it - 128);
          const int stride = rows ? 1024 : 48, np = rows && l == 0 ? 1 : 8;
          float4 a = make_float4(0.f, 0.f, 0.f, 0.f);
#pragma unroll
          for (int k = 0; k < 8; k++) if (k < np) { const float4 v = __ldcg(p + k * stride); a.x += v.x; a.y += v.y; a.z += v.z; a.w += v.w; }
          if (rows) {
            const float m0 = a.x * (1.f / 1024.f), m1 = a.z * (1.f / 1024.f);
            const float v0 = fmaxf(a.y * (1.f / 1024.f) - m0 * m0, 0.f), v1 = fmaxf(a.w * (1.f / 1024.f) - m1 * m1, 0.f);
            const float r0 = __fdividef(1.f, bf_round(sqrtf(bf_round(bf_round(v0) + 1e-5f)))), r1 = __fdividef(1.f, bf_round(sqrtf(bf_round(bf_round(v1) + 1e-5f))));
            *(float2*)(smem + RSTD + it * 8) = make_float2(r0, r1);
            *(uint32_t*)(smem + MEAN + it * 4) = pack2(-m0, -m1);
          } else {
            float2* d = (float2*)(smem + COLS) + ((it - 128) >> 2) * 8 + (it & 1) * 4 + ((it >> 1) & 1);
            d[0] = make_float2(a.y, a.x); d[2] = make_float2(a.w, a.z);
          }
        }
        __syncwarp();
        if (lane == 0) asm volatile("red.release.cta.shared.add.u32 [%0], 0x100;" ::"r"(sb + W_X) : "memory");
        if (hw == 2) {
          if (!(l & 1)) {
            bar_sync(NB_ST, 288);
            const volatile unsigned long long* hp = g_halo + ((size_t)(l >> 1) * 128 + b - 16) * 1024 + lane;
#pragma unroll 1
            for (int h = 0; h < 2; h++) {
              uint32_t t[16];
#pragma unroll
              for (int i = 0; i < 16; i++) t[i] = 0;
#pragma unroll 1
              for (uint32_t n = bm ? 0 : 100000u; n < 100000u; n++) {
                uint32_t miss = 0;
#pragma unroll
                for (int i = 0; i < 16; i++) {
                  const unsigned long long v = hp[h * 512 + i * 32];
                  t[i] = (uint32_t)v; miss |= (uint32_t)(v >> 32) ^ ep1;
                }
                if (__all_sync(~0u, !miss)) break;
              }
              const uint32_t r = (lane & 7) + ((lane >> 3) & 1) * 8, rv = lane >> 2;
#pragma unroll
              for (int jj = 0; jj < 2; jj++) stsm4(sb + 2 * h * ASC + r * 64 + (((2 * jj + (lane >> 4)) ^ ((r >> 1) & 3)) << 4), t[4 * jj], t[4 * jj + 1], t[4 * jj + 2], t[4 * jj + 3]);
              const uint32_t ad = sb + (2 * h + 1) * ASC + rv * 64 + (((lane & 3) ^ ((rv >> 1) & 3)) << 4);
              sts128(ad, t[8], t[10], t[12], t[14]); sts128(ad + 512, t[9], t[11], t[13], t[15]);
              bar_arrive(NB_HALO + h, 64);
            }
          } else {
            bar_sync(NB_HALO, 64);
            const uint4* kp = (const uint4*)(g_kn + ((l >> 1) * 128 + bn * 8) * 32) + 2 * lane;
            const uint4 v = __ldcg(kp), u = __ldcg(kp + 1);
            const uint32_t mx = max(max(max(v.x, v.y), max(v.z, v.w)), max(max(u.x, u.y), max(u.z, u.w)));
            const uint32_t m0 = __reduce_max_sync(~0u, (lane & 2) ? 0u : mx), m1 = __reduce_max_sync(~0u, (lane & 2) ? mx : 0u);
            if (lane == 0) *(uint2*)(smem + KMAX) = make_uint2(m0, m1);
            __syncwarp();
            bar_arrive(NB_KN, 160); bar_arrive(NB_KN + 1, 160);
            bar_sync(NB_HALO + 1, 64);
            watch(cnt_o(l, pm, 0) + (lane & 7), ep1 * 2, 0xFFu, l + 1, sb + W_O);
          }
        } else {
          bar_sync(NB_SIG + 2 * hw, 160); bar_sync(NB_SIG + 2 * hw + 1, 160);
          if (!(l & 1)) bar_arrive(NB_DONE, 96);
          if (hw == (l & 1)) bar_arrive((l & 1) ? NB_DONE : NB_KN, 64);
          asm volatile("fence.acq_rel.gpu;" ::: "memory");
          e_red_relaxed(cnt_o(l, 2 * bm, hw) + (bn >> 1));
          e_red_relaxed(cnt_o(l, 2 * bm + 1, hw) + (bn >> 1));
          if (hw == 0 && !(l & 1)) e_arrive_both(sb + B_OW);
          if (hw == 1 && l == 1) { e_red_relaxed(cnt_ad(bn)); e_red_relaxed(cnt_ad(bn)); }
        }
        if (hw == 2) { bar_sync((l & 1) ? NB_DONE : NB_KN, 64); watch(cnt_o(l, pm, (lane >> 3) & 1) + (lane & 7), ep1 * 2, 0xFFFFu, l + 1, sb + W_O); }
        if (l < 3) {
          bar_sync(NB_X0, 352);
          if (hw == 0) {
            e_red(cnt_x(l + 1, bm) + pn);
          } else if (hw == 1) {
            mbar_wait(sb + B_PE + 8 * 3, l & 1);
            push_peer(sb + 2 * QSTG + po * 16384, sb + po * 16384, sb + B_QD, rank ^ 1);
            push_peer(sb + 3 * QSTG + po * 16384, sb + QSTG + po * 16384, sb + B_QD + 8, rank ^ 1);
          }
        }
      }
    }
  } else {
    asm volatile("setmaxnreg.inc.sync.aligned.u32 224;");
    const uint32_t zero = prm.zero;
    cluster_wait();
    const uint32_t ep1 = __shfl_sync(~0u, epoch + 1, 0);
#pragma unroll 1
    for (int l = 0; l < 4; l++) {
      {
        float acc[2][96];
#pragma unroll
        for (int i = 0; i < 96; i++) { acc[0][i] = 0.f; acc[1][i] = 0.f; }
        fence_regs(acc[0]); fence_regs(acc[1]);
        const bool early = l > 0 && wg == ((cta_id() >> 3) & 1);
#pragma unroll 1
        for (int kt = 0; kt < 14; kt++) {
          const int s = kt & 3;
          if (l > 0 && kt < 4 && kt != 1) mbar_wait(sb + (kt ? B_QD - 16 + 8 * kt : B_QL), (l + 1) & 1);
          if (!(early && kt < 4)) mbar_wait(sb + B_QF + 8 * s, (kt >> 2) & 1);
          const uint64_t da = mkdesc(sb + s * QSTG + wg * 16384, 16, 1024, 1), db = mkdesc(sb + s * QSTG + 32768, 8192, 1024, 1);
          wg_fence();
#pragma unroll
          for (int k = 0; k < 4; k++)
#pragma unroll
            for (int m = 0; m < 2; m++) wgmma_m64n192k16_ss_tb(acc[m], da + m * 512 + k * 2, db + k * 128, 1);
          wg_commit();
          wg_wait<1>();
          if (early && kt < 5) {
#pragma unroll 1
            for (int i = kt == 3 ? 0 : 3; i < kt; i++) { mbar_wait(sb + B_QF + 8 * i, 0); if (w == 0) e_arrive_both(sb + B_QE + 8 * i); }
          } else if (kt > 0 && w == 0) e_arrive_both(sb + B_QE + 8 * ((kt - 1) & 3));
          if (kt == 11 + 2 * wg) {
#pragma unroll 1
            for (uint32_t n = 0; n < 4000000u; n++) {
              uint32_t v;
              asm volatile("ld.acquire.cta.shared.u32 %0, [%1];" : "=r"(v) : "r"(sb + W_X) : "memory");
              if ((v >> 8) == (uint32_t)(l * 256 + 3)) break;
            }
            const int lane = lane_id();
            float nm[4];
#pragma unroll
            for (int i = 0; i < 4; i++) nm[i] = bf_lo(*(volatile unsigned short*)(smem + MEAN + (wg * 128 + w * 16 + (lane >> 2) + (i >> 1) * 64 + (i & 1) * 8) * 2));
            wg_wait<0>();
            fence_regs(acc[0]); fence_regs(acc[1]);
#pragma unroll
            for (int j = 0; j < 12; j++) {
              const float4 c = lds128f(sb + COLS + j * 64 + (lane & 3) * 16);
#pragma unroll
              for (int m = 0; m < 2; m++) {
                float* a = &acc[m][8 * j];
                a[0] = fmaf(nm[2 * m], c.y, a[0]); a[1] = fmaf(nm[2 * m], c.x, a[1]); a[2] = fmaf(nm[2 * m + 1], c.y, a[2]); a[3] = fmaf(nm[2 * m + 1], c.x, a[3]);
                a[4] = fmaf(nm[2 * m], c.w, a[4]); a[5] = fmaf(nm[2 * m], c.z, a[5]); a[6] = fmaf(nm[2 * m + 1], c.w, a[6]); a[7] = fmaf(nm[2 * m + 1], c.z, a[7]);
              }
            }
            fence_regs(acc[0]); fence_regs(acc[1]);
          }
        }
        auto part = [&](int s, int m, int k0, int k1) {
          const uint64_t da = mkdesc(sb + s * QSTG + wg * 16384 + m * 8192, 16, 1024, 1), db = mkdesc(sb + s * QSTG + 32768, 8192, 1024, 1);
          wg_fence();
#pragma unroll
          for (int k = k0; k < k1; k++) wgmma_m64n192k16_ss_tb(acc[m], da + k * 2, db + k * 128, 1);
          wg_commit();
        };
        mbar_wait(sb + B_QF + 16, 1);
        part(2, 1, 0, 4);
        wg_wait<1>();
        if (w == 0) e_arrive_both(sb + B_QE + 8);
        if (!(l & 1)) bar_arrive(NB_ST, 288);
        mbar_wait(sb + B_QF + 24, 1);
        part(3, 1, 0, 4);
        part(2, 0, 0, 2);
        IDS();
        const int g = lane >> 2, qd = lane & 3;
        float rs[2][2];
#pragma unroll
        for (int i = 0; i < 4; i++) rs[i >> 1][i & 1] = lds32f(sb + RSTD + (wg * 128 + w * 16 + g + (i >> 1) * 64 + (i & 1) * 8) * 4);
        auto scale = [&](int gi, int m, float sc) {
          const float r0 = rs[m][0] * sc, r1 = rs[m][1] * sc;
#pragma unroll
          for (int i = 0; i < 16; i++) acc[m][16 * gi + i] *= (i & 2) ? r1 : r0;
        };
        auto pack_b = [&](int gi, int m, uint32_t (&t)[8]) {
#pragma unroll
          for (int i = 0; i < 8; i++) t[i] = pack2(acc[m][16 * gi + 2 * i], acc[m][16 * gi + 2 * i + 1]);
        };
        auto norm_tile = [&](int gi, int m, uint32_t (&t)[8]) { scale(gi, m, 1.f); pack_b(gi, m, t); };
        auto pack_h = [&](int gi, int m, uint32_t (&t)[8]) {
#pragma unroll
          for (int i = 0; i < 8; i++) t[i] = pack2h(acc[m][16 * gi + 2 * i], acc[m][16 * gi + 2 * i + 1]);
        };
        uint32_t q[2][2][8], qn[2][2];
        const uint32_t srow = (lane & 7) + ((lane >> 3) & 1) * 8;
        const uint32_t row0 = wg * 128 + w * 16;
        auto put_kv = [&](int h, int v, int m, const uint32_t (&t)[8]) {
          const uint32_t base = sb + ((l & 1) ? (h ? 0 : T0) + v * 16384 : (2 * h + v) * ASC + 1024) + (row0 + m * 64) * 64;
          if (!v) {
#pragma unroll
            for (int jj = 0; jj < 2; jj++) stsm4(base + srow * 64 + (((2 * jj + (lane >> 4)) ^ ((srow >> 1) & 3)) << 4), t[4 * jj], t[4 * jj + 1], t[4 * jj + 2], t[4 * jj + 3]);
          } else {
            const uint32_t ad = base + g * 64 + ((qd ^ (g >> 1)) << 4);
            sts128(ad, t[0], t[2], t[4], t[6]); sts128(ad + 512, t[1], t[3], t[5], t[7]);
          }
        };
        auto send_halo = [&](int h, int v, const uint32_t (&t)[8]) {
          unsigned long long* hp = g_halo + ((size_t)(l >> 1) * 128 + b) * 1024 + h * 512 + v * 256 + lane;
#pragma unroll
          for (int i = 0; i < 8; i++) st_tagged(hp + i * 32, t[i], ep1);
        };
        auto put_kn = [&](int h, int m, uint32_t kn) {
          if (lane == 0) g_kn[((l >> 1) * 128 + bn * 8 + bm) * 32 + 16 * h + 8 * m + wg * 4 + w] = __uint_as_float(kn);
        };
        auto conv_tile1 = [&](int h) {
          uint32_t t[8], tv[8], kn = NOT_F16;
          norm_tile(4 + h, 1, tv);
          put_kv(h, 1, 1, tv);
          scale(2 + h, 1, 1.f);
          part(2 + h, 0, 2, 4);
          if (l & 1) {
            float n[2] = {0.f, 0.f};
#pragma unroll
            for (int i = 0; i < 16; i++) n[(i >> 1) & 1] = fmaf(acc[1][32 + 16 * h + i], acc[1][32 + 16 * h + i], n[(i >> 1) & 1]);
            const float a = ((qd & 1) ? n[1] : n[0]) + __shfl_xor_sync(~0u, (qd & 1) ? n[0] : n[1], 1);
            scale(h, 1, QSCALE / 128.f);
            kn = f16_class(__reduce_max_sync(~0u, __float_as_uint(a + __shfl_xor_sync(~0u, a, 2))), K_LO);
            put_kn(h, 1, kn);
          } else scale(h, 1, 1.f);
          if (kn == NOT_F16) pack_b(2 + h, 1, t); else pack_h(2 + h, 1, t);
          put_kv(h, 0, 1, t);
          if (!(l & 1) && row0 == 176 && bm < 7) { send_halo(h, 0, t); send_halo(h, 1, tv); }
        };
        mbar_wait(sb + B_QE + 8, 1);
        wg_wait<1>();
        fence_regs(acc[1]);
        conv_tile1(0);
        part(3, 0, 0, 2);
        if (l & 1) { fence_async_smem(); bar_arrive(NB_ST, 288); }
        conv_tile1(1);
        wg_wait<2>();
        if (w == 0) e_arrive_both(sb + B_QE + 16);
        wg_wait<0>();
        fence_regs(acc[0]);
        if (w == 0) e_arrive_both(sb + B_QE + 24);
        bf16* const op0 = [&] { IDS(); return g_os + (size_t)(bm * 256 + row0 + (lane >> 2)) * 1024 + bn * 32 + (lane & 3) * 8; }();
        auto put_o = [&](int h, int m, const float (&o)[16], float i0, float i1) {
          bf16* op = op0 + m * 65536 + h * 512;
          const uint4 a = make_uint4(pack2(o[0] * i0, o[1] * i0), pack2(o[4] * i0, o[5] * i0), pack2(o[8] * i0, o[9] * i0), pack2(o[12] * i0, o[13] * i0));
          const uint4 c = make_uint4(pack2(o[2] * i1, o[3] * i1), pack2(o[6] * i1, o[7] * i1), pack2(o[10] * i1, o[11] * i1), pack2(o[14] * i1, o[15] * i1));
          *(uint4*)op = a; *(uint4*)(op + 8 * 1024) = c;
          const uint32_t hi = __vimax3_u16x2(__vimax3_u16x2(a.x, a.y, a.z), __vimax3_u16x2(a.w, c.x, c.y), __vmaxu2(c.z, c.w));
          const uint32_t lo = __vimax3_s16x2(__vimax3_s16x2(a.x, a.y, a.z), __vimax3_s16x2(a.w, c.x, c.y), __vmaxs2(c.z, c.w));
          return __vmaxu2(hi & 0x7FFF7FFFu, lo & 0x7FFF7FFFu);
        };
        if (!(l & 1)) {
          auto conv_kv = [&](int h) {
            uint32_t t[8];
            norm_tile(2 + h, 0, t); put_kv(h, 0, 0, t);
            norm_tile(4 + h, 0, t); put_kv(h, 1, 0, t);
          };
          conv_kv(0);
          norm_tile(0, 0, q[0][0]); pack_b(0, 1, q[0][1]);
          bar_sync(NB_SC, 256);
          const bool e = g & 1, sel = 2 * qd + (g & 1) >= g + 2, first = bm == 0 && row0 == 0;
          const uint32_t pm_a = e ? 0x1044 : 0x4410, pm_b = e ? 0x3244 : 0x4432, pm_lo = sel ? pm_b : 0x4444, pm_hi = sel ? 0x4444 : pm_b;
          const uint32_t ka = sb + (row0 + (lane & 7)) * 64 + (((lane >> 3) ^ ((lane >> 1) & 3)) << 4);
          const uint32_t va0 = sb + ASC + (row0 + srow) * 64 + (((lane >> 4) ^ ((lane >> 1) & 3)) << 4);
#pragma unroll 1
          for (int h = 0; h < 2; h++) {
            if (row0 == 0) bar_sync(NB_HALO + h, 64);
            float s[2][4][4];
            uint32_t vf[2][4][4], pf[2][2][4];
#pragma unroll
            for (int m = 0; m < 2; m++)
#pragma unroll
              for (int nt = 0; nt < 4; nt++) {
                uint32_t kf[4];
                ldsm4(ka + h * (2 * ASC) + (m * 64 + 8 * nt) * 64, kf);
                s[m][nt][0] = s[m][nt][1] = s[m][nt][2] = s[m][nt][3] = 0.f;
                mma16816(s[m][nt], q[0][m][0], q[0][m][1], q[0][m][2], q[0][m][3], kf[0], kf[1]);
                mma16816(s[m][nt], q[0][m][4], q[0][m][5], q[0][m][6], q[0][m][7], kf[2], kf[3]);
              }
#pragma unroll
            for (int m = 0; m < 2; m++)
#pragma unroll
              for (int i = 0; i < 4; i++) {
                ldsm4t(((va0 + h * (2 * ASC)) ^ (32 * (i & 1))) + (m * 64 + 16 * (i >> 1)) * 64, vf[m][i]);
              }
            float va[4], vb[4], mx[4];
            uint32_t ua[2], ub[2], um[2];
#pragma unroll
            for (int m = 0; m < 2; m++) {
              float a[2], c[2];
#pragma unroll
              for (int hh = 0; hh < 2; hh++) {
                a[hh] = e ? s[m][hh + 1][2 * hh + 1] : s[m][hh + 1][2 * hh];
                const float lo = e ? s[m][hh][2 * hh + 1] : s[m][hh][2 * hh], hi = e ? s[m][hh + 2][2 * hh + 1] : s[m][hh + 2][2 * hh];
                c[hh] = sel ? lo : hi;
              }
              ua[m] = scale_bf2(pack2(a[0], a[1])); ub[m] = scale_bf2(pack2(c[0], c[1]));
              if (m == 0) { ua[0] = first ? (ua[0] & 0xFFFF0000u) | 0xFF80u : ua[0]; ub[0] = first && sel ? 0xFF80FF80u : ub[0]; }
              um[m] = max_bf2(ua[m], ub[m]);
            }
#pragma unroll
            for (int m = 0; m < 2; m++) um[m] = max_bf2(um[m], __shfl_xor_sync(~0u, um[m], 1));
#pragma unroll
            for (int m = 0; m < 2; m++) um[m] = max_bf2(um[m], __shfl_xor_sync(~0u, um[m], 2));
#pragma unroll
            for (int i = 0; i < 4; i++) {
              const int m = i >> 1;
              const float top = (i & 1) ? bf_hi(um[m]) : bf_lo(um[m]);
              va[i] = ex2((((i & 1) ? bf_hi(ua[m]) : bf_lo(ua[m])) - top) * 1.4426950408889634f);
              vb[i] = ex2((((i & 1) ? bf_hi(ub[m]) : bf_lo(ub[m])) - top) * 1.4426950408889634f);
              mx[i] = va[i] + vb[i];
            }
#pragma unroll
            for (int i = 0; i < 4; i++) mx[i] += __shfl_xor_sync(~0u, mx[i], 1);
#pragma unroll
            for (int i = 0; i < 4; i++) mx[i] += __shfl_xor_sync(~0u, mx[i], 2);
#pragma unroll
            for (int i = 0; i < 4; i++) {
              const int m = i >> 1, hh = i & 1;
              const float inv = rcp(mx[i]);
              const uint32_t t = pack2(va[i] * inv, vb[i] * inv);
              pf[m][hh][hh + 1] = __byte_perm(t, 0, pm_a); pf[m][hh][hh] = __byte_perm(t, 0, pm_lo); pf[m][hh][hh + 2] = __byte_perm(t, 0, pm_hi); pf[m][hh][3 - 3 * hh] = t & zero;
            }
#pragma unroll
            for (int m = 0; m < 2; m++) {
              float o[4][4];
#pragma unroll
              for (int j = 0; j < 4; j++) o[j][0] = o[j][1] = o[j][2] = o[j][3] = 0.f;
#pragma unroll
              for (int i = 0; i < 4; i++) {
                const int kk = i >> 1, jj = 2 * (i & 1);
                mma16816(o[jj], pf[m][0][2 * kk], pf[m][1][2 * kk], pf[m][0][2 * kk + 1], pf[m][1][2 * kk + 1], vf[m][i][0], vf[m][i][1]);
                mma16816(o[jj + 1], pf[m][0][2 * kk], pf[m][1][2 * kk], pf[m][0][2 * kk + 1], pf[m][1][2 * kk + 1], vf[m][i][2], vf[m][i][3]);
              }
              const float of[16] = {o[0][0], o[0][1], o[0][2], o[0][3], o[1][0], o[1][1], o[1][2], o[1][3], o[2][0], o[2][1], o[2][2], o[2][3], o[3][0], o[3][1], o[3][2], o[3][3]};
              put_o(h, m, of, 1.f, 1.f);
            }
            bar_arrive(NB_SIG + 2 * h + wg, 160);
            if (h == 0) {
              conv_kv(1);
              norm_tile(1, 0, q[0][0]); pack_b(1, 1, q[0][1]);
              bar_sync(NB_SC, 256);
            }
          }
        } else {
          auto conv_h = [&](int gi, int m, uint32_t (&t)[8]) {
            pack_h(gi, m, t);
            float d0[4] = {0.f, 0.f, 0.f, 0.f}, d1[4] = {0.f, 0.f, 0.f, 0.f};
            if (gi == 2) {
              mma16816h(d0, t[0], t[1], t[2], t[3], t[0], t[2]); mma16816h(d1, t[0], t[1], t[2], t[3], t[1], t[3]);
              mma16816h(d0, t[4], t[5], t[6], t[7], t[4], t[6]); mma16816h(d1, t[4], t[5], t[6], t[7], t[5], t[7]);
            } else {
#pragma unroll
              for (int i = 0; i < 8; i += 2) { mma1688h(d0, t[i], t[i + 1], t[i]); mma1688h(d1, t[i], t[i + 1], t[i + 1]); }
            }
            return f16_class(__reduce_max_sync(~0u, max(max(__float_as_int(d0[0]), __float_as_int(d0[1])), max(__float_as_int(d1[2]), __float_as_int(d1[3])))), K_LO);
          };
          uint32_t tk[8], tv[8];
          scale(2, 0, 1.f);
          uint32_t kn = conv_h(2, 0, tk);
          norm_tile(4, 0, tv);
          put_kv(0, 1, 0, tv);
          put_kn(0, 0, kn);
          if (kn == NOT_F16) pack_b(2, 0, tk);
          put_kv(0, 0, 0, tk);
          fence_async_smem();
          bar_arrive(NB_KV, 288);
          mbar_wait(sb + B_QF + 24, 1);
          scale(3, 0, 1.f); scale(0, 0, QSCALE); scale(1, 0, QSCALE);
          kn = conv_h(3, 0, tk);
#pragma unroll
          for (int i = 0; i < 4; i++) qn[i >> 1][i & 1] = conv_h(i >> 1, i & 1, q[i >> 1][i & 1]);
          norm_tile(5, 0, tv);
          if (max(max(max(qn[0][0], qn[0][1]), max(qn[1][0], qn[1][1])), kn) == NOT_F16) {
#pragma unroll
            for (int i = 0; i < 4; i++) if (qn[i >> 1][i & 1] == NOT_F16) pack_b(i >> 1, i & 1, q[i >> 1][i & 1]);
            if (kn == NOT_F16) pack_b(3, 0, tk);
          }
          fence_regs(tv);
          const bool elected = w == 0 && lane == 0;
          const uint64_t kd0 = mkdesc(sb + T0, 16, 512, 2);
          const uint64_t vd0 = mkdesc(sb + T0 + 16384, ONES - (T0 + 16384), 512, 2);
          constexpr uint64_t VSTEP = 64 - (64ull << 16);
          float o[2][20], SA[2][16];
          uint32_t SB[2][8], PA[4], PB[4];
          auto qk = [&](int b, int k, uint64_t d, int h = 0) {
            wgmma_m64n32k16_rs_nb_h(SA[b], q[h][0][4 * k], q[h][0][4 * k + 1], q[h][0][4 * k + 2], q[h][0][4 * k + 3], d + 2 * k, k ? 1 : zero);
            wgmma_m64n32k16_rs_nb_hh(SB[b], q[h][1][4 * k], q[h][1][4 * k + 1], q[h][1][4 * k + 2], q[h][1][4 * k + 3], d + 2 * k, k ? 1 : zero);
          };
          auto pv = [&](int m, const uint32_t (&Px)[4], uint64_t vd, int keep = 1) { wgmma_m64n40k16_rs_tb(o[m], Px[0], Px[1], Px[2], Px[3], vd, keep); };
          mbar_wait(sb + B_TF, 0);
#pragma unroll
          for (int i = 0; i < 4; i++) PA[i] = PB[i] = zero;
          wg_fence();
          wgmma_m64n40k16_rs_tb_z(o[0], PA[0], PA[1], PA[2], PA[3], vd0, 0); wgmma_m64n40k16_rs_tb_z(o[1], PB[0], PB[1], PB[2], PB[3], vd0 + VSTEP, 0);
#pragma unroll
          for (int b = 1; b >= 0; b--) {
            wgmma_m64n32k16_rs_nb_z_h(SA[b], q[0][0][0], q[0][0][1], q[0][0][2], q[0][0][3], kd0 + 128 * b, 0);
            wgmma_m64n32k16_rs_nb_z_hh(SB[b], q[0][1][0], q[0][1][1], q[0][1][2], q[0][1][3], kd0 + 128 * b, 0);
          }
          qk(0, 1, kd0); wg_commit();
          put_kv(1, 1, 0, tv); put_kv(1, 0, 0, tk); put_kn(1, 0, kn);
          fence_async_smem();
          bar_arrive(NB_KV + 12, 288);
          wg_wait<0>();
          fence_regs(SA[0]); fence_regs(SB[0]); fence_regs(SA[1]); fence_regs(SB[1]); fence_regs(o[0]); fence_regs(o[1]);
#pragma unroll 1
          for (int pass = 0; pass < 2; pass++) {
            uint32_t kc = (uint32_t)kd0, vc = (uint32_t)vd0, vp = (uint32_t)(vd0 + VSTEP);
#pragma unroll 1
            for (int it = 1; it <= 8; it++) {
              const uint32_t sn = it & 3, par = (it >> 2) & 1, kn = it < 8 ? (uint32_t)kd0 + sn * 2048 : kc;
              const uint64_t hi = kd0 & 0xFFFFFFFF00000000ull, kd = hi | kc, vd = hi | vc, kdn = hi | kn, vdp = hi | vp;
              kc = kn; vp = vc + (uint32_t)(16 * VSTEP); vc = (uint32_t)vd0 + sn * 32 * (uint32_t)VSTEP;
              bool landed = false;
#pragma unroll
              for (int r = 0; r < 16; r++) {
                const int c = r >> 1, ro = r & 1;
                if (r == 14 && !landed) mbar_wait(sb + B_TF + 8 * sn, par);
                wg_fence();
                qk(~c & 1, ro, c < 7 ? kd + (c + 1) * 128 : kdn);
                if (ro) wg_commit();
                const uint64_t vx = (r ? vd : vdp) + (r - 1) * VSTEP;
                const int keep = r ? 1 : it - 1;
                pv(0, PA, vx, keep); pv(1, PB, vx, keep);
                wg_commit();
                if (r == 12) landed = mbar_test(sb + B_TF + 8 * sn, par) || it == 8;
#pragma unroll
                for (int i = 0; i < 4; i++) {
                  PA[i] = pack2(ex2(SA[c & 1][8 * ro + 2 * i]), ex2(SA[c & 1][8 * ro + 2 * i + 1]));
                  PB[i] = exp2_h2(SB[c & 1][4 * ro + i]);
                }
                if (r == 15) wg_wait<0>(); else if (ro) wg_wait<1>();
                if (ro) { fence_regs(SA[~c & 1]); fence_regs(SB[~c & 1]); }
                if (r == 2 && elected && it > 1) mbar_arrive(sb + B_TE + 8 * ((sn + 2) & 3));
              }
            }
            int badm = 0;
            if (pass == 0) mbar_wait(sb + B_TF, 0);
            wg_fence();
            pv(0, PA, vd0 + 111 * VSTEP); pv(1, PB, vd0 + 111 * VSTEP); wg_commit();
            qk(0, 0, kd0, 1); qk(0, 1, kd0, 1); wg_commit();
            if (pass == 0) bar_sync(NB_KN + wg, 160);
            const float kmax = *(volatile float*)(smem + KMAX + 4 * pass);
            wg_wait<1>(); fence_regs(o[0]); fence_regs(o[1]);
            if (w == 0) e_arrive(sb + B_TE + 8 * 3);
#pragma unroll
            for (int m = 0; m < 2; m++) {
              const float of[16] = {o[m][0], o[m][1], o[m][2], o[m][3], o[m][4], o[m][5], o[m][6], o[m][7], o[m][8], o[m][9], o[m][10], o[m][11], o[m][12], o[m][13], o[m][14], o[m][15]};
              const uint32_t chk = put_o(pass, m, of, rcp(o[m][16]), rcp(o[m][18]));
              const bool bad = !(__uint_as_float(qn[0][m]) * kmax <= (m ? 0.875f * 0.875f : 112.f * 112.f)) || !(fminf(o[m][16], o[m][18]) >= 9.3e-10f) ||
                               !(o[m][16] + o[m][18] <= 3e38f) || ((chk + 0x00800080u) & 0x80008000u);
              badm |= __any_sync(~0u, bad) << m;
            }
            wg_wait<0>(); fence_regs(SA[0]); fence_regs(SB[0]);
            if (badm) {
#pragma unroll 1
              for (int m = 0; m < 2; m++) if ((badm >> m) & 1) {
                uint32_t qq[8]; float res[20];
#pragma unroll
                for (int i = 0; i < 8; i++) { qq[i] = m ? q[0][1][i] : q[0][0][i]; if ((m ? qn[0][1] : qn[0][0]) != NOT_F16) qq[i] = h2_to_bf2(qq[i]); }
                attn_slow(qq, m ? 128.f : 1.f, 2 * (cta_id() & 15) + pass, g_kn + ((l >> 1) * 128 + (cta_id() & 15) * 8) * 32 + 16 * pass, res, lane_id());
                const float of[16] = {res[0], res[1], res[2], res[3], res[4], res[5], res[6], res[7], res[8], res[9], res[10], res[11], res[12], res[13], res[14], res[15]};
                put_o(pass, m, of, rcp(res[16]), rcp(res[18]));
              }
            }
            bar_arrive(NB_SIG + 2 * pass + wg, 160);
            qn[0][0] = qn[1][0]; qn[0][1] = qn[1][1];
#pragma unroll
            for (int m = 0; m < 2; m++)
#pragma unroll
              for (int i = 0; i < 8; i++) q[0][m][i] = q[1][m][i];
#pragma unroll
            for (int i = 0; i < 4; i++) PA[i] = PB[i] = zero;
          }
        }
      }
      {
        float acc[64];
#pragma unroll
        for (int i = 0; i < 64; i++) acc[i] = 0.f;
        fence_regs(acc);
        uint32_t s = 0, lap = 0;
#pragma unroll 1
        for (int kt = 0; kt < 16; kt++) {
          mbar_wait(sb + B_PF + 8 * s, ((s < 4 ? l : 0) + lap) & 1);
          const uint64_t da = mkdesc(sb + pslot_a(s, l) + wg * 8192, 16, 1024, 1), db = mkdesc(sb + pslot_b(s, l), 8192, 1024, 1);
          wg_fence();
#pragma unroll
          for (int k = 0; k < 4; k++) wgmma_m64n128k16_ss_tb(acc, da + k * 2, db + k * 128, 1);
          wg_commit();
          wg_wait<1>();
          if (kt > 0 && w == 0) e_arrive_both(sb + B_PE + 8 * (s ? s - 1 : 5));
          if (++s == 6) { s = 0; lap++; }
        }
        IDS();
        const int g = lane >> 2, qd = lane & 3;
        const int r0 = wg * 64 + w * 16;
        const uint32_t r = r0 + (lane & 7) + ((lane >> 3) & 1) * 8;
        uint32_t x[8][4];
        mbar_wait(sb + B_RF, l & 1);
#pragma unroll
        for (int jj = 0; jj < 8; jj++) ldsm4(sb + ((l & 1) ? RES : 0) + (jj >> 2) * 16384 + r * 128 + ((((2 * jj + (lane >> 4)) & 7) ^ (r & 7)) << 4), x[jj]);
        wg_wait<0>();
        fence_regs(acc);
        bar_sync(NB_SC, 256);
        if (w == 0) e_arrive_both(sb + B_PE + 8 * 3);
        const CUtensorMap* mo = &prm.m[l == 3 ? M_OUT : M_XST];
#pragma unroll
        for (int jj = 0; jj < 8; jj++) {
#pragma unroll
          for (int i = 0; i < 4; i++) x[jj][i] = add_bf16x2(x[jj][i], pack2(acc[8 * jj + 2 * i], acc[8 * jj + 2 * i + 1]));
          stsm4(sb + (jj >> 2) * QSTG + po * 16384 + r * 128 + ((((2 * jj + (lane >> 4)) & 7) ^ (r & 7)) << 4), x[jj][0], x[jj][1], x[jj][2], x[jj][3]);
          if ((jj & 3) == 3) { fence_async_smem(); __syncwarp(); tma_st(mo, pn * 128 + (jj >> 2) * 64, pm * 128 + r0, sb + (jj >> 2) * QSTG + po * 16384 + r0 * 128); }
        }
        bulk_commit();
        if (l < 3) {
          bar_arrive(NB_X, 288);
          float s1[4] = {0.f, 0.f, 0.f, 0.f}, s2[4][4];
#pragma unroll
          for (int i = 0; i < 16; i++) s2[i >> 2][i & 3] = 0.f;
#pragma unroll
          for (int jj = 0; jj < 8; jj++) {
            mma16816(s1, x[jj][0], x[jj][1], x[jj][2], x[jj][3], 0x3f803f80u, 0x3f803f80u);
#pragma unroll
            for (int i = 0; i < 4; i++) mma1688(s2[i], x[jj][i & 2], x[jj][i | 1], x[jj][i]);
          }
          if (qd == (g >> 1)) {
            float2* sp = g_stats + pn * 2048 + pm * 128 + r0 + g;
            sp[0] = make_float2(s1[0], (g & 1) ? s2[0][1] + s2[2][1] : s2[0][0] + s2[2][0]);
            sp[8] = make_float2(s1[2], (g & 1) ? s2[1][3] + s2[3][3] : s2[1][2] + s2[3][2]);
          }
        }
        bulk_wait_n<0>();
        if (l < 3) bar_arrive(NB_X0, 352);
      }
    }
  }
  asm volatile("barrier.cluster.arrive.relaxed.aligned;\nbarrier.cluster.wait.aligned;" ::: "memory");
}

typedef CUresult (*EncodeFn)(CUtensorMap*, CUtensorMapDataType, cuuint32_t, void*, const cuuint64_t*, const cuuint64_t*, const cuuint32_t*,
                             const cuuint32_t*, CUtensorMapInterleave, CUtensorMapSwizzle, CUtensorMapL2promotion, CUtensorMapFloatOOBfill);

static void make_map(EncodeFn fn, CUtensorMap* m, const void* ptr, int rank, const uint64_t* dims, const uint64_t* strides, const uint32_t* box, CUtensorMapSwizzle sw) {
  cuuint64_t d[5], st[4];
  cuuint32_t bx[5], es[5];
  for (int i = 0; i < rank; i++) { d[i] = dims[i]; bx[i] = box[i]; es[i] = 1; if (i) st[i - 1] = strides[i - 1] * 2; }
  fn(m, CU_TENSOR_MAP_DATA_TYPE_BFLOAT16, rank, (void*)ptr, d, st, bx, es, CU_TENSOR_MAP_INTERLEAVE_NONE, sw,
     CU_TENSOR_MAP_L2_PROMOTION_L2_128B, CU_TENSOR_MAP_FLOAT_OOB_FILL_NONE);
}
static void map2(EncodeFn fn, CUtensorMap* m, const void* ptr, uint64_t inner, uint64_t outer, uint32_t bi, uint32_t bo, CUtensorMapSwizzle sw) {
  const uint64_t d[2] = {inner, outer}, st[1] = {inner};
  const uint32_t bx[2] = {bi, bo};
  make_map(fn, m, ptr, 2, d, st, bx, sw);
}

extern "C" void kernel_launch(void* const* d_in, const int* in_sizes, int n_in, void* d_out, int out_size) {
  (void)in_sizes; (void)n_in; (void)out_size;
  static EncodeFn enc = nullptr;
  static void *xs, *os, *kk, *vv, *ep;
  if (!enc) {
    void* p = nullptr;
    cudaDriverEntryPointQueryResult qr;
    cudaGetDriverEntryPoint("cuTensorMapEncodeTiled", &p, cudaEnableDefault, &qr);
    enc = (EncodeFn)p;
    cudaGetSymbolAddress(&xs, g_xs); cudaGetSymbolAddress(&os, g_os); cudaGetSymbolAddress(&kk, g_k); cudaGetSymbolAddress(&vv, g_v); cudaGetSymbolAddress(&ep, g_epoch);
    cudaFuncSetAttribute(fused_kernel, cudaFuncAttributeMaxDynamicSharedMemorySize, SMEM_BYTES);
  }
  Params prm;
  const CUtensorMapSwizzle S128 = CU_TENSOR_MAP_SWIZZLE_128B, S64 = CU_TENSOR_MAP_SWIZZLE_64B;
  map2(enc, &prm.m[M_X0A], d_in[0], 1024, 2048, 64, 256, S128);
  map2(enc, &prm.m[M_XSA], xs, 1024, 2048, 64, 256, S128);
  for (int t = 0; t < 2; t++) {
    const uint64_t d3[3] = {1024, 1024, 3}, s3[2] = {3072, 1024};
    const uint32_t b3[3] = {64, 64, 3};
    make_map(enc, &prm.m[M_WQA + t], d_in[1 + 3 * t], 3, d3, s3, b3, S128);
    const uint64_t d5[5] = {64, 32, 2, 16, 16}, s5[4] = {1024, 32 * 1024, 64 * 1024, 64};
    const uint32_t b5[5] = {64, 32, 1, 2, 2};
    make_map(enc, &prm.m[M_WOA + t], d_in[2 + 3 * t], 5, d5, s5, b5, S128);
    const uint64_t dr[3] = {64, 2048, 16}, sr[2] = {1024, 64};
    const uint32_t br[3] = {64, 128, 2};
    make_map(enc, &prm.m[M_X0R + t], t ? xs : d_in[0], 3, dr, sr, br, S128);
  }
  map2(enc, &prm.m[M_OS], os, 1024, 2048, 64, 64, S128);
  map2(enc, &prm.m[M_K], kk, 32, 65536, 32, 256, S64);
  map2(enc, &prm.m[M_V], vv, 32, 65536, 32, 256, S64);
  map2(enc, &prm.m[M_K4], kk, 32, 65536, 32, 64, S64);
  map2(enc, &prm.m[M_V4], vv, 32, 65536, 32, 64, S64);
  map2(enc, &prm.m[M_XSO], xs, 1024, 2048, 64, 128, S128);
  map2(enc, &prm.m[M_X0H], d_in[0], 1024, 2048, 64, 128, S128);
  map2(enc, &prm.m[M_XST], xs, 1024, 2048, 64, 16, S128);
  map2(enc, &prm.m[M_OUT], d_out, 1024, 2048, 64, 16, S128);
  prm.x0 = (const bf16*)d_in[0];
  prm.wq[0] = (const bf16*)d_in[1]; prm.wq[1] = (const bf16*)d_in[4];
  prm.wo[0] = (const bf16*)d_in[2]; prm.wo[1] = (const bf16*)d_in[5];
  prm.epoch = (uint32_t*)ep;
  prm.zero = 0;
  for (int i = 0; i < 128; i++) prm.map[i] = remap(i);
  fused_kernel<<<128, 384, SMEM_BYTES>>>(prm);
}
```

```cpp
#include <cuda_runtime.h>
#include <cuda_bf16.h>
#include <cuda.h>
#include <stdint.h>

typedef __nv_bfloat16 bf16;

__device__ __forceinline__ void wgmma_m64n192k16_ss_tb(float (&d)[96], uint64_t da, uint64_t db, int scale_d) {
  asm volatile("{\n.reg .pred p;\nsetp.ne.b32 p, %98, 0;\n"
    "wgmma.mma_async.sync.aligned.m64n192k16.f32.bf16.bf16 "
    "{%0, %1, %2, %3, %4, %5, %6, %7, %8, %9, %10, %11, %12, %13, %14, %15, "
    "%16, %17, %18, %19, %20, %21, %22, %23, %24, %25, %26, %27, %28, %29, %30, %31, "
    "%32, %33, %34, %35, %36, %37, %38, %39, %40, %41, %42, %43, %44, %45, %46, %47, "
    "%48, %49, %50, %51, %52, %53, %54, %55, %56, %57, %58, %59, %60, %61, %62, %63, "
    "%64, %65, %66, %67, %68, %69, %70, %71, %72, %73, %74, %75, %76, %77, %78, %79, "
    "%80, %81, %82, %83, %84, %85, %86, %87, %88, %89, %90, %91, %92, %93, %94, %95}, "
    "%96, %97, p, 1, 1, 0, 1;\n}\n"
    : "+f"(d[0]), "+f"(d[1]), "+f"(d[2]), "+f"(d[3]), "+f"(d[4]), "+f"(d[5]), "+f"(d[6]), "+f"(d[7]),
      "+f"(d[8]), "+f"(d[9]), "+f"(d[10]), "+f"(d[11]), "+f"(d[12]), "+f"(d[13]), "+f"(d[14]), "+f"(d[15]),
      "+f"(d[16]), "+f"(d[17]), "+f"(d[18]), "+f"(d[19]), "+f"(d[20]), "+f"(d[21]), "+f"(d[22]), "+f"(d[23]),
      "+f"(d[24]), "+f"(d[25]), "+f"(d[26]), "+f"(d[27]), "+f"(d[28]), "+f"(d[29]), "+f"(d[30]), "+f"(d[31]),
      "+f"(d[32]), "+f"(d[33]), "+f"(d[34]), "+f"(d[35]), "+f"(d[36]), "+f"(d[37]), "+f"(d[38]), "+f"(d[39]),
      "+f"(d[40]), "+f"(d[41]), "+f"(d[42]), "+f"(d[43]), "+f"(d[44]), "+f"(d[45]), "+f"(d[46]), "+f"(d[47]),
      "+f"(d[48]), "+f"(d[49]), "+f"(d[50]), "+f"(d[51]), "+f"(d[52]), "+f"(d[53]), "+f"(d[54]), "+f"(d[55]),
      "+f"(d[56]), "+f"(d[57]), "+f"(d[58]), "+f"(d[59]), "+f"(d[60]), "+f"(d[61]), "+f"(d[62]), "+f"(d[63]),
      "+f"(d[64]), "+f"(d[65]), "+f"(d[66]), "+f"(d[67]), "+f"(d[68]), "+f"(d[69]), "+f"(d[70]), "+f"(d[71]),
      "+f"(d[72]), "+f"(d[73]), "+f"(d[74]), "+f"(d[75]), "+f"(d[76]), "+f"(d[77]), "+f"(d[78]), "+f"(d[79]),
      "+f"(d[80]), "+f"(d[81]), "+f"(d[82]), "+f"(d[83]), "+f"(d[84]), "+f"(d[85]), "+f"(d[86]), "+f"(d[87]),
      "+f"(d[88]), "+f"(d[89]), "+f"(d[90]), "+f"(d[91]), "+f"(d[92]), "+f"(d[93]), "+f"(d[94]), "+f"(d[95])
    : "l"(da), "l"(db), "r"(scale_d));
}

__device__ __forceinline__ void wgmma_m64n128k16_ss_tb(float (&d)[64], uint64_t da, uint64_t db, int scale_d) {
  asm volatile("{\n.reg .pred p;\nsetp.ne.b32 p, %66, 0;\n"
    "wgmma.mma_async.sync.aligned.m64n128k16.f32.bf16.bf16 "
    "{%0, %1, %2, %3, %4, %5, %6, %7, %8, %9, %10, %11, %12, %13, %14, %15, "
    "%16, %17, %18, %19, %20, %21, %22, %23, %24, %25, %26, %27, %28, %29, %30, %31, "
    "%32, %33, %34, %35, %36, %37, %38, %39, %40, %41, %42, %43, %44, %45, %46, %47, "
    "%48, %49, %50, %51, %52, %53, %54, %55, %56, %57, %58, %59, %60, %61, %62, %63}, "
    "%64, %65, p, 1, 1, 0, 1;\n}\n"
    : "+f"(d[0]), "+f"(d[1]), "+f"(d[2]), "+f"(d[3]), "+f"(d[4]), "+f"(d[5]), "+f"(d[6]), "+f"(d[7]),
      "+f"(d[8]), "+f"(d[9]), "+f"(d[10]), "+f"(d[11]), "+f"(d[12]), "+f"(d[13]), "+f"(d[14]), "+f"(d[15]),
      "+f"(d[16]), "+f"(d[17]), "+f"(d[18]), "+f"(d[19]), "+f"(d[20]), "+f"(d[21]), "+f"(d[22]), "+f"(d[23]),
      "+f"(d[24]), "+f"(d[25]), "+f"(d[26]), "+f"(d[27]), "+f"(d[28]), "+f"(d[29]), "+f"(d[30]), "+f"(d[31]),
      "+f"(d[32]), "+f"(d[33]), "+f"(d[34]), "+f"(d[35]), "+f"(d[36]), "+f"(d[37]), "+f"(d[38]), "+f"(d[39]),
      "+f"(d[40]), "+f"(d[41]), "+f"(d[42]), "+f"(d[43]), "+f"(d[44]), "+f"(d[45]), "+f"(d[46]), "+f"(d[47]),
      "+f"(d[48]), "+f"(d[49]), "+f"(d[50]), "+f"(d[51]), "+f"(d[52]), "+f"(d[53]), "+f"(d[54]), "+f"(d[55]),
      "+f"(d[56]), "+f"(d[57]), "+f"(d[58]), "+f"(d[59]), "+f"(d[60]), "+f"(d[61]), "+f"(d[62]), "+f"(d[63])
    : "l"(da), "l"(db), "r"(scale_d));
}

__device__ __forceinline__ void wgmma_m64n32k16_rs_nb_h(float (&d)[16], uint32_t a0, uint32_t a1, uint32_t a2, uint32_t a3, uint64_t db, int scale_d) {
  asm volatile("{\n.reg .pred p;\nsetp.ne.b32 p, %21, 0;\n"
    "wgmma.mma_async.sync.aligned.m64n32k16.f32.f16.f16 "
    "{%0, %1, %2, %3, %4, %5, %6, %7, %8, %9, %10, %11, %12, %13, %14, %15}, "
    "{%16, %17, %18, %19}, %20, p, 1, 1, 0;\n}\n"
    : "+f"(d[0]), "+f"(d[1]), "+f"(d[2]), "+f"(d[3]), "+f"(d[4]), "+f"(d[5]), "+f"(d[6]), "+f"(d[7]),
      "+f"(d[8]), "+f"(d[9]), "+f"(d[10]), "+f"(d[11]), "+f"(d[12]), "+f"(d[13]), "+f"(d[14]), "+f"(d[15])
    : "r"(a0), "r"(a1), "r"(a2), "r"(a3), "l"(db), "r"(scale_d));
}

__device__ __forceinline__ void wgmma_m64n32k16_rs_nb_hh(uint32_t (&d)[8], uint32_t a0, uint32_t a1, uint32_t a2, uint32_t a3, uint64_t db, int scale_d) {
  asm volatile("{\n.reg .pred p;\nsetp.ne.b32 p, %13, 0;\n"
    "wgmma.mma_async.sync.aligned.m64n32k16.f16.f16.f16 "
    "{%0, %1, %2, %3, %4, %5, %6, %7}, "
    "{%8, %9, %10, %11}, %12, p, 1, 1, 0;\n}\n"
    : "+r"(d[0]), "+r"(d[1]), "+r"(d[2]), "+r"(d[3]), "+r"(d[4]), "+r"(d[5]), "+r"(d[6]), "+r"(d[7])
    : "r"(a0), "r"(a1), "r"(a2), "r"(a3), "l"(db), "r"(scale_d));
}

__device__ __forceinline__ void wgmma_m64n40k16_rs_tb(float (&d)[20], uint32_t a0, uint32_t a1, uint32_t a2, uint32_t a3, uint64_t db, int scale_d) {
  asm volatile("{\n.reg .pred p;\nsetp.ne.b32 p, %25, 0;\n"
    "wgmma.mma_async.sync.aligned.m64n40k16.f32.bf16.bf16 "
    "{%0, %1, %2, %3, %4, %5, %6, %7, %8, %9, %10, %11, %12, %13, %14, %15, "
    "%16, %17, %18, %19}, "
    "{%20, %21, %22, %23}, %24, p, 1, 1, 1;\n}\n"
    : "+f"(d[0]), "+f"(d[1]), "+f"(d[2]), "+f"(d[3]), "+f"(d[4]), "+f"(d[5]), "+f"(d[6]), "+f"(d[7]),
      "+f"(d[8]), "+f"(d[9]), "+f"(d[10]), "+f"(d[11]), "+f"(d[12]), "+f"(d[13]), "+f"(d[14]), "+f"(d[15]),
      "+f"(d[16]), "+f"(d[17]), "+f"(d[18]), "+f"(d[19])
    : "r"(a0), "r"(a1), "r"(a2), "r"(a3), "l"(db), "r"(scale_d));
}

__device__ __forceinline__ void wgmma_m64n40k16_rs_tb_z(float (&d)[20], uint32_t a0, uint32_t a1, uint32_t a2, uint32_t a3, uint64_t db, int scale_d) {
  asm volatile("{\n.reg .pred p;\nsetp.ne.b32 p, %25, 0;\n"
    "wgmma.mma_async.sync.aligned.m64n40k16.f32.bf16.bf16 "
    "{%0, %1, %2, %3, %4, %5, %6, %7, %8, %9, %10, %11, %12, %13, %14, %15, "
    "%16, %17, %18, %19}, "
    "{%20, %21, %22, %23}, %24, p, 1, 1, 1;\n}\n"
    : "=f"(d[0]), "=f"(d[1]), "=f"(d[2]), "=f"(d[3]), "=f"(d[4]), "=f"(d[5]), "=f"(d[6]), "=f"(d[7]),
      "=f"(d[8]), "=f"(d[9]), "=f"(d[10]), "=f"(d[11]), "=f"(d[12]), "=f"(d[13]), "=f"(d[14]), "=f"(d[15]),
      "=f"(d[16]), "=f"(d[17]), "=f"(d[18]), "=f"(d[19])
    : "r"(a0), "r"(a1), "r"(a2), "r"(a3), "l"(db), "r"(scale_d));
}

__device__ __forceinline__ void wgmma_m64n32k16_rs_nb_z_h(float (&d)[16], uint32_t a0, uint32_t a1, uint32_t a2, uint32_t a3, uint64_t db, int scale_d) {
  asm volatile("{\n.reg .pred p;\nsetp.ne.b32 p, %21, 0;\n"
    "wgmma.mma_async.sync.aligned.m64n32k16.f32.f16.f16 "
    "{%0, %1, %2, %3, %4, %5, %6, %7, %8, %9, %10, %11, %12, %13, %14, %15}, "
    "{%16, %17, %18, %19}, %20, p, 1, 1, 0;\n}\n"
    : "=f"(d[0]), "=f"(d[1]), "=f"(d[2]), "=f"(d[3]), "=f"(d[4]), "=f"(d[5]), "=f"(d[6]), "=f"(d[7]),
      "=f"(d[8]), "=f"(d[9]), "=f"(d[10]), "=f"(d[11]), "=f"(d[12]), "=f"(d[13]), "=f"(d[14]), "=f"(d[15])
    : "r"(a0), "r"(a1), "r"(a2), "r"(a3), "l"(db), "r"(scale_d));
}

__device__ __forceinline__ void wgmma_m64n32k16_rs_nb_z_hh(uint32_t (&d)[8], uint32_t a0, uint32_t a1, uint32_t a2, uint32_t a3, uint64_t db, int scale_d) {
  asm volatile("{\n.reg .pred p;\nsetp.ne.b32 p, %13, 0;\n"
    "wgmma.mma_async.sync.aligned.m64n32k16.f16.f16.f16 "
    "{%0, %1, %2, %3, %4, %5, %6, %7}, "
    "{%8, %9, %10, %11}, %12, p, 1, 1, 0;\n}\n"
    : "=r"(d[0]), "=r"(d[1]), "=r"(d[2]), "=r"(d[3]), "=r"(d[4]), "=r"(d[5]), "=r"(d[6]), "=r"(d[7])
    : "r"(a0), "r"(a1), "r"(a2), "r"(a3), "l"(db), "r"(scale_d));
}

#define DEVINL __device__ __forceinline__
DEVINL void wg_fence() { asm volatile("wgmma.fence.sync.aligned;" ::: "memory"); }
DEVINL void wg_commit() { asm volatile("wgmma.commit_group.sync.aligned;" ::: "memory"); }
template <int N> DEVINL void wg_wait() { asm volatile("wgmma.wait_group.sync.aligned %0;" ::"n"(N) : "memory"); }
DEVINL uint64_t mkdesc(uint32_t addr, uint32_t lbo, uint32_t sbo, int sw) {
  return (uint64_t)((addr & 0x3FFFF) >> 4) | ((uint64_t)(lbo >> 4) << 16) | ((uint64_t)(sbo >> 4) << 32) | ((uint64_t)sw << 62);
}
DEVINL void mbar_arrive(uint32_t bar) { asm volatile("mbarrier.arrive.shared::cta.b64 _, [%0];" ::"r"(bar) : "memory"); }
DEVINL bool mbar_try(uint32_t bar, uint32_t parity) {
  uint32_t ok;
  asm volatile("{\n.reg .pred p;\nmbarrier.try_wait.parity.shared::cta.b64 p, [%1], %2;\nselp.u32 %0, 1, 0, p;\n}" : "=r"(ok) : "r"(bar), "r"(parity) : "memory");
  return ok;
}
DEVINL bool mbar_test(uint32_t bar, uint32_t parity) {
  uint32_t ok;
  asm volatile("{\n.reg .pred p;\nmbarrier.test_wait.parity.shared::cta.b64 p, [%1], %2;\nselp.u32 %0, 1, 0, p;\n}" : "=r"(ok) : "r"(bar), "r"(parity) : "memory");
  return ok;
}
DEVINL void mbar_hint(uint32_t bar, uint32_t parity) {
#pragma unroll 1
  for (uint32_t n = 0; n < 16u; n++) if (mbar_try(bar, parity)) break;
}
DEVINL void mbar_wait(uint32_t bar, uint32_t parity) {
#pragma unroll 1
  for (uint32_t n = 0; n < 100000u; n++) if (mbar_try(bar, parity)) break;
}
DEVINL void mbar_wait_long(uint32_t bar, uint32_t parity) {
#pragma unroll 1
  for (uint32_t n = 0; n < 100000u; n++) {
    uint32_t ok;
    asm volatile("{\n.reg .pred p;\nmbarrier.try_wait.parity.shared::cta.b64 p, [%1], %2, %3;\nselp.u32 %0, 1, 0, p;\n}" : "=r"(ok) : "r"(bar), "r"(parity), "r"(4000) : "memory");
    if (ok) break;
  }
}
#define EL(txt) "{\n.reg .pred pe;\nelect.sync _|pe, 0xffffffff;\n@pe " txt "\n}"
DEVINL void e_expect_tx(uint32_t bar, uint32_t bytes) { asm volatile(EL("mbarrier.arrive.expect_tx.shared::cta.b64 _, [%0], %1;") ::"r"(bar), "r"(bytes) : "memory"); }
DEVINL void e_init(uint32_t bar, uint32_t cnt) { asm volatile(EL("mbarrier.init.shared::cta.b64 [%0], %1;") ::"r"(bar), "r"(cnt) : "memory"); }
DEVINL void e_arrive(uint32_t bar) { asm volatile(EL("mbarrier.arrive.shared::cta.b64 _, [%0];") ::"r"(bar) : "memory"); }
DEVINL void e_red(uint32_t* p) { asm volatile(EL("red.release.gpu.global.add.u32 [%0], 1;") ::"l"(p) : "memory"); }
DEVINL void e_red_relaxed(uint32_t* p) { asm volatile(EL("red.relaxed.gpu.global.add.u32 [%0], 1;") ::"l"(p) : "memory"); }
DEVINL void tma_ld(uint32_t dst, const CUtensorMap* m, int c0, int c1, uint32_t bar) {
  asm volatile(EL("cp.async.bulk.tensor.2d.shared::cluster.global.mbarrier::complete_tx::bytes [%0], [%1, {%3, %4}], [%2];")
               ::"r"(dst), "l"(m), "r"(bar), "r"(c0), "r"(c1) : "memory");
}
DEVINL void tma_ld3(uint32_t dst, const CUtensorMap* m, int c0, int c1, int c2, uint32_t bar) {
  asm volatile(EL("cp.async.bulk.tensor.3d.shared::cluster.global.mbarrier::complete_tx::bytes [%0], [%1, {%3, %4, %5}], [%2];")
               ::"r"(dst), "l"(m), "r"(bar), "r"(c0), "r"(c1), "r"(c2) : "memory");
}
DEVINL void tma_ld5(uint32_t dst, const CUtensorMap* m, int c2, int c3, int c4, uint32_t bar) {
  asm volatile(EL("cp.async.bulk.tensor.5d.shared::cluster.global.mbarrier::complete_tx::bytes [%0], [%1, {0, 0, %3, %4, %5}], [%2];")
               ::"r"(dst), "l"(m), "r"(bar), "r"(c2), "r"(c3), "r"(c4) : "memory");
}
DEVINL void tma_ld_mc(uint32_t dst, const CUtensorMap* m, int c0, int c1, uint32_t bar) {
  asm volatile(EL("cp.async.bulk.tensor.2d.shared::cluster.global.mbarrier::complete_tx::bytes.multicast::cluster [%0], [%1, {%3, %4}], [%2], %5;")
               ::"r"(dst), "l"(m), "r"(bar), "r"(c0), "r"(c1), "h"((uint16_t)3) : "memory");
}
DEVINL void e_arrive_both(uint32_t bar) {
  asm volatile("{\n.reg .pred pe;\n.reg .b32 r0, r1;\nelect.sync _|pe, 0xffffffff;\nmapa.shared::cluster.u32 r0, %0, 0;\nmapa.shared::cluster.u32 r1, %0, 1;\n"
               "@pe mbarrier.arrive.shared::cluster.b64 _, [r0];\n@pe mbarrier.arrive.shared::cluster.b64 _, [r1];\n}" ::"r"(bar) : "memory");
}
DEVINL void push_peer(uint32_t dst, uint32_t src, uint32_t bar, uint32_t peer) {
  asm volatile("{\n.reg .pred pe;\n.reg .b32 d, b;\nelect.sync _|pe, 0xffffffff;\nmapa.shared::cluster.u32 d, %0, %3;\nmapa.shared::cluster.u32 b, %2, %3;\n"
               "@pe cp.async.bulk.shared::cluster.shared::cta.mbarrier::complete_tx::bytes [d], [%1], 16384, [b];\n}" ::"r"(dst), "r"(src), "r"(bar), "r"(peer) : "memory");
}
DEVINL void tma_st(const CUtensorMap* m, int c0, int c1, uint32_t src) {
  asm volatile(EL("cp.async.bulk.tensor.2d.global.shared::cta.bulk_group [%0, {%2, %3}], [%1];") ::"l"(m), "r"(src), "r"(c0), "r"(c1) : "memory");
}
DEVINL void bulk_commit() { asm volatile("cp.async.bulk.commit_group;" ::: "memory"); }
template <int N> DEVINL void bulk_wait_n() { asm volatile("cp.async.bulk.wait_group %0;\nbar.warp.sync 0xffffffff;" ::"n"(N) : "memory"); }
DEVINL void l2_prefetch(const void* g, uint32_t bytes) { asm volatile(EL("cp.async.bulk.prefetch.L2.global [%0], %1;") ::"l"(g), "r"(bytes) : "memory"); }
DEVINL void fence_async_smem() { asm volatile("fence.proxy.async.shared::cta;" ::: "memory"); }
DEVINL void fence_async_gl() { asm volatile("fence.proxy.async.global;" ::: "memory"); }
DEVINL void cluster_wait() { asm volatile("barrier.cluster.wait.aligned;" ::: "memory"); }
DEVINL void bar_sync(int id, int n) { asm volatile("bar.sync %0, %1;" ::"r"(id), "r"(n) : "memory"); }
DEVINL void bar_arrive(int id, int n) { asm volatile("bar.arrive %0, %1;" ::"r"(id), "r"(n) : "memory"); }
DEVINL uint32_t ld_acquire(const uint32_t* p) { uint32_t v; asm volatile("ld.acquire.gpu.global.u32 %0, [%1];" : "=r"(v) : "l"(p) : "memory"); return v; }
DEVINL void watch(const uint32_t* p, uint32_t target, uint32_t all, uint32_t tag, uint32_t slot) {
  uint32_t seen = 0;
#pragma unroll 1
  for (uint32_t n = 0; n < 200000u && seen != all; n++) {
    const uint32_t m = __ballot_sync(~0u, (int)(ld_acquire(p) - target) >= 0) & all;
    if (m != seen) { seen = m; asm volatile("st.release.cta.shared.u32 [%0], %1;" ::"r"(slot), "r"(tag << 16 | m) : "memory"); }
  }
}
template <bool RELAXED = false> DEVINL void await_bit(uint32_t slot, uint32_t tag, int j, uint32_t& rdy) {
  if ((rdy >> j) & 1) return;
#pragma unroll 1
  for (uint32_t n = 0; n < 8000000u; n++) {
    uint32_t v;
    asm volatile("ld.acquire.cta.shared.u32 %0, [%1];" : "=r"(v) : "r"(slot) : "memory");
    if ((v >> 16) == tag && ((v >> j) & 1)) { rdy = v; break; }
    if (RELAXED) __nanosleep(200);
  }
  asm volatile("fence.proxy.async.global;" ::: "memory");
}
DEVINL void poll_ge(const uint32_t* p, uint32_t target) {
#pragma unroll 1
  for (uint32_t n = 0; n < 200000u; n++) if (__all_sync(~0u, (int)(ld_acquire(p) - target) >= 0)) break;
}
DEVINL int lane_id() { int v; asm volatile("mov.u32 %0, %%laneid;" : "=r"(v)); return v; }
__host__ DEVINL int remap(int v) {
  const int c = v >> 1, u = c - 36, r = (u * 37) >> 8;
  const int L = max(c - 4 + max(r + 1, 0), (c - 4) >> 31 & (32 + 8 * c));
  return 2 * L + (v & 1);
}
DEVINL int block_id() { int v; asm volatile("mov.u32 %0, %%ctaid.x;" : "=r"(v)); return v; }
#define cta_id() prm.map[block_id()]
#define IDS() const int lane = lane_id(), b = cta_id(), bm = b >> 4, bn = b & 15, rank = b & 1, pm = 2 * bm + (bn >> 3), pn = bn & 7, po = pm & 1; \
  (void)lane; (void)bm; (void)bn; (void)rank; (void)pm; (void)pn; (void)po
DEVINL void st_tagged(unsigned long long* p, uint32_t v, uint32_t tag) {
  asm volatile("{\n.reg .b64 t;\nmov.b64 t, {%1, %2};\nst.relaxed.gpu.global.b64 [%0], t;\n}" ::"l"(p), "r"(v), "r"(tag) : "memory");
}
DEVINL float ex2(float x) { float y; asm("ex2.approx.ftz.f32 %0, %1;" : "=f"(y) : "f"(x)); return y; }
DEVINL float rcp(float x) { float y; asm("rcp.approx.ftz.f32 %0, %1;" : "=f"(y) : "f"(x)); return y; }
DEVINL uint32_t pack2(float lo, float hi) { uint32_t r; asm("cvt.rn.bf16x2.f32 %0, %1, %2;" : "=r"(r) : "f"(hi), "f"(lo)); return r; }
DEVINL float bf_lo(uint32_t w) { return __uint_as_float(w << 16); }
DEVINL float bf_hi(uint32_t w) { return __uint_as_float(w & 0xFFFF0000u); }
DEVINL float bf_round(float x) { return bf_lo(pack2(x, 0.f)); }
DEVINL uint32_t add_bf16x2(uint32_t a, uint32_t b) { uint32_t r; asm("add.rn.bf16x2 %0, %1, %2;" : "=r"(r) : "r"(a), "r"(b)); return r; }
DEVINL uint32_t max_bf2(uint32_t a, uint32_t b) { uint32_t r; asm("max.bf16x2 %0, %1, %2;" : "=r"(r) : "r"(a), "r"(b)); return r; }
DEVINL uint32_t scale_bf2(uint32_t a) {
  uint32_t r;
  asm("{\n.reg .b32 t;\nmul.rn.bf16x2 t, %1, %3;\nfma.rn.bf16x2 %0, %1, %2, t;\n}" : "=r"(r) : "r"(a), "r"(0x3E353E35u), "r"(0x379E379Eu));
  return r;
}
DEVINL void stsm4(uint32_t addr, uint32_t a, uint32_t b, uint32_t c, uint32_t d) {
  asm volatile("stmatrix.sync.aligned.m8n8.x4.shared.b16 [%0], {%1, %2, %3, %4};" ::"r"(addr), "r"(a), "r"(b), "r"(c), "r"(d) : "memory");
}
DEVINL void ldsm4(uint32_t addr, uint32_t (&r)[4]) {
  asm volatile("ldmatrix.sync.aligned.m8n8.x4.shared.b16 {%0, %1, %2, %3}, [%4];" : "=r"(r[0]), "=r"(r[1]), "=r"(r[2]), "=r"(r[3]) : "r"(addr) : "memory");
}
DEVINL void ldsm4t(uint32_t addr, uint32_t (&r)[4]) {
  asm volatile("ldmatrix.sync.aligned.m8n8.x4.trans.shared.b16 {%0, %1, %2, %3}, [%4];" : "=r"(r[0]), "=r"(r[1]), "=r"(r[2]), "=r"(r[3]) : "r"(addr) : "memory");
}
DEVINL void sts128(uint32_t addr, uint32_t a, uint32_t b, uint32_t c, uint32_t d) {
  asm volatile("st.shared.v4.b32 [%0], {%1, %2, %3, %4};" ::"r"(addr), "r"(a), "r"(b), "r"(c), "r"(d) : "memory");
}
DEVINL float4 lds128f(uint32_t addr) { float4 v; asm volatile("ld.shared.v4.f32 {%0, %1, %2, %3}, [%4];" : "=f"(v.x), "=f"(v.y), "=f"(v.z), "=f"(v.w) : "r"(addr) : "memory"); return v; }
DEVINL float lds32f(uint32_t addr) { float v; asm volatile("ld.shared.f32 %0, [%1];" : "=f"(v) : "r"(addr) : "memory"); return v; }
DEVINL float2 lds64f(uint32_t addr) { float2 v; asm volatile("ld.shared.v2.f32 {%0, %1}, [%2];" : "=f"(v.x), "=f"(v.y) : "r"(addr) : "memory"); return v; }
DEVINL void mma16816(float (&d)[4], uint32_t a0, uint32_t a1, uint32_t a2, uint32_t a3, uint32_t b0, uint32_t b1) {
  asm("mma.sync.aligned.m16n8k16.row.col.f32.bf16.bf16.f32 {%0, %1, %2, %3}, {%4, %5, %6, %7}, {%8, %9}, {%0, %1, %2, %3};"
               : "+f"(d[0]), "+f"(d[1]), "+f"(d[2]), "+f"(d[3]) : "r"(a0), "r"(a1), "r"(a2), "r"(a3), "r"(b0), "r"(b1));
}
DEVINL void mma1688(float (&d)[4], uint32_t a0, uint32_t a1, uint32_t b0) {
  asm("mma.sync.aligned.m16n8k8.row.col.f32.bf16.bf16.f32 {%0, %1, %2, %3}, {%4, %5}, {%6}, {%0, %1, %2, %3};"
               : "+f"(d[0]), "+f"(d[1]), "+f"(d[2]), "+f"(d[3]) : "r"(a0), "r"(a1), "r"(b0));
}
DEVINL void mma1688h(float (&d)[4], uint32_t a0, uint32_t a1, uint32_t b0) {
  asm("mma.sync.aligned.m16n8k8.row.col.f32.f16.f16.f32 {%0, %1, %2, %3}, {%4, %5}, {%6}, {%0, %1, %2, %3};"
               : "+f"(d[0]), "+f"(d[1]), "+f"(d[2]), "+f"(d[3]) : "r"(a0), "r"(a1), "r"(b0));
}
DEVINL void mma16816h(float (&d)[4], uint32_t a0, uint32_t a1, uint32_t a2, uint32_t a3, uint32_t b0, uint32_t b1) {
  asm("mma.sync.aligned.m16n8k16.row.col.f32.f16.f16.f32 {%0, %1, %2, %3}, {%4, %5, %6, %7}, {%8, %9}, {%0, %1, %2, %3};"
               : "+f"(d[0]), "+f"(d[1]), "+f"(d[2]), "+f"(d[3]) : "r"(a0), "r"(a1), "r"(a2), "r"(a3), "r"(b0), "r"(b1));
}
template <int N> DEVINL void fence_regs(uint32_t (&d)[N]) {
#pragma unroll
  for (int i = 0; i < N; i++) asm volatile("" : "+r"(d[i])::"memory");
}
template <int N> DEVINL void fence_regs(float (&d)[N]) {
#pragma unroll
  for (int i = 0; i < N; i++) asm volatile("" : "+f"(d[i])::"memory");
}

__device__ __align__(1024) bf16 g_xs[2048 * 1024];
__device__ __align__(1024) bf16 g_os[2048 * 1024];
__device__ __align__(1024) bf16 g_k[32 * 2048 * 32];
__device__ __align__(1024) bf16 g_v[32 * 2048 * 32];
__device__ __align__(128) float2 g_stats[8 * 2048];
__device__ __align__(16) float g_csp[2 * 16 * 8 * 192];
__device__ __align__(128) float g_kn[2 * 128 * 32];
__device__ unsigned long long g_halo[2 * 128 * 32 * 32];
__device__ __align__(128) uint32_t g_cnt[256 * 32];
__device__ uint32_t g_epoch;

DEVINL uint32_t* cnt_x(int l, int bm) { return g_cnt + (l * 8 + bm) * 32; }
DEVINL uint32_t* cnt_o(int l, int pm, int h) { return g_cnt + (32 + (l * 16 + pm) * 2 + h) * 32; }
DEVINL uint32_t* cnt_kv(int lb, int bn) { return g_cnt + (160 + lb * 16 + bn) * 32; }
DEVINL uint32_t* cnt_ad(int bn) { return g_cnt + (192 + bn) * 32; }
DEVINL uint32_t* cnt_cs(int t, int bn) { return g_cnt + (208 + t * 16 + bn) * 32; }

DEVINL int qord(int i, int l, int pn) { return l == 0 ? i : i < 4 ? ((2 * pn) ^ (i & 2)) + (i & 1) : i - 4 < 2 * (pn & 6) ? i - 4 : i; }
DEVINL int pord(int i, int l, int p) { return (l & 1) || i > p ? i : i ? i - 1 : p; }
struct Params {
  CUtensorMap m[17];
  const bf16* x0;
  const bf16* wq[2];
  const bf16* wo[2];
  uint32_t* epoch;
  uint32_t zero;
  int map[128];
};
enum { M_X0A = 0, M_XSA, M_WQA, M_WQB, M_WOA, M_WOB, M_OS, M_K, M_V, M_X0R, M_XSR, M_XSO, M_OUT, M_XST, M_X0H, M_K4, M_V4, M_COUNT };

constexpr uint32_t QSTG = 57344;
constexpr uint32_t T0 = 65536, TSTG = 32768;
constexpr uint32_t ONES = 229376;
constexpr uint32_t PSTG = 32768;
constexpr uint32_t ASC = 17408;
constexpr uint32_t RSTD = 229376, MEAN = 230400, COLS = 230912, KMAX = 231680, B_QD = 231688, B_OW = 231704, BARS = 232192, SMEM_BYTES = 232448;
constexpr uint32_t B_QF = BARS, B_QE = BARS + 32, B_TF = BARS + 64, B_TE = BARS + 96, B_PF = BARS + 128, B_PE = BARS + 176,
                   B_RF = BARS + 224, W_X = BARS + 232, W_O = BARS + 236, B_QL = BARS + 240, B_PA = BARS + 248;
enum { NB_ST = 1, NB_KV = 2  , NB_DONE = 3, NB_SC = 4, NB_SIG = 5  , NB_KN = 9  , NB_X = 11, NB_HALO = 12  , NB_X0 = 15 };

DEVINL uint32_t pslot_b(uint32_t s, int l) { return ((((l & 1) ? 0x32DC45u : 0x468795u) >> (4 * s)) & 15) * 16384u; }
DEVINL uint32_t pslot_a(uint32_t s, int l) { return ((((l & 1) ? 0xBA8796u : 0x32DCBAu) >> (4 * s)) & 15) * 16384u; }

#define PST 0
#define PWG 0
constexpr float QSCALE = 0.17677669529663687f * 1.4426950408889634f;

DEVINL uint32_t hfma2(uint32_t a, uint32_t b, uint32_t c) { uint32_t r; asm("fma.rn.f16x2 %0, %1, %2, %3;" : "=r"(r) : "r"(a), "r"(b), "r"(c)); return r; }
DEVINL uint32_t pack2h(float lo, float hi) { uint32_t r; asm("cvt.rn.f16x2.f32 %0, %1, %2;" : "=r"(r) : "f"(hi), "f"(lo)); return r; }
DEVINL uint32_t h2_to_bf2(uint32_t h) {
  float a, b;
  asm("{\n.reg .b16 l, h;\nmov.b32 {l, h}, %2;\ncvt.f32.f16 %0, l;\ncvt.f32.f16 %1, h;\n}" : "=f"(a), "=f"(b) : "r"(h));
  return pack2(a, b);
}
DEVINL uint32_t exp2_h2(uint32_t s) {
  const uint32_t r = hfma2(s, 0x00800080u, 0x007E007Eu);
  const uint32_t g = hfma2(hfma2(r, 0xF800F800u, 0x33FD33FDu), 0x44004400u, s);
  return __funnelshift_l(r, r, 7) + hfma2(hfma2(g, g, 0x0DE10DE1u), g, 0x00300030u);
}
constexpr uint32_t NOT_F16 = 0x7FC00000u, K_LO = 0x35000000u  ;
DEVINL uint32_t f16_class(uint32_t norm2, uint32_t lo) { return norm2 - lo > 0x4E800000u - lo ? NOT_F16 : norm2; }

DEVINL void attn_slow(const uint32_t (&q)[8], float up, int head, const float* kn, float (&res)[20], int lane) {
  const int g = lane >> 2, qd = lane & 3;
  const bf16* kb = g_k + (size_t)head * 2048 * 32;
  const bf16* vb = g_v + (size_t)head * 2048 * 32;
  float o[4][4], m0 = -INFINITY, m1 = -INFINITY, l0 = 0.f, l1 = 0.f;
#pragma unroll
  for (int j = 0; j < 4; j++) { o[j][0] = o[j][1] = o[j][2] = o[j][3] = 0.f; }
#pragma unroll 1
  for (int k0 = 0; k0 < 2048; k0 += 16) {
    float s[2][4];
    const bool kh = __float_as_uint(__ldcg(kn + (k0 >> 8) * 32 + ((k0 >> 6) & 1) * 8 + ((k0 >> 7) & 1) * 4 + ((k0 >> 4) & 3))) != NOT_F16;
#pragma unroll
    for (int nt = 0; nt < 2; nt++) {
      s[nt][0] = s[nt][1] = s[nt][2] = s[nt][3] = 0.f;
      const uint32_t* kp = (const uint32_t*)(kb + (size_t)(k0 + nt * 8 + g) * 32) + qd;
      uint32_t kf[4];
#pragma unroll
      for (int i = 0; i < 4; i++) { kf[i] = __ldcg(kp + 4 * i); if (kh) kf[i] = h2_to_bf2(kf[i]); }
      mma16816(s[nt], q[0], q[1], q[2], q[3], kf[0], kf[1]);
      mma16816(s[nt], q[4], q[5], q[6], q[7], kf[2], kf[3]);
      s[nt][0] *= up; s[nt][1] *= up; s[nt][2] *= up; s[nt][3] *= up;
    }
    float a0 = fmaxf(fmaxf(s[0][0], s[0][1]), fmaxf(s[1][0], s[1][1]));
    float a1 = fmaxf(fmaxf(s[0][2], s[0][3]), fmaxf(s[1][2], s[1][3]));
    a0 = fmaxf(a0, __shfl_xor_sync(~0u, a0, 1)); a0 = fmaxf(a0, __shfl_xor_sync(~0u, a0, 2));
    a1 = fmaxf(a1, __shfl_xor_sync(~0u, a1, 1)); a1 = fmaxf(a1, __shfl_xor_sync(~0u, a1, 2));
    const float n0 = fmaxf(m0, a0), n1 = fmaxf(m1, a1);
    const float c0 = (m0 == n0) ? 1.f : ex2(m0 - n0), c1 = (m1 == n1) ? 1.f : ex2(m1 - n1);
    m0 = n0; m1 = n1;
    const uint32_t p0 = pack2(ex2(s[0][0] - n0), ex2(s[0][1] - n0)), p1 = pack2(ex2(s[0][2] - n1), ex2(s[0][3] - n1));
    const uint32_t p2 = pack2(ex2(s[1][0] - n0), ex2(s[1][1] - n0)), p3 = pack2(ex2(s[1][2] - n1), ex2(s[1][3] - n1));
    l0 = l0 * c0 + bf_lo(p0) + bf_hi(p0) + bf_lo(p2) + bf_hi(p2);
    l1 = l1 * c1 + bf_lo(p1) + bf_hi(p1) + bf_lo(p3) + bf_hi(p3);
#pragma unroll
    for (int j = 0; j < 4; j++) {
      o[j][0] *= c0; o[j][1] *= c0; o[j][2] *= c1; o[j][3] *= c1;
      const unsigned short* vp = (const unsigned short*)(vb + (size_t)(k0 + 2 * qd) * 32 + j * 8 + g);
      const uint32_t b0 = (uint32_t)__ldcg(vp) | ((uint32_t)__ldcg(vp + 32) << 16);
      const uint32_t b1 = (uint32_t)__ldcg(vp + 256) | ((uint32_t)__ldcg(vp + 288) << 16);
      mma16816(o[j], p0, p1, p2, p3, b0, b1);
    }
  }
  l0 += __shfl_xor_sync(~0u, l0, 1); l0 += __shfl_xor_sync(~0u, l0, 2);
  l1 += __shfl_xor_sync(~0u, l1, 1); l1 += __shfl_xor_sync(~0u, l1, 2);
#pragma unroll
  for (int j = 0; j < 4; j++) { res[4 * j] = o[j][0]; res[4 * j + 1] = o[j][1]; res[4 * j + 2] = o[j][2]; res[4 * j + 3] = o[j][3]; }
  res[16] = l0; res[18] = l1;
}

__global__ void __cluster_dims__(2, 1, 1) __launch_bounds__(384, 1) fused_kernel(const __grid_constant__ Params prm) {
  extern __shared__ __align__(1024) char smem[];
  const uint32_t sb = (uint32_t)__cvta_generic_to_shared(smem);
  const int tid = threadIdx.x;
  const int wid = __shfl_sync(0xffffffffu, tid >> 5, 0), wg = wid >> 2, w = wid & 3;
  const int bm = remap(blockIdx.x) >> 4, bn = remap(blockIdx.x) & 15;
  auto first_tile = [&](int kt) {
    e_expect_tx(sb + B_QF + 8 * kt, QSTG);
    tma_ld(sb + kt * QSTG, &prm.m[M_X0A], kt * 64, bm * 256, sb + B_QF + 8 * kt);
    tma_ld3(sb + kt * QSTG + 32768, &prm.m[M_WQA], bn * 64, kt * 64, 0, sb + B_QF + 8 * kt);
  };
  if (wid == 8) {
    e_init(sb + B_QF, 1);
    asm volatile("fence.mbarrier_init.release.cluster;" ::: "memory");
    first_tile(0);
  }
  if (wid < 8) {
#pragma unroll
    for (int i = 0; i < 4; i++) {
      const uint32_t cnt = (uint32_t)((i == 0 ? 0x14112140 : i == 1 ? 0x04112141 : i == 2 ? 0x14412141 : 0x24412141) >> (4 * wid)) & 7;
      if (cnt) e_init(sb + BARS + 32 * wid + 8 * i, cnt);
    }
    if (wid < 3) e_init(sb + B_QD + wid * 8, wid < 2 ? 1 : 2);
    if (tid == 255) *(uint2*)(smem + W_X) = make_uint2(0u, 0u);
    asm volatile("fence.mbarrier_init.release.cluster;" ::: "memory");
  }
  const uint32_t epoch = *(volatile uint32_t*)prm.epoch;
  __syncthreads();
  asm volatile("barrier.cluster.arrive.relaxed.aligned;" ::: "memory");

  if (wg == 2) {
    asm volatile("setmaxnreg.dec.sync.aligned.u32 56;");
    const uint32_t ep1 = epoch + 1;
    if (w == 0) {
      first_tile(1);
      mbar_wait(sb + B_QF, 0);
      first_tile(2); first_tile(3);
#pragma unroll 1
      for (int kt = 4; kt < 16; kt++) l2_prefetch(prm.wq[0] + kt * 196608 + blockIdx.x * 1536, 3072);
      cluster_wait();
#pragma unroll 1
      for (int l = 0; l < 4; l++) {
        IDS();
        const CUtensorMap* mw = &prm.m[M_WQA + (l & 1)];
        const CUtensorMap* mh = &prm.m[l == 0 ? M_X0H : M_XSO];
        const CUtensorMap* mo = &prm.m[M_WOA + (l & 1)];
        auto q_b = [&](int i) {
          const int s = i & 3;
          mbar_wait(sb + B_QE + 8 * s, ((i >> 2) & 1) ^ 1);
          e_expect_tx(sb + B_QF + 8 * s, QSTG);
          tma_ld3(sb + s * QSTG + 32768, mw, bn * 64, qord(i, l, pn) * 64, 0, sb + B_QF + 8 * s);
        };
        uint32_t rdy = l ? 0u : ~0u;
        auto q_a = [&](int i) {
          const int kt = qord(i, l, pn);
          await_bit(sb + W_X, l, kt >> 1, rdy);
          tma_ld_mc(sb + (i & 3) * QSTG + rank * 16384, mh, kt * 64, bm * 256 + rank * 128, sb + B_QF + 8 * (i & 3));
        };
        if (l > 0) {
#pragma unroll 1
          for (int i = 0; i < 4; i++) {
            const int kt = qord(i, l, pn);
            await_bit(sb + W_X, l, kt >> 1, rdy);
            e_expect_tx(sb + B_QF + 8 * i, 16384);
            tma_ld(sb + i * QSTG + (po ^ 1) * 16384, &prm.m[M_XSO], kt * 64, (pm ^ 1) * 128, sb + B_QF + 8 * i);
          }
        }
#pragma unroll 1
        for (int i = 4; i < 16; i++) {
          q_b(i); q_a(i);
          if (l == 0 && i >= 8 && i < 12) l2_prefetch(prm.wq[1] + (blockIdx.x * 4 + i - 8) * 6144, 12288);
          if (l < 2 && i == 12) l2_prefetch(prm.wo[l] + blockIdx.x * 8192, 16384);
        }
        if (l & 1) {
          if (l == 3) poll_ge(cnt_ad(bn), ep1 * 16);
          const int krow = 2 * bn * 2048 + bm * 256;
          uint32_t* kvc = cnt_kv(l >> 1, bn);
#pragma unroll 1
          for (int m = 1; m >= 0; m--) {
            bar_sync(m ? NB_ST : NB_KV, 288);
#pragma unroll
            for (int i = 0; i < 4; i++) tma_st(&prm.m[M_K4 + (i >> 1)], 0, krow + (i & 1) * 128 + m * 64, sb + T0 + i * 8192 + m * 4096);
            if (m) {
              sts128(sb + ONES + lane * 32, 0x3f803f80u, 0x3f803f80u, 0x3f803f80u, 0x3f803f80u);
              sts128(sb + ONES + lane * 32 + 16, 0x3f803f80u, 0x3f803f80u, 0x3f803f80u, 0x3f803f80u);
              fence_async_smem();
              __syncwarp();
            }
          }
          e_arrive(sb + B_TF);
          bulk_commit(); bulk_wait_n<0>();
          e_red(kvc + bm);
          bar_sync(NB_KV + 12, 288);
          uint32_t seen = 0;
#pragma unroll 1
          for (int it = 1; it < 16; it++) {
            const int s = it & 3, blk = it;
            if (it == 4) { tma_st(&prm.m[M_K], 0, krow + 2048, sb); tma_st(&prm.m[M_V], 0, krow + 2048, sb + 16384); bulk_commit(); }
            if (it == 5) { bulk_wait_n<0>(); e_red(kvc + bm); }
            if (it == 12) { e_expect_tx(sb + B_RF, 32768); tma_ld3(sb, &prm.m[M_XSR], 0, pm * 128, 2 * pn, sb + B_RF); }
            if (it == 2 || it == 3) mbar_wait(sb + B_TF + 8 * (it - 1), 0);
            mbar_wait_long(sb + B_TE + 8 * s, ((it >> 2) & 1) ^ 1);
            if (it < 8) {
#pragma unroll 1
              for (uint32_t n = 0; n < 200000u && !((seen >> it) & 1); n++)
                seen = __ballot_sync(~0u, (int)(ld_acquire(kvc + ((bm + lane) & 7)) - (ep1 * 2 - 1)) >= 0);
              fence_async_gl();
            } else if (it == 8) { poll_ge(kvc + (lane & 7), ep1 * 2); fence_async_gl(); bar_arrive(NB_HALO, 64); }
            else if (it == 15) bar_arrive(NB_HALO + 1, 64);
            const int row = (2 * bn + (it >> 3)) * 2048 + ((bm + blk) & 7) * 256;
            e_expect_tx(sb + B_TF + 8 * s, 32768);
            tma_ld(sb + T0 + s * TSTG, &prm.m[M_K], 0, row, sb + B_TF + 8 * s);
            tma_ld(sb + T0 + s * TSTG + 16384, &prm.m[M_V], 0, row, sb + B_TF + 8 * s);
          }
        }
        auto p_b = [&](int i, uint32_t s, uint32_t par) {
          const int kt = pord(i, l, bn >> 1);
          mbar_wait(sb + B_PE + 8 * s, par ^ 1);
          e_expect_tx(sb + B_PF + 8 * s, PSTG);
          tma_ld5(sb + pslot_b(s, l), mo, kt >> 3, 2 * (kt & 7), 2 * pn, sb + B_PF + 8 * s);
        };
        auto p_a = [&](int i, uint32_t s) {
          const int kt = pord(i, l, bn >> 1);
          await_bit(sb + W_O, l + 1, kt, rdy);
          tma_ld_mc(sb + pslot_a(s, l) + rank * 8192, &prm.m[M_OS], kt * 64, pm * 128 + rank * 64, sb + B_PF + 8 * s);
        };
        auto p_a2 = [&](int i) {
          const int kt = pord(i, l, bn >> 1);
          await_bit(sb + W_O, l + 1, kt, rdy);
          tma_ld(sb + pslot_a(i, l), &prm.m[M_OS], kt * 64, pm * 128, sb + B_PF + 8 * i);
          tma_ld(sb + pslot_a(i, l) + 8192, &prm.m[M_OS], kt * 64, pm * 128 + 64, sb + B_PF + 8 * i);
        };
        rdy = 0;
        if (l & 1) {
#pragma unroll 1
          for (int u = 0; u < 6; u++) { const int i = (0x105432 >> (4 * u)) & 7; if (u == 4) mbar_wait_long(sb + B_TE, 1); p_b(i, i, i < 4 ? 1 : 0); }
#pragma unroll 1
          for (int u = 0; u < 6; u++) {
            const int i = (0x543120 >> (4 * u)) & 7;
            if (!(u & 1)) mbar_wait_long(sb + B_TE + 8 + 4 * u, 1);
            p_a2(i);
          }
        } else {
#pragma unroll 1
          for (int u = 0; u < 5; u++) { const int i = (0x32140 >> (4 * u)) & 7; if (!(u & 5)) mbar_wait(sb + B_QE + 8 + 4 * u, 1); p_b(i, i, 0); }
          mbar_wait(sb + B_QE + 24, 1);
          mbar_wait(sb + B_OW, (l >> 1) & 1);
          fence_async_gl();
          rdy = 1u << (bn >> 1);
#pragma unroll 1
          for (int i = 0; i < 4; i++) { p_a(i, i); }
          bar_sync(NB_DONE, 96);
          e_arrive_both(sb + B_PA);
          p_b(5, 5, 0);
          mbar_wait(sb + B_PA, (l >> 1) & 1);
          p_a(4, 4); p_a(5, 5);
        }
        uint32_t s = 0, lap = 1;
#pragma unroll 1
        for (int i = 6; i < 16; i++) {
          if (i == 12 && !(l & 1)) { e_expect_tx(sb + B_RF, 32768); tma_ld3(sb, &prm.m[l == 0 ? M_X0R : M_XSR], 0, pm * 128, 2 * pn, sb + B_RF); }
          p_b(i, s, ((s < 4 ? l : 0) + lap) & 1);
          p_a(i, s);
          if (++s == 6) { s = 0; lap++; }
        }
        const CUtensorMap* mn = &prm.m[M_WQA + ((l + 1) & 1)];
        if (l < 3) {
          mbar_wait(sb + B_PE + 8 * 4, 1); mbar_wait(sb + B_PE + 8 * 5, 1);
          tma_ld3(sb + 32768, mn, bn * 64, 2 * pn * 64, 0, sb + B_QL);
          mbar_wait(sb + B_PE + 8 * 0, l & 1);
          tma_ld3(sb + QSTG + 32768, mn, bn * 64, (2 * pn + 1) * 64, 0, sb + B_QL);
          mbar_wait(sb + B_PE + 8 * 1, l & 1);
          e_expect_tx(sb + B_QD, 40960);
          tma_ld3(sb + 2 * QSTG + 32768, mn, bn * 64, ((2 * pn) ^ 2) * 64, 0, sb + B_QD);
          bar_sync(NB_X, 288);
          e_expect_tx(sb + B_QL, 49152);
          e_expect_tx(sb + B_QD + 8, 40960);
          tma_ld3(sb + 3 * QSTG + 32768, mn, bn * 64, (((2 * pn) ^ 2) + 1) * 64, 0, sb + B_QD + 8);
        }
      }
      if (blockIdx.x == 0 && lane_id() == 0) *(volatile uint32_t*)prm.epoch = ep1;
    } else {
      const int hw = w - 1;
      if (hw == 1 && lane_id() < M_COUNT) asm volatile("prefetch.tensormap [%0];" ::"l"(&prm.m[lane_id()]) : "memory");
      cluster_wait();
      mbar_wait(sb + B_QF, 0);
#pragma unroll 1
      for (int l = 0; l < 4; l++) {
        IDS();
        if (hw == 2 && l > 0) watch(cnt_x(l, bm) + (lane & 7), ep1 * 2, 0xFFu, l, sb + W_X);
        if (l == 0) {
#pragma unroll 1
          for (int r = 2 * hw; r < 16; r += 6) {
            const uint4* p = (const uint4*)(prm.x0 + (size_t)(b * 16 + r) * 1024) + lane;
            float s1[2] = {0.f, 0.f}, s2[2] = {0.f, 0.f};
#pragma unroll
            for (int i = 0; i < 8; i++) {
              const uint4 v = __ldg(p + 32 * i);
              const uint32_t u[4] = {v.x, v.y, v.z, v.w};
#pragma unroll
              for (int k = 0; k < 4; k++) { const float a = bf_lo(u[k]), c = bf_hi(u[k]); s1[i >> 2] += a + c; s2[i >> 2] = fmaf(a, a, fmaf(c, c, s2[i >> 2])); }
            }
#pragma unroll
            for (int o = 16; o; o >>= 1)
#pragma unroll
              for (int rr = 0; rr < 2; rr++) { s1[rr] += __shfl_xor_sync(~0u, s1[rr], o); s2[rr] += __shfl_xor_sync(~0u, s2[rr], o); }
            if (lane == 0) *(float4*)&g_stats[b * 16 + r] = make_float4(s1[0], s2[0], s1[1], s2[1]);
          }
        }
        if (l == 1) { uint32_t rdy = 0; await_bit<true>(sb + W_X, 1, pn, rdy); mbar_hint(sb + B_QF + 8, 0); }
        if (l < 2) {
          float cs[8];
#pragma unroll
          for (int i = 0; i < 8; i++) cs[i] = 0.f;
          const uint4* wp = (const uint4*)(prm.wq[l] + (size_t)(bm * 128 + (lane >> 3)) * 3072 + hw * 1024 + bn * 64) + (lane & 7);
#pragma unroll 8
          for (int i = 0; i < 32; i++) {
            const uint4 v = __ldg(wp + (size_t)i * 4 * 384);
            cs[0] += bf_lo(v.x); cs[1] += bf_hi(v.x); cs[2] += bf_lo(v.y); cs[3] += bf_hi(v.y);
            cs[4] += bf_lo(v.z); cs[5] += bf_hi(v.z); cs[6] += bf_lo(v.w); cs[7] += bf_hi(v.w);
          }
#pragma unroll
          for (int i = 0; i < 8; i++) { cs[i] += __shfl_xor_sync(~0u, cs[i], 8); cs[i] += __shfl_xor_sync(~0u, cs[i], 16); }
          if (lane < 8) {
            float4* d = (float4*)(g_csp + ((l * 16 + bn) * 8 + bm) * 192 + hw * 64 + lane * 8);
            d[0] = make_float4(cs[0], cs[1], cs[2], cs[3]); d[1] = make_float4(cs[4], cs[5], cs[6], cs[7]);
          }
          __syncwarp();
          asm volatile("fence.acq_rel.gpu;" ::: "memory");
          e_red_relaxed(cnt_cs(l, bn));
          if (l == 0) e_red_relaxed(cnt_x(0, bm) + pn);
          poll_ge(lane < 8 && l == 0 ? cnt_x(0, bm) + lane : cnt_cs(l, bn), ep1 * (lane < 8 && l == 0 ? 6 : 24));
        }
        if (l > 0) {
          uint32_t rdy = 0;
#pragma unroll 1
          for (int j = 0; j < 8; j++) await_bit<true>(sb + W_X, l, j, rdy);
        }
#pragma unroll 1
        for (int it = hw * 32 + lane; it < 176; it += 96) {
          const bool rows = it < 128;
          const float4* p = rows ? (const float4*)(g_stats + bm * 256) + it : (const float4*)(g_csp + ((l & 1) * 16 + bn) * 8 * 192) + (it - 128);
          const int stride = rows ? 1024 : 48, np = rows && l == 0 ? 1 : 8;
          float4 a = make_float4(0.f, 0.f, 0.f, 0.f);
#pragma unroll
          for (int k = 0; k < 8; k++) if (k < np) { const float4 v = __ldcg(p + k * stride); a.x += v.x; a.y += v.y; a.z += v.z; a.w += v.w; }
          if (rows) {
            const float m0 = a.x * (1.f / 1024.f), m1 = a.z * (1.f / 1024.f);
            const float v0 = fmaxf(a.y * (1.f / 1024.f) - m0 * m0, 0.f), v1 = fmaxf(a.w * (1.f / 1024.f) - m1 * m1, 0.f);
            const float r0 = __fdividef(1.f, bf_round(sqrtf(bf_round(bf_round(v0) + 1e-5f)))), r1 = __fdividef(1.f, bf_round(sqrtf(bf_round(bf_round(v1) + 1e-5f))));
            *(float2*)(smem + RSTD + it * 8) = make_float2(r0, r1);
            *(uint32_t*)(smem + MEAN + it * 4) = pack2(-m0, -m1);
          } else {
            float2* d = (float2*)(smem + COLS) + ((it - 128) >> 2) * 8 + (it & 1) * 4 + ((it >> 1) & 1);
            d[0] = make_float2(a.y, a.x); d[2] = make_float2(a.w, a.z);
          }
        }
        __syncwarp();
        if (lane == 0) asm volatile("red.release.cta.shared.add.u32 [%0], 0x100;" ::"r"(sb + W_X) : "memory");
        if (hw == 2) {
          if (!(l & 1)) {
            bar_sync(NB_ST, 288);
            const volatile unsigned long long* hp = g_halo + ((size_t)(l >> 1) * 128 + b - 16) * 1024 + lane;
#pragma unroll 1
            for (int h = 0; h < 2; h++) {
              uint32_t t[16];
#pragma unroll
              for (int i = 0; i < 16; i++) t[i] = 0;
#pragma unroll 1
              for (uint32_t n = bm ? 0 : 100000u; n < 100000u; n++) {
                uint32_t miss = 0;
#pragma unroll
                for (int i = 0; i < 16; i++) {
                  const unsigned long long v = hp[h * 512 + i * 32];
                  t[i] = (uint32_t)v; miss |= (uint32_t)(v >> 32) ^ ep1;
                }
                if (__all_sync(~0u, !miss)) break;
              }
              const uint32_t r = (lane & 7) + ((lane >> 3) & 1) * 8, rv = lane >> 2;
#pragma unroll
              for (int jj = 0; jj < 2; jj++) stsm4(sb + 2 * h * ASC + r * 64 + (((2 * jj + (lane >> 4)) ^ ((r >> 1) & 3)) << 4), t[4 * jj], t[4 * jj + 1], t[4 * jj + 2], t[4 * jj + 3]);
              const uint32_t ad = sb + (2 * h + 1) * ASC + rv * 64 + (((lane & 3) ^ ((rv >> 1) & 3)) << 4);
              sts128(ad, t[8], t[10], t[12], t[14]); sts128(ad + 512, t[9], t[11], t[13], t[15]);
              bar_arrive(NB_HALO + h, 64);
            }
          } else {
            bar_sync(NB_HALO, 64);
            const uint4* kp = (const uint4*)(g_kn + ((l >> 1) * 128 + bn * 8) * 32) + 2 * lane;
            const uint4 v = __ldcg(kp), u = __ldcg(kp + 1);
            const uint32_t mx = max(max(max(v.x, v.y), max(v.z, v.w)), max(max(u.x, u.y), max(u.z, u.w)));
            const uint32_t m0 = __reduce_max_sync(~0u, (lane & 2) ? 0u : mx), m1 = __reduce_max_sync(~0u, (lane & 2) ? mx : 0u);
            if (lane == 0) *(uint2*)(smem + KMAX) = make_uint2(m0, m1);
            __syncwarp();
            bar_arrive(NB_KN, 160); bar_arrive(NB_KN + 1, 160);
            bar_sync(NB_HALO + 1, 64);
            watch(cnt_o(l, pm, 0) + (lane & 7), ep1 * 2, 0xFFu, l + 1, sb + W_O);
          }
        } else {
          bar_sync(NB_SIG + 2 * hw, 160); bar_sync(NB_SIG + 2 * hw + 1, 160);
          if (!(l & 1)) bar_arrive(NB_DONE, 96);
          if (hw == (l & 1)) bar_arrive((l & 1) ? NB_DONE : NB_KN, 64);
          asm volatile("fence.acq_rel.gpu;" ::: "memory");
          e_red_relaxed(cnt_o(l, 2 * bm, hw) + (bn >> 1));
          e_red_relaxed(cnt_o(l, 2 * bm + 1, hw) + (bn >> 1));
          if (hw == 0 && !(l & 1)) e_arrive_both(sb + B_OW);
          if (hw == 1 && l == 1) { e_red_relaxed(cnt_ad(bn)); e_red_relaxed(cnt_ad(bn)); }
        }
        if (hw == 2) { bar_sync((l & 1) ? NB_DONE : NB_KN, 64); watch(cnt_o(l, pm, (lane >> 3) & 1) + (lane & 7), ep1 * 2, 0xFFFFu, l + 1, sb + W_O); }
        if (l < 3) {
          bar_sync(NB_X0, 352);
          if (hw == 0) {
            e_red(cnt_x(l + 1, bm) + pn);
          } else if (hw == 1) {
            mbar_wait(sb + B_PE + 8 * 3, l & 1);
            push_peer(sb + 2 * QSTG + po * 16384, sb + po * 16384, sb + B_QD, rank ^ 1);
            push_peer(sb + 3 * QSTG + po * 16384, sb + QSTG + po * 16384, sb + B_QD + 8, rank ^ 1);
          }
        }
      }
    }
  } else {
    asm volatile("setmaxnreg.inc.sync.aligned.u32 224;");
    const uint32_t zero = prm.zero;
    cluster_wait();
    const uint32_t ep1 = __shfl_sync(~0u, epoch + 1, 0);
#pragma unroll 1
    for (int l = 0; l < 4; l++) {
      {
        float acc[2][96];
#pragma unroll
        for (int i = 0; i < 96; i++) { acc[0][i] = 0.f; acc[1][i] = 0.f; }
        fence_regs(acc[0]); fence_regs(acc[1]);
        const bool early = l > 0 && wg == ((cta_id() >> 3) & 1);
#pragma unroll 1
        for (int kt = 0; kt < 14; kt++) {
          const int s = kt & 3;
          if (l > 0 && kt < 4 && kt != 1) mbar_wait(sb + (kt ? B_QD - 16 + 8 * kt : B_QL), (l + 1) & 1);
          if (!(early && kt < 4)) mbar_wait(sb + B_QF + 8 * s, (kt >> 2) & 1);
          const uint64_t da = mkdesc(sb + s * QSTG + wg * 16384, 16, 1024, 1), db = mkdesc(sb + s * QSTG + 32768, 8192, 1024, 1);
          wg_fence();
#pragma unroll
          for (int k = 0; k < 4; k++)
#pragma unroll
            for (int m = 0; m < 2; m++) wgmma_m64n192k16_ss_tb(acc[m], da + m * 512 + k * 2, db + k * 128, 1);
          wg_commit();
          wg_wait<1>();
          if (early && kt < 5) {
#pragma unroll 1
            for (int i = kt == 3 ? 0 : 3; i < kt; i++) { mbar_wait(sb + B_QF + 8 * i, 0); if (w == 0) e_arrive_both(sb + B_QE + 8 * i); }
          } else if (kt > 0 && w == 0) e_arrive_both(sb + B_QE + 8 * ((kt - 1) & 3));
          if (kt == 11 + 2 * wg) {
#pragma unroll 1
            for (uint32_t n = 0; n < 4000000u; n++) {
              uint32_t v;
              asm volatile("ld.acquire.cta.shared.u32 %0, [%1];" : "=r"(v) : "r"(sb + W_X) : "memory");
              if ((v >> 8) == (uint32_t)(l * 256 + 3)) break;
            }
            const int lane = lane_id();
            float nm[4];
#pragma unroll
            for (int i = 0; i < 4; i++) nm[i] = bf_lo(*(volatile unsigned short*)(smem + MEAN + (wg * 128 + w * 16 + (lane >> 2) + (i >> 1) * 64 + (i & 1) * 8) * 2));
            wg_wait<0>();
            fence_regs(acc[0]); fence_regs(acc[1]);
#pragma unroll
            for (int j = 0; j < 12; j++) {
              const float4 c = lds128f(sb + COLS + j * 64 + (lane & 3) * 16);
#pragma unroll
              for (int m = 0; m < 2; m++) {
                float* a = &acc[m][8 * j];
                a[0] = fmaf(nm[2 * m], c.y, a[0]); a[1] = fmaf(nm[2 * m], c.x, a[1]); a[2] = fmaf(nm[2 * m + 1], c.y, a[2]); a[3] = fmaf(nm[2 * m + 1], c.x, a[3]);
                a[4] = fmaf(nm[2 * m], c.w, a[4]); a[5] = fmaf(nm[2 * m], c.z, a[5]); a[6] = fmaf(nm[2 * m + 1], c.w, a[6]); a[7] = fmaf(nm[2 * m + 1], c.z, a[7]);
              }
            }
            fence_regs(acc[0]); fence_regs(acc[1]);
          }
        }
        auto part = [&](int s, int m, int k0, int k1) {
          const uint64_t da = mkdesc(sb + s * QSTG + wg * 16384 + m * 8192, 16, 1024, 1), db = mkdesc(sb + s * QSTG + 32768, 8192, 1024, 1);
          wg_fence();
#pragma unroll
          for (int k = k0; k < k1; k++) wgmma_m64n192k16_ss_tb(acc[m], da + k * 2, db + k * 128, 1);
          wg_commit();
        };
        mbar_wait(sb + B_QF + 16, 1);
        part(2, 1, 0, 4);
        wg_wait<1>();
        if (w == 0) e_arrive_both(sb + B_QE + 8);
        if (!(l & 1)) bar_arrive(NB_ST, 288);
        mbar_wait(sb + B_QF + 24, 1);
        part(3, 1, 0, 4);
        part(2, 0, 0, 2);
        IDS();
        const int g = lane >> 2, qd = lane & 3;
        float rs[2][2];
#pragma unroll
        for (int i = 0; i < 4; i++) rs[i >> 1][i & 1] = lds32f(sb + RSTD + (wg * 128 + w * 16 + g + (i >> 1) * 64 + (i & 1) * 8) * 4);
        auto scale = [&](int gi, int m, float sc) {
          const float r0 = rs[m][0] * sc, r1 = rs[m][1] * sc;
#pragma unroll
          for (int i = 0; i < 16; i++) acc[m][16 * gi + i] *= (i & 2) ? r1 : r0;
        };
        auto pack_b = [&](int gi, int m, uint32_t (&t)[8]) {
#pragma unroll
          for (int i = 0; i < 8; i++) t[i] = pack2(acc[m][16 * gi + 2 * i], acc[m][16 * gi + 2 * i + 1]);
        };
        auto norm_tile = [&](int gi, int m, uint32_t (&t)[8]) { scale(gi, m, 1.f); pack_b(gi, m, t); };
        auto pack_h = [&](int gi, int m, uint32_t (&t)[8]) {
#pragma unroll
          for (int i = 0; i < 8; i++) t[i] = pack2h(acc[m][16 * gi + 2 * i], acc[m][16 * gi + 2 * i + 1]);
        };
        uint32_t q[2][2][8], qn[2][2];
        const uint32_t srow = (lane & 7) + ((lane >> 3) & 1) * 8;
        const uint32_t row0 = wg * 128 + w * 16;
        auto put_kv = [&](int h, int v, int m, const uint32_t (&t)[8]) {
          const uint32_t base = sb + ((l & 1) ? (h ? 0 : T0) + v * 16384 : (2 * h + v) * ASC + 1024) + (row0 + m * 64) * 64;
          if (!v) {
#pragma unroll
            for (int jj = 0; jj < 2; jj++) stsm4(base + srow * 64 + (((2 * jj + (lane >> 4)) ^ ((srow >> 1) & 3)) << 4), t[4 * jj], t[4 * jj + 1], t[4 * jj + 2], t[4 * jj + 3]);
          } else {
            const uint32_t ad = base + g * 64 + ((qd ^ (g >> 1)) << 4);
            sts128(ad, t[0], t[2], t[4], t[6]); sts128(ad + 512, t[1], t[3], t[5], t[7]);
          }
        };
        auto send_halo = [&](int h, int v, const uint32_t (&t)[8]) {
          unsigned long long* hp = g_halo + ((size_t)(l >> 1) * 128 + b) * 1024 + h * 512 + v * 256 + lane;
#pragma unroll
          for (int i = 0; i < 8; i++) st_tagged(hp + i * 32, t[i], ep1);
        };
        auto put_kn = [&](int h, int m, uint32_t kn) {
          if (lane == 0) g_kn[((l >> 1) * 128 + bn * 8 + bm) * 32 + 16 * h + 8 * m + wg * 4 + w] = __uint_as_float(kn);
        };
        auto conv_tile1 = [&](int h) {
          uint32_t t[8], tv[8], kn = NOT_F16;
          norm_tile(4 + h, 1, tv);
          put_kv(h, 1, 1, tv);
          scale(2 + h, 1, 1.f);
          part(2 + h, 0, 2, 4);
          if (l & 1) {
            float n[2] = {0.f, 0.f};
#pragma unroll
            for (int i = 0; i < 16; i++) n[(i >> 1) & 1] = fmaf(acc[1][32 + 16 * h + i], acc[1][32 + 16 * h + i], n[(i >> 1) & 1]);
            const float a = ((qd & 1) ? n[1] : n[0]) + __shfl_xor_sync(~0u, (qd & 1) ? n[0] : n[1], 1);
            scale(h, 1, QSCALE / 128.f);
            kn = f16_class(__reduce_max_sync(~0u, __float_as_uint(a + __shfl_xor_sync(~0u, a, 2))), K_LO);
            put_kn(h, 1, kn);
          } else scale(h, 1, 1.f);
          if (kn == NOT_F16) pack_b(2 + h, 1, t); else pack_h(2 + h, 1, t);
          put_kv(h, 0, 1, t);
          if (!(l & 1) && row0 == 176 && bm < 7) { send_halo(h, 0, t); send_halo(h, 1, tv); }
        };
        mbar_wait(sb + B_QE + 8, 1);
        wg_wait<1>();
        fence_regs(acc[1]);
        conv_tile1(0);
        part(3, 0, 0, 2);
        if (l & 1) { fence_async_smem(); bar_arrive(NB_ST, 288); }
        conv_tile1(1);
        wg_wait<2>();
        if (w == 0) e_arrive_both(sb + B_QE + 16);
        wg_wait<0>();
        fence_regs(acc[0]);
        if (w == 0) e_arrive_both(sb + B_QE + 24);
        bf16* const op0 = [&] { IDS(); return g_os + (size_t)(bm * 256 + row0 + (lane >> 2)) * 1024 + bn * 32 + (lane & 3) * 8; }();
        auto put_o = [&](int h, int m, const float (&o)[16], float i0, float i1) {
          bf16* op = op0 + m * 65536 + h * 512;
          const uint4 a = make_uint4(pack2(o[0] * i0, o[1] * i0), pack2(o[4] * i0, o[5] * i0), pack2(o[8] * i0, o[9] * i0), pack2(o[12] * i0, o[13] * i0));
          const uint4 c = make_uint4(pack2(o[2] * i1, o[3] * i1), pack2(o[6] * i1, o[7] * i1), pack2(o[10] * i1, o[11] * i1), pack2(o[14] * i1, o[15] * i1));
          *(uint4*)op = a; *(uint4*)(op + 8 * 1024) = c;
          const uint32_t hi = __vimax3_u16x2(__vimax3_u16x2(a.x, a.y, a.z), __vimax3_u16x2(a.w, c.x, c.y), __vmaxu2(c.z, c.w));
          const uint32_t lo = __vimax3_s16x2(__vimax3_s16x2(a.x, a.y, a.z), __vimax3_s16x2(a.w, c.x, c.y), __vmaxs2(c.z, c.w));
          return __vmaxu2(hi & 0x7FFF7FFFu, lo & 0x7FFF7FFFu);
        };
        if (!(l & 1)) {
          auto conv_kv = [&](int h) {
            uint32_t t[8];
            norm_tile(2 + h, 0, t); put_kv(h, 0, 0, t);
            norm_tile(4 + h, 0, t); put_kv(h, 1, 0, t);
          };
          conv_kv(0);
          norm_tile(0, 0, q[0][0]); pack_b(0, 1, q[0][1]);
          bar_sync(NB_SC, 256);
          const bool e = g & 1, sel = 2 * qd + (g & 1) >= g + 2, first = bm == 0 && row0 == 0;
          const uint32_t pm_a = e ? 0x1044 : 0x4410, pm_b = e ? 0x3244 : 0x4432, pm_lo = sel ? pm_b : 0x4444, pm_hi = sel ? 0x4444 : pm_b;
          const uint32_t ka = sb + (row0 + (lane & 7)) * 64 + (((lane >> 3) ^ ((lane >> 1) & 3)) << 4);
          const uint32_t va0 = sb + ASC + (row0 + srow) * 64 + (((lane >> 4) ^ ((lane >> 1) & 3)) << 4);
#pragma unroll 1
          for (int h = 0; h < 2; h++) {
            if (row0 == 0) bar_sync(NB_HALO + h, 64);
            float s[2][4][4];
            uint32_t vf[2][4][4], pf[2][2][4];
#pragma unroll
            for (int m = 0; m < 2; m++)
#pragma unroll
              for (int nt = 0; nt < 4; nt++) {
                uint32_t kf[4];
                ldsm4(ka + h * (2 * ASC) + (m * 64 + 8 * nt) * 64, kf);
                s[m][nt][0] = s[m][nt][1] = s[m][nt][2] = s[m][nt][3] = 0.f;
                mma16816(s[m][nt], q[0][m][0], q[0][m][1], q[0][m][2], q[0][m][3], kf[0], kf[1]);
                mma16816(s[m][nt], q[0][m][4], q[0][m][5], q[0][m][6], q[0][m][7], kf[2], kf[3]);
              }
#pragma unroll
            for (int m = 0; m < 2; m++)
#pragma unroll
              for (int i = 0; i < 4; i++) {
                ldsm4t(((va0 + h * (2 * ASC)) ^ (32 * (i & 1))) + (m * 64 + 16 * (i >> 1)) * 64, vf[m][i]);
              }
            float va[4], vb[4], mx[4];
            uint32_t ua[2], ub[2], um[2];
#pragma unroll
            for (int m = 0; m < 2; m++) {
              float a[2], c[2];
#pragma unroll
              for (int hh = 0; hh < 2; hh++) {
                a[hh] = e ? s[m][hh + 1][2 * hh + 1] : s[m][hh + 1][2 * hh];
                const float lo = e ? s[m][hh][2 * hh + 1] : s[m][hh][2 * hh], hi = e ? s[m][hh + 2][2 * hh + 1] : s[m][hh + 2][2 * hh];
                c[hh] = sel ? lo : hi;
              }
              ua[m] = scale_bf2(pack2(a[0], a[1])); ub[m] = scale_bf2(pack2(c[0], c[1]));
              if (m == 0) { ua[0] = first ? (ua[0] & 0xFFFF0000u) | 0xFF80u : ua[0]; ub[0] = first && sel ? 0xFF80FF80u : ub[0]; }
              um[m] = max_bf2(ua[m], ub[m]);
            }
#pragma unroll
            for (int m = 0; m < 2; m++) um[m] = max_bf2(um[m], __shfl_xor_sync(~0u, um[m], 1));
#pragma unroll
            for (int m = 0; m < 2; m++) um[m] = max_bf2(um[m], __shfl_xor_sync(~0u, um[m], 2));
#pragma unroll
            for (int i = 0; i < 4; i++) {
              const int m = i >> 1;
              const float top = (i & 1) ? bf_hi(um[m]) : bf_lo(um[m]);
              va[i] = ex2((((i & 1) ? bf_hi(ua[m]) : bf_lo(ua[m])) - top) * 1.4426950408889634f);
              vb[i] = ex2((((i & 1) ? bf_hi(ub[m]) : bf_lo(ub[m])) - top) * 1.4426950408889634f);
              mx[i] = va[i] + vb[i];
            }
#pragma unroll
            for (int i = 0; i < 4; i++) mx[i] += __shfl_xor_sync(~0u, mx[i], 1);
#pragma unroll
            for (int i = 0; i < 4; i++) mx[i] += __shfl_xor_sync(~0u, mx[i], 2);
#pragma unroll
            for (int i = 0; i < 4; i++) {
              const int m = i >> 1, hh = i & 1;
              const float inv = rcp(mx[i]);
              const uint32_t t = pack2(va[i] * inv, vb[i] * inv);
              pf[m][hh][hh + 1] = __byte_perm(t, 0, pm_a); pf[m][hh][hh] = __byte_perm(t, 0, pm_lo); pf[m][hh][hh + 2] = __byte_perm(t, 0, pm_hi); pf[m][hh][3 - 3 * hh] = t & zero;
            }
#pragma unroll
            for (int m = 0; m < 2; m++) {
              float o[4][4];
#pragma unroll
              for (int j = 0; j < 4; j++) o[j][0] = o[j][1] = o[j][2] = o[j][3] = 0.f;
#pragma unroll
              for (int i = 0; i < 4; i++) {
                const int kk = i >> 1, jj = 2 * (i & 1);
                mma16816(o[jj], pf[m][0][2 * kk], pf[m][1][2 * kk], pf[m][0][2 * kk + 1], pf[m][1][2 * kk + 1], vf[m][i][0], vf[m][i][1]);
                mma16816(o[jj + 1], pf[m][0][2 * kk], pf[m][1][2 * kk], pf[m][0][2 * kk + 1], pf[m][1][2 * kk + 1], vf[m][i][2], vf[m][i][3]);
              }
              const float of[16] = {o[0][0], o[0][1], o[0][2], o[0][3], o[1][0], o[1][1], o[1][2], o[1][3], o[2][0], o[2][1], o[2][2], o[2][3], o[3][0], o[3][1], o[3][2], o[3][3]};
              put_o(h, m, of, 1.f, 1.f);
            }
            bar_arrive(NB_SIG + 2 * h + wg, 160);
            if (h == 0) {
              conv_kv(1);
              norm_tile(1, 0, q[0][0]); pack_b(1, 1, q[0][1]);
              bar_sync(NB_SC, 256);
            }
          }
        } else {
          auto conv_h = [&](int gi, int m, uint32_t (&t)[8]) {
            pack_h(gi, m, t);
            float d0[4] = {0.f, 0.f, 0.f, 0.f}, d1[4] = {0.f, 0.f, 0.f, 0.f};
            if (gi == 2) {
              mma16816h(d0, t[0], t[1], t[2], t[3], t[0], t[2]); mma16816h(d1, t[0], t[1], t[2], t[3], t[1], t[3]);
              mma16816h(d0, t[4], t[5], t[6], t[7], t[4], t[6]); mma16816h(d1, t[4], t[5], t[6], t[7], t[5], t[7]);
            } else {
#pragma unroll
              for (int i = 0; i < 8; i += 2) { mma1688h(d0, t[i], t[i + 1], t[i]); mma1688h(d1, t[i], t[i + 1], t[i + 1]); }
            }
            return f16_class(__reduce_max_sync(~0u, max(max(__float_as_int(d0[0]), __float_as_int(d0[1])), max(__float_as_int(d1[2]), __float_as_int(d1[3])))), K_LO);
          };
          uint32_t tk[8], tv[8];
          scale(2, 0, 1.f);
          uint32_t kn = conv_h(2, 0, tk);
          norm_tile(4, 0, tv);
          put_kv(0, 1, 0, tv);
          put_kn(0, 0, kn);
          if (kn == NOT_F16) pack_b(2, 0, tk);
          put_kv(0, 0, 0, tk);
          fence_async_smem();
          bar_arrive(NB_KV, 288);
          mbar_wait(sb + B_QF + 24, 1);
          scale(3, 0, 1.f); scale(0, 0, QSCALE); scale(1, 0, QSCALE);
          kn = conv_h(3, 0, tk);
#pragma unroll
          for (int i = 0; i < 4; i++) qn[i >> 1][i & 1] = conv_h(i >> 1, i & 1, q[i >> 1][i & 1]);
          norm_tile(5, 0, tv);
          if (max(max(max(qn[0][0], qn[0][1]), max(qn[1][0], qn[1][1])), kn) == NOT_F16) {
#pragma unroll
            for (int i = 0; i < 4; i++) if (qn[i >> 1][i & 1] == NOT_F16) pack_b(i >> 1, i & 1, q[i >> 1][i & 1]);
            if (kn == NOT_F16) pack_b(3, 0, tk);
          }
          fence_regs(tv);
          const bool elected = w == 0 && lane == 0;
          const uint64_t kd0 = mkdesc(sb + T0, 16, 512, 2);
          const uint64_t vd0 = mkdesc(sb + T0 + 16384, ONES - (T0 + 16384), 512, 2);
          constexpr uint64_t VSTEP = 64 - (64ull << 16);
          float o[2][20], SA[2][16];
          uint32_t SB[2][8], PA[4], PB[4];
          auto qk = [&](int b, int k, uint64_t d, int h = 0) {
            wgmma_m64n32k16_rs_nb_h(SA[b], q[h][0][4 * k], q[h][0][4 * k + 1], q[h][0][4 * k + 2], q[h][0][4 * k + 3], d + 2 * k, k ? 1 : zero);
            wgmma_m64n32k16_rs_nb_hh(SB[b], q[h][1][4 * k], q[h][1][4 * k + 1], q[h][1][4 * k + 2], q[h][1][4 * k + 3], d + 2 * k, k ? 1 : zero);
          };
          auto pv = [&](int m, const uint32_t (&Px)[4], uint64_t vd, int keep = 1) { wgmma_m64n40k16_rs_tb(o[m], Px[0], Px[1], Px[2], Px[3], vd, keep); };
          mbar_wait(sb + B_TF, 0);
#pragma unroll
          for (int i = 0; i < 4; i++) PA[i] = PB[i] = zero;
          wg_fence();
          wgmma_m64n40k16_rs_tb_z(o[0], PA[0], PA[1], PA[2], PA[3], vd0, 0); wgmma_m64n40k16_rs_tb_z(o[1], PB[0], PB[1], PB[2], PB[3], vd0 + VSTEP, 0);
#pragma unroll
          for (int b = 1; b >= 0; b--) {
            wgmma_m64n32k16_rs_nb_z_h(SA[b], q[0][0][0], q[0][0][1], q[0][0][2], q[0][0][3], kd0 + 128 * b, 0);
            wgmma_m64n32k16_rs_nb_z_hh(SB[b], q[0][1][0], q[0][1][1], q[0][1][2], q[0][1][3], kd0 + 128 * b, 0);
          }
          qk(0, 1, kd0); wg_commit();
          put_kv(1, 1, 0, tv); put_kv(1, 0, 0, tk); put_kn(1, 0, kn);
          fence_async_smem();
          bar_arrive(NB_KV + 12, 288);
          wg_wait<0>();
          fence_regs(SA[0]); fence_regs(SB[0]); fence_regs(SA[1]); fence_regs(SB[1]); fence_regs(o[0]); fence_regs(o[1]);
#pragma unroll 1
          for (int pass = 0; pass < 2; pass++) {
            uint32_t kc = (uint32_t)kd0, vc = (uint32_t)vd0, vp = (uint32_t)(vd0 + VSTEP);
#pragma unroll 1
            for (int it = 1; it <= 8; it++) {
              const uint32_t sn = it & 3, par = (it >> 2) & 1, kn = it < 8 ? (uint32_t)kd0 + sn * 2048 : kc;
              const uint64_t hi = kd0 & 0xFFFFFFFF00000000ull, kd = hi | kc, vd = hi | vc, kdn = hi | kn, vdp = hi | vp;
              kc = kn; vp = vc + (uint32_t)(16 * VSTEP); vc = (uint32_t)vd0 + sn * 32 * (uint32_t)VSTEP;
              bool landed = false;
#pragma unroll
              for (int r = 0; r < 16; r++) {
                const int c = r >> 1, ro = r & 1;
                if (r == 14 && !landed) mbar_wait(sb + B_TF + 8 * sn, par);
                wg_fence();
                qk(~c & 1, ro, c < 7 ? kd + (c + 1) * 128 : kdn);
                if (ro) wg_commit();
                const uint64_t vx = (r ? vd : vdp) + (r - 1) * VSTEP;
                const int keep = r ? 1 : it - 1;
                pv(0, PA, vx, keep); pv(1, PB, vx, keep);
                wg_commit();
                if (r == 12) landed = mbar_test(sb + B_TF + 8 * sn, par) || it == 8;
#pragma unroll
                for (int i = 0; i < 4; i++) {
                  PA[i] = pack2(ex2(SA[c & 1][8 * ro + 2 * i]), ex2(SA[c & 1][8 * ro + 2 * i + 1]));
                  PB[i] = exp2_h2(SB[c & 1][4 * ro + i]);
                }
                if (r == 15) wg_wait<0>(); else if (ro) wg_wait<1>();
                if (ro) { fence_regs(SA[~c & 1]); fence_regs(SB[~c & 1]); }
                if (r == 2 && elected && it > 1) mbar_arrive(sb + B_TE + 8 * ((sn + 2) & 3));
              }
            }
            int badm = 0;
            if (pass == 0) mbar_wait(sb + B_TF, 0);
            wg_fence();
            pv(0, PA, vd0 + 111 * VSTEP); pv(1, PB, vd0 + 111 * VSTEP); wg_commit();
            qk(0, 0, kd0, 1); qk(0, 1, kd0, 1); wg_commit();
            if (pass == 0) bar_sync(NB_KN + wg, 160);
            const float kmax = *(volatile float*)(smem + KMAX + 4 * pass);
            wg_wait<1>(); fence_regs(o[0]); fence_regs(o[1]);
            if (w == 0) e_arrive(sb + B_TE + 8 * 3);
#pragma unroll
            for (int m = 0; m < 2; m++) {
              const float of[16] = {o[m][0], o[m][1], o[m][2], o[m][3], o[m][4], o[m][5], o[m][6], o[m][7], o[m][8], o[m][9], o[m][10], o[m][11], o[m][12], o[m][13], o[m][14], o[m][15]};
              const uint32_t chk = put_o(pass, m, of, rcp(o[m][16]), rcp(o[m][18]));
              const bool bad = !(__uint_as_float(qn[0][m]) * kmax <= (m ? 0.875f * 0.875f : 112.f * 112.f)) || !(fminf(o[m][16], o[m][18]) >= 9.3e-10f) ||
                               !(o[m][16] + o[m][18] <= 3e38f) || ((chk + 0x00800080u) & 0x80008000u);
              badm |= __any_sync(~0u, bad) << m;
            }
            wg_wait<0>(); fence_regs(SA[0]); fence_regs(SB[0]);
            if (badm) {
#pragma unroll 1
              for (int m = 0; m < 2; m++) if ((badm >> m) & 1) {
                uint32_t qq[8]; float res[20];
#pragma unroll
                for (int i = 0; i < 8; i++) { qq[i] = m ? q[0][1][i] : q[0][0][i]; if ((m ? qn[0][1] : qn[0][0]) != NOT_F16) qq[i] = h2_to_bf2(qq[i]); }
                attn_slow(qq, m ? 128.f : 1.f, 2 * (cta_id() & 15) + pass, g_kn + ((l >> 1) * 128 + (cta_id() & 15) * 8) * 32 + 16 * pass, res, lane_id());
                const float of[16] = {res[0], res[1], res[2], res[3], res[4], res[5], res[6], res[7], res[8], res[9], res[10], res[11], res[12], res[13], res[14], res[15]};
                put_o(pass, m, of, rcp(res[16]), rcp(res[18]));
              }
            }
            bar_arrive(NB_SIG + 2 * pass + wg, 160);
            qn[0][0] = qn[1][0]; qn[0][1] = qn[1][1];
#pragma unroll
            for (int m = 0; m < 2; m++)
#pragma unroll
              for (int i = 0; i < 8; i++) q[0][m][i] = q[1][m][i];
#pragma unroll
            for (int i = 0; i < 4; i++) PA[i] = PB[i] = zero;
          }
        }
      }
      {
        float acc[64];
#pragma unroll
        for (int i = 0; i < 64; i++) acc[i] = 0.f;
        fence_regs(acc);
        uint32_t s = 0, lap = 0;
#pragma unroll 1
        for (int kt = 0; kt < 16; kt++) {
          mbar_wait(sb + B_PF + 8 * s, ((s < 4 ? l : 0) + lap) & 1);
          if (PST && kt == 16 - PST && wg != PWG) bar_sync(NB_SC, 256);
          const uint64_t da = mkdesc(sb + pslot_a(s, l) + wg * 8192, 16, 1024, 1), db = mkdesc(sb + pslot_b(s, l), 8192, 1024, 1);
          wg_fence();
#pragma unroll
          for (int k = 0; k < 4; k++) wgmma_m64n128k16_ss_tb(acc, da + k * 2, db + k * 128, 1);
          wg_commit();
          if (PST && kt == 15 && wg == PWG) bar_arrive(NB_SC, 256);
          wg_wait<1>();
          if (kt > 0 && w == 0) e_arrive_both(sb + B_PE + 8 * (s ? s - 1 : 5));
          if (++s == 6) { s = 0; lap++; }
        }
        IDS();
        const int g = lane >> 2, qd = lane & 3;
        const int r0 = wg * 64 + w * 16;
        const uint32_t r = r0 + (lane & 7) + ((lane >> 3) & 1) * 8;
        uint32_t x[8][4];
        mbar_wait(sb + B_RF, l & 1);
        mbar_wait(sb + B_PE + 8, l & 1);
#pragma unroll
        for (int jj = 0; jj < 8; jj++) ldsm4(sb + (jj >> 2) * 16384 + r * 128 + ((((2 * jj + (lane >> 4)) & 7) ^ (r & 7)) << 4), x[jj]);
        wg_wait<0>();
        fence_regs(acc);
        if (w == 0) e_arrive_both(sb + B_PE + 8 * 3);
        const CUtensorMap* mo = &prm.m[l == 3 ? M_OUT : M_XST];
#pragma unroll
        for (int jj = 0; jj < 8; jj++) {
#pragma unroll
          for (int i = 0; i < 4; i++) x[jj][i] = add_bf16x2(x[jj][i], pack2(acc[8 * jj + 2 * i], acc[8 * jj + 2 * i + 1]));
          stsm4(sb + (jj >> 2) * QSTG + po * 16384 + r * 128 + ((((2 * jj + (lane >> 4)) & 7) ^ (r & 7)) << 4), x[jj][0], x[jj][1], x[jj][2], x[jj][3]);
          if ((jj & 3) == 3) { fence_async_smem(); __syncwarp(); tma_st(mo, pn * 128 + (jj >> 2) * 64, pm * 128 + r0, sb + (jj >> 2) * QSTG + po * 16384 + r0 * 128); }
        }
        bulk_commit();
        if (l < 3) {
          bar_arrive(NB_X, 288);
          float s1[4] = {0.f, 0.f, 0.f, 0.f}, s2[4][4];
#pragma unroll
          for (int i = 0; i < 16; i++) s2[i >> 2][i & 3] = 0.f;
#pragma unroll
          for (int jj = 0; jj < 8; jj++) {
            mma16816(s1, x[jj][0], x[jj][1], x[jj][2], x[jj][3], 0x3f803f80u, 0x3f803f80u);
#pragma unroll
            for (int i = 0; i < 4; i++) mma1688(s2[i], x[jj][i & 2], x[jj][i | 1], x[jj][i]);
          }
          if (qd == (g >> 1)) {
            float2* sp = g_stats + pn * 2048 + pm * 128 + r0 + g;
            sp[0] = make_float2(s1[0], (g & 1) ? s2[0][1] + s2[2][1] : s2[0][0] + s2[2][0]);
            sp[8] = make_float2(s1[2], (g & 1) ? s2[1][3] + s2[3][3] : s2[1][2] + s2[3][2]);
          }
        }
        bulk_wait_n<0>();
        if (l < 3) bar_arrive(NB_X0, 352);
      }
    }
  }
  asm volatile("barrier.cluster.arrive.relaxed.aligned;\nbarrier.cluster.wait.aligned;" ::: "memory");
}

typedef CUresult (*EncodeFn)(CUtensorMap*, CUtensorMapDataType, cuuint32_t, void*, const cuuint64_t*, const cuuint64_t*, const cuuint32_t*,
                             const cuuint32_t*, CUtensorMapInterleave, CUtensorMapSwizzle, CUtensorMapL2promotion, CUtensorMapFloatOOBfill);

static void make_map(EncodeFn fn, CUtensorMap* m, const void* ptr, int rank, const uint64_t* dims, const uint64_t* strides, const uint32_t* box, CUtensorMapSwizzle sw) {
  cuuint64_t d[5], st[4];
  cuuint32_t bx[5], es[5];
  for (int i = 0; i < rank; i++) { d[i] = dims[i]; bx[i] = box[i]; es[i] = 1; if (i) st[i - 1] = strides[i - 1] * 2; }
  fn(m, CU_TENSOR_MAP_DATA_TYPE_BFLOAT16, rank, (void*)ptr, d, st, bx, es, CU_TENSOR_MAP_INTERLEAVE_NONE, sw,
     CU_TENSOR_MAP_L2_PROMOTION_L2_128B, CU_TENSOR_MAP_FLOAT_OOB_FILL_NONE);
}
static void map2(EncodeFn fn, CUtensorMap* m, const void* ptr, uint64_t inner, uint64_t outer, uint32_t bi, uint32_t bo, CUtensorMapSwizzle sw) {
  const uint64_t d[2] = {inner, outer}, st[1] = {inner};
  const uint32_t bx[2] = {bi, bo};
  make_map(fn, m, ptr, 2, d, st, bx, sw);
}

extern "C" void kernel_launch(void* const* d_in, const int* in_sizes, int n_in, void* d_out, int out_size) {
  (void)in_sizes; (void)n_in; (void)out_size;
  static EncodeFn enc = nullptr;
  static void *xs, *os, *kk, *vv, *ep;
  if (!enc) {
    void* p = nullptr;
    cudaDriverEntryPointQueryResult qr;
    cudaGetDriverEntryPoint("cuTensorMapEncodeTiled", &p, cudaEnableDefault, &qr);
    enc = (EncodeFn)p;
    cudaGetSymbolAddress(&xs, g_xs); cudaGetSymbolAddress(&os, g_os); cudaGetSymbolAddress(&kk, g_k); cudaGetSymbolAddress(&vv, g_v); cudaGetSymbolAddress(&ep, g_epoch);
    cudaFuncSetAttribute(fused_kernel, cudaFuncAttributeMaxDynamicSharedMemorySize, SMEM_BYTES);
  }
  Params prm;
  const CUtensorMapSwizzle S128 = CU_TENSOR_MAP_SWIZZLE_128B, S64 = CU_TENSOR_MAP_SWIZZLE_64B;
  map2(enc, &prm.m[M_X0A], d_in[0], 1024, 2048, 64, 256, S128);
  map2(enc, &prm.m[M_XSA], xs, 1024, 2048, 64, 256, S128);
  for (int t = 0; t < 2; t++) {
    const uint64_t d3[3] = {1024, 1024, 3}, s3[2] = {3072, 1024};
    const uint32_t b3[3] = {64, 64, 3};
    make_map(enc, &prm.m[M_WQA + t], d_in[1 + 3 * t], 3, d3, s3, b3, S128);
    const uint64_t d5[5] = {64, 32, 2, 16, 16}, s5[4] = {1024, 32 * 1024, 64 * 1024, 64};
    const uint32_t b5[5] = {64, 32, 1, 2, 2};
    make_map(enc, &prm.m[M_WOA + t], d_in[2 + 3 * t], 5, d5, s5, b5, S128);
    const uint64_t dr[3] = {64, 2048, 16}, sr[2] = {1024, 64};
    const uint32_t br[3] = {64, 128, 2};
    make_map(enc, &prm.m[M_X0R + t], t ? xs : d_in[0], 3, dr, sr, br, S128);
  }
  map2(enc, &prm.m[M_OS], os, 1024, 2048, 64, 64, S128);
  map2(enc, &prm.m[M_K], kk, 32, 65536, 32, 256, S64);
  map2(enc, &prm.m[M_V], vv, 32, 65536, 32, 256, S64);
  map2(enc, &prm.m[M_K4], kk, 32, 65536, 32, 64, S64);
  map2(enc, &prm.m[M_V4], vv, 32, 65536, 32, 64, S64);
  map2(enc, &prm.m[M_XSO], xs, 1024, 2048, 64, 128, S128);
  map2(enc, &prm.m[M_X0H], d_in[0], 1024, 2048, 64, 128, S128);
  map2(enc, &prm.m[M_XST], xs, 1024, 2048, 64, 16, S128);
  map2(enc, &prm.m[M_OUT], d_out, 1024, 2048, 64, 16, S128);
  prm.x0 = (const bf16*)d_in[0];
  prm.wq[0] = (const bf16*)d_in[1]; prm.wq[1] = (const bf16*)d_in[4];
  prm.wo[0] = (const bf16*)d_in[2]; prm.wo[1] = (const bf16*)d_in[5];
  prm.epoch = (uint32_t*)ep;
  prm.zero = 0;
  for (int i = 0; i < 128; i++) prm.map[i] = remap(i);
  fused_kernel<<<128, 384, SMEM_BYTES>>>(prm);
}
```

```cpp
#include <cuda_runtime.h>
#include <cuda_bf16.h>
#include <cuda.h>
#include <stdint.h>

typedef __nv_bfloat16 bf16;

__device__ __forceinline__ void wgmma_m64n192k16_ss_tb(float (&d)[96], uint64_t da, uint64_t db, int scale_d) {
  asm volatile("{\n.reg .pred p;\nsetp.ne.b32 p, %98, 0;\n"
    "wgmma.mma_async.sync.aligned.m64n192k16.f32.bf16.bf16 "
    "{%0, %1, %2, %3, %4, %5, %6, %7, %8, %9, %10, %11, %12, %13, %14, %15, "
    "%16, %17, %18, %19, %20, %21, %22, %23, %24, %25, %26, %27, %28, %29, %30, %31, "
    "%32, %33, %34, %35, %36, %37, %38, %39, %40, %41, %42, %43, %44, %45, %46, %47, "
    "%48, %49, %50, %51, %52, %53, %54, %55, %56, %57, %58, %59, %60, %61, %62, %63, "
    "%64, %65, %66, %67, %68, %69, %70, %71, %72, %73, %74, %75, %76, %77, %78, %79, "
    "%80, %81, %82, %83, %84, %85, %86, %87, %88, %89, %90, %91, %92, %93, %94, %95}, "
    "%96, %97, p, 1, 1, 0, 1;\n}\n"
    : "+f"(d[0]), "+f"(d[1]), "+f"(d[2]), "+f"(d[3]), "+f"(d[4]), "+f"(d[5]), "+f"(d[6]), "+f"(d[7]),
      "+f"(d[8]), "+f"(d[9]), "+f"(d[10]), "+f"(d[11]), "+f"(d[12]), "+f"(d[13]), "+f"(d[14]), "+f"(d[15]),
      "+f"(d[16]), "+f"(d[17]), "+f"(d[18]), "+f"(d[19]), "+f"(d[20]), "+f"(d[21]), "+f"(d[22]), "+f"(d[23]),
      "+f"(d[24]), "+f"(d[25]), "+f"(d[26]), "+f"(d[27]), "+f"(d[28]), "+f"(d[29]), "+f"(d[30]), "+f"(d[31]),
      "+f"(d[32]), "+f"(d[33]), "+f"(d[34]), "+f"(d[35]), "+f"(d[36]), "+f"(d[37]), "+f"(d[38]), "+f"(d[39]),
      "+f"(d[40]), "+f"(d[41]), "+f"(d[42]), "+f"(d[43]), "+f"(d[44]), "+f"(d[45]), "+f"(d[46]), "+f"(d[47]),
      "+f"(d[48]), "+f"(d[49]), "+f"(d[50]), "+f"(d[51]), "+f"(d[52]), "+f"(d[53]), "+f"(d[54]), "+f"(d[55]),
      "+f"(d[56]), "+f"(d[57]), "+f"(d[58]), "+f"(d[59]), "+f"(d[60]), "+f"(d[61]), "+f"(d[62]), "+f"(d[63]),
      "+f"(d[64]), "+f"(d[65]), "+f"(d[66]), "+f"(d[67]), "+f"(d[68]), "+f"(d[69]), "+f"(d[70]), "+f"(d[71]),
      "+f"(d[72]), "+f"(d[73]), "+f"(d[74]), "+f"(d[75]), "+f"(d[76]), "+f"(d[77]), "+f"(d[78]), "+f"(d[79]),
      "+f"(d[80]), "+f"(d[81]), "+f"(d[82]), "+f"(d[83]), "+f"(d[84]), "+f"(d[85]), "+f"(d[86]), "+f"(d[87]),
      "+f"(d[88]), "+f"(d[89]), "+f"(d[90]), "+f"(d[91]), "+f"(d[92]), "+f"(d[93]), "+f"(d[94]), "+f"(d[95])
    : "l"(da), "l"(db), "r"(scale_d));
}

__device__ __forceinline__ void wgmma_m64n128k16_ss_tb(float (&d)[64], uint64_t da, uint64_t db, int scale_d) {
  asm volatile("{\n.reg .pred p;\nsetp.ne.b32 p, %66, 0;\n"
    "wgmma.mma_async.sync.aligned.m64n128k16.f32.bf16.bf16 "
    "{%0, %1, %2, %3, %4, %5, %6, %7, %8, %9, %10, %11, %12, %13, %14, %15, "
    "%16, %17, %18, %19, %20, %21, %22, %23, %24, %25, %26, %27, %28, %29, %30, %31, "
    "%32, %33, %34, %35, %36, %37, %38, %39, %40, %41, %42, %43, %44, %45, %46, %47, "
    "%48, %49, %50, %51, %52, %53, %54, %55, %56, %57, %58, %59, %60, %61, %62, %63}, "
    "%64, %65, p, 1, 1, 0, 1;\n}\n"
    : "+f"(d[0]), "+f"(d[1]), "+f"(d[2]), "+f"(d[3]), "+f"(d[4]), "+f"(d[5]), "+f"(d[6]), "+f"(d[7]),
      "+f"(d[8]), "+f"(d[9]), "+f"(d[10]), "+f"(d[11]), "+f"(d[12]), "+f"(d[13]), "+f"(d[14]), "+f"(d[15]),
      "+f"(d[16]), "+f"(d[17]), "+f"(d[18]), "+f"(d[19]), "+f"(d[20]), "+f"(d[21]), "+f"(d[22]), "+f"(d[23]),
      "+f"(d[24]), "+f"(d[25]), "+f"(d[26]), "+f"(d[27]), "+f"(d[28]), "+f"(d[29]), "+f"(d[30]), "+f"(d[31]),
      "+f"(d[32]), "+f"(d[33]), "+f"(d[34]), "+f"(d[35]), "+f"(d[36]), "+f"(d[37]), "+f"(d[38]), "+f"(d[39]),
      "+f"(d[40]), "+f"(d[41]), "+f"(d[42]), "+f"(d[43]), "+f"(d[44]), "+f"(d[45]), "+f"(d[46]), "+f"(d[47]),
      "+f"(d[48]), "+f"(d[49]), "+f"(d[50]), "+f"(d[51]), "+f"(d[52]), "+f"(d[53]), "+f"(d[54]), "+f"(d[55]),
      "+f"(d[56]), "+f"(d[57]), "+f"(d[58]), "+f"(d[59]), "+f"(d[60]), "+f"(d[61]), "+f"(d[62]), "+f"(d[63])
    : "l"(da), "l"(db), "r"(scale_d));
}

__device__ __forceinline__ void wgmma_m64n32k16_rs_nb_h(float (&d)[16], uint32_t a0, uint32_t a1, uint32_t a2, uint32_t a3, uint64_t db, int scale_d) {
  asm volatile("{\n.reg .pred p;\nsetp.ne.b32 p, %21, 0;\n"
    "wgmma.mma_async.sync.aligned.m64n32k16.f32.f16.f16 "
    "{%0, %1, %2, %3, %4, %5, %6, %7, %8, %9, %10, %11, %12, %13, %14, %15}, "
    "{%16, %17, %18, %19}, %20, p, 1, 1, 0;\n}\n"
    : "+f"(d[0]), "+f"(d[1]), "+f"(d[2]), "+f"(d[3]), "+f"(d[4]), "+f"(d[5]), "+f"(d[6]), "+f"(d[7]),
      "+f"(d[8]), "+f"(d[9]), "+f"(d[10]), "+f"(d[11]), "+f"(d[12]), "+f"(d[13]), "+f"(d[14]), "+f"(d[15])
    : "r"(a0), "r"(a1), "r"(a2), "r"(a3), "l"(db), "r"(scale_d));
}

__device__ __forceinline__ void wgmma_m64n32k16_rs_nb_hh(uint32_t (&d)[8], uint32_t a0, uint32_t a1, uint32_t a2, uint32_t a3, uint64_t db, int scale_d) {
  asm volatile("{\n.reg .pred p;\nsetp.ne.b32 p, %13, 0;\n"
    "wgmma.mma_async.sync.aligned.m64n32k16.f16.f16.f16 "
    "{%0, %1, %2, %3, %4, %5, %6, %7}, "
    "{%8, %9, %10, %11}, %12, p, 1, 1, 0;\n}\n"
    : "+r"(d[0]), "+r"(d[1]), "+r"(d[2]), "+r"(d[3]), "+r"(d[4]), "+r"(d[5]), "+r"(d[6]), "+r"(d[7])
    : "r"(a0), "r"(a1), "r"(a2), "r"(a3), "l"(db), "r"(scale_d));
}

__device__ __forceinline__ void wgmma_m64n40k16_rs_tb(float (&d)[20], uint32_t a0, uint32_t a1, uint32_t a2, uint32_t a3, uint64_t db, int scale_d) {
  asm volatile("{\n.reg .pred p;\nsetp.ne.b32 p, %25, 0;\n"
    "wgmma.mma_async.sync.aligned.m64n40k16.f32.bf16.bf16 "
    "{%0, %1, %2, %3, %4, %5, %6, %7, %8, %9, %10, %11, %12, %13, %14, %15, "
    "%16, %17, %18, %19}, "
    "{%20, %21, %22, %23}, %24, p, 1, 1, 1;\n}\n"
    : "+f"(d[0]), "+f"(d[1]), "+f"(d[2]), "+f"(d[3]), "+f"(d[4]), "+f"(d[5]), "+f"(d[6]), "+f"(d[7]),
      "+f"(d[8]), "+f"(d[9]), "+f"(d[10]), "+f"(d[11]), "+f"(d[12]), "+f"(d[13]), "+f"(d[14]), "+f"(d[15]),
      "+f"(d[16]), "+f"(d[17]), "+f"(d[18]), "+f"(d[19])
    : "r"(a0), "r"(a1), "r"(a2), "r"(a3), "l"(db), "r"(scale_d));
}

__device__ __forceinline__ void wgmma_m64n40k16_rs_tb_z(float (&d)[20], uint32_t a0, uint32_t a1, uint32_t a2, uint32_t a3, uint64_t db, int scale_d) {
  asm volatile("{\n.reg .pred p;\nsetp.ne.b32 p, %25, 0;\n"
    "wgmma.mma_async.sync.aligned.m64n40k16.f32.bf16.bf16 "
    "{%0, %1, %2, %3, %4, %5, %6, %7, %8, %9, %10, %11, %12, %13, %14, %15, "
    "%16, %17, %18, %19}, "
    "{%20, %21, %22, %23}, %24, p, 1, 1, 1;\n}\n"
    : "=f"(d[0]), "=f"(d[1]), "=f"(d[2]), "=f"(d[3]), "=f"(d[4]), "=f"(d[5]), "=f"(d[6]), "=f"(d[7]),
      "=f"(d[8]), "=f"(d[9]), "=f"(d[10]), "=f"(d[11]), "=f"(d[12]), "=f"(d[13]), "=f"(d[14]), "=f"(d[15]),
      "=f"(d[16]), "=f"(d[17]), "=f"(d[18]), "=f"(d[19])
    : "r"(a0), "r"(a1), "r"(a2), "r"(a3), "l"(db), "r"(scale_d));
}

__device__ __forceinline__ void wgmma_m64n32k16_rs_nb_z_h(float (&d)[16], uint32_t a0, uint32_t a1, uint32_t a2, uint32_t a3, uint64_t db, int scale_d) {
  asm volatile("{\n.reg .pred p;\nsetp.ne.b32 p, %21, 0;\n"
    "wgmma.mma_async.sync.aligned.m64n32k16.f32.f16.f16 "
    "{%0, %1, %2, %3, %4, %5, %6, %7, %8, %9, %10, %11, %12, %13, %14, %15}, "
    "{%16, %17, %18, %19}, %20, p, 1, 1, 0;\n}\n"
    : "=f"(d[0]), "=f"(d[1]), "=f"(d[2]), "=f"(d[3]), "=f"(d[4]), "=f"(d[5]), "=f"(d[6]), "=f"(d[7]),
      "=f"(d[8]), "=f"(d[9]), "=f"(d[10]), "=f"(d[11]), "=f"(d[12]), "=f"(d[13]), "=f"(d[14]), "=f"(d[15])
    : "r"(a0), "r"(a1), "r"(a2), "r"(a3), "l"(db), "r"(scale_d));
}

__device__ __forceinline__ void wgmma_m64n32k16_rs_nb_z_hh(uint32_t (&d)[8], uint32_t a0, uint32_t a1, uint32_t a2, uint32_t a3, uint64_t db, int scale_d) {
  asm volatile("{\n.reg .pred p;\nsetp.ne.b32 p, %13, 0;\n"
    "wgmma.mma_async.sync.aligned.m64n32k16.f16.f16.f16 "
    "{%0, %1, %2, %3, %4, %5, %6, %7}, "
    "{%8, %9, %10, %11}, %12, p, 1, 1, 0;\n}\n"
    : "=r"(d[0]), "=r"(d[1]), "=r"(d[2]), "=r"(d[3]), "=r"(d[4]), "=r"(d[5]), "=r"(d[6]), "=r"(d[7])
    : "r"(a0), "r"(a1), "r"(a2), "r"(a3), "l"(db), "r"(scale_d));
}

#define DEVINL __device__ __forceinline__
DEVINL void wg_fence() { asm volatile("wgmma.fence.sync.aligned;" ::: "memory"); }
DEVINL void wg_commit() { asm volatile("wgmma.commit_group.sync.aligned;" ::: "memory"); }
template <int N> DEVINL void wg_wait() { asm volatile("wgmma.wait_group.sync.aligned %0;" ::"n"(N) : "memory"); }
DEVINL uint64_t mkdesc(uint32_t addr, uint32_t lbo, uint32_t sbo, int sw) {
  return (uint64_t)((addr & 0x3FFFF) >> 4) | ((uint64_t)(lbo >> 4) << 16) | ((uint64_t)(sbo >> 4) << 32) | ((uint64_t)sw << 62);
}
DEVINL void mbar_arrive(uint32_t bar) { asm volatile("mbarrier.arrive.shared::cta.b64 _, [%0];" ::"r"(bar) : "memory"); }
DEVINL bool mbar_try(uint32_t bar, uint32_t parity) {
  uint32_t ok;
  asm volatile("{\n.reg .pred p;\nmbarrier.try_wait.parity.shared::cta.b64 p, [%1], %2;\nselp.u32 %0, 1, 0, p;\n}" : "=r"(ok) : "r"(bar), "r"(parity) : "memory");
  return ok;
}
DEVINL bool mbar_test(uint32_t bar, uint32_t parity) {
  uint32_t ok;
  asm volatile("{\n.reg .pred p;\nmbarrier.test_wait.parity.shared::cta.b64 p, [%1], %2;\nselp.u32 %0, 1, 0, p;\n}" : "=r"(ok) : "r"(bar), "r"(parity) : "memory");
  return ok;
}
DEVINL void mbar_hint(uint32_t bar, uint32_t parity) {
#pragma unroll 1
  for (uint32_t n = 0; n < 16u; n++) if (mbar_try(bar, parity)) break;
}
DEVINL void mbar_wait(uint32_t bar, uint32_t parity) {
#pragma unroll 1
  for (uint32_t n = 0; n < 100000u; n++) if (mbar_try(bar, parity)) break;
}
DEVINL void mbar_wait_long(uint32_t bar, uint32_t parity) {
#pragma unroll 1
  for (uint32_t n = 0; n < 100000u; n++) {
    uint32_t ok;
    asm volatile("{\n.reg .pred p;\nmbarrier.try_wait.parity.shared::cta.b64 p, [%1], %2, %3;\nselp.u32 %0, 1, 0, p;\n}" : "=r"(ok) : "r"(bar), "r"(parity), "r"(4000) : "memory");
    if (ok) break;
  }
}
#define EL(txt) "{\n.reg .pred pe;\nelect.sync _|pe, 0xffffffff;\n@pe " txt "\n}"
DEVINL void e_expect_tx(uint32_t bar, uint32_t bytes) { asm volatile(EL("mbarrier.arrive.expect_tx.shared::cta.b64 _, [%0], %1;") ::"r"(bar), "r"(bytes) : "memory"); }
DEVINL void e_init(uint32_t bar, uint32_t cnt) { asm volatile(EL("mbarrier.init.shared::cta.b64 [%0], %1;") ::"r"(bar), "r"(cnt) : "memory"); }
DEVINL void e_arrive(uint32_t bar) { asm volatile(EL("mbarrier.arrive.shared::cta.b64 _, [%0];") ::"r"(bar) : "memory"); }
DEVINL void e_red(uint32_t* p) { asm volatile(EL("red.release.gpu.global.add.u32 [%0], 1;") ::"l"(p) : "memory"); }
DEVINL void e_red_relaxed(uint32_t* p) { asm volatile(EL("red.relaxed.gpu.global.add.u32 [%0], 1;") ::"l"(p) : "memory"); }
DEVINL void tma_ld(uint32_t dst, const CUtensorMap* m, int c0, int c1, uint32_t bar) {
  asm volatile(EL("cp.async.bulk.tensor.2d.shared::cluster.global.mbarrier::complete_tx::bytes [%0], [%1, {%3, %4}], [%2];")
               ::"r"(dst), "l"(m), "r"(bar), "r"(c0), "r"(c1) : "memory");
}
DEVINL void tma_ld3(uint32_t dst, const CUtensorMap* m, int c0, int c1, int c2, uint32_t bar) {
  asm volatile(EL("cp.async.bulk.tensor.3d.shared::cluster.global.mbarrier::complete_tx::bytes [%0], [%1, {%3, %4, %5}], [%2];")
               ::"r"(dst), "l"(m), "r"(bar), "r"(c0), "r"(c1), "r"(c2) : "memory");
}
DEVINL void tma_ld5(uint32_t dst, const CUtensorMap* m, int c2, int c3, int c4, uint32_t bar) {
  asm volatile(EL("cp.async.bulk.tensor.5d.shared::cluster.global.mbarrier::complete_tx::bytes [%0], [%1, {0, 0, %3, %4, %5}], [%2];")
               ::"r"(dst), "l"(m), "r"(bar), "r"(c2), "r"(c3), "r"(c4) : "memory");
}
DEVINL void tma_ld_mc(uint32_t dst, const CUtensorMap* m, int c0, int c1, uint32_t bar) {
  asm volatile(EL("cp.async.bulk.tensor.2d.shared::cluster.global.mbarrier::complete_tx::bytes.multicast::cluster [%0], [%1, {%3, %4}], [%2], %5;")
               ::"r"(dst), "l"(m), "r"(bar), "r"(c0), "r"(c1), "h"((uint16_t)3) : "memory");
}
DEVINL void e_arrive_both(uint32_t bar) {
  asm volatile("{\n.reg .pred pe;\n.reg .b32 r0, r1;\nelect.sync _|pe, 0xffffffff;\nmapa.shared::cluster.u32 r0, %0, 0;\nmapa.shared::cluster.u32 r1, %0, 1;\n"
               "@pe mbarrier.arrive.shared::cluster.b64 _, [r0];\n@pe mbarrier.arrive.shared::cluster.b64 _, [r1];\n}" ::"r"(bar) : "memory");
}
DEVINL void push_peer(uint32_t dst, uint32_t src, uint32_t bar, uint32_t peer) {
  asm volatile("{\n.reg .pred pe;\n.reg .b32 d, b;\nelect.sync _|pe, 0xffffffff;\nmapa.shared::cluster.u32 d, %0, %3;\nmapa.shared::cluster.u32 b, %2, %3;\n"
               "@pe cp.async.bulk.shared::cluster.shared::cta.mbarrier::complete_tx::bytes [d], [%1], 16384, [b];\n}" ::"r"(dst), "r"(src), "r"(bar), "r"(peer) : "memory");
}
DEVINL void tma_st(const CUtensorMap* m, int c0, int c1, uint32_t src) {
  asm volatile(EL("cp.async.bulk.tensor.2d.global.shared::cta.bulk_group [%0, {%2, %3}], [%1];") ::"l"(m), "r"(src), "r"(c0), "r"(c1) : "memory");
}
DEVINL void bulk_commit() { asm volatile("cp.async.bulk.commit_group;" ::: "memory"); }
template <int N> DEVINL void bulk_wait_n() { asm volatile("cp.async.bulk.wait_group %0;\nbar.warp.sync 0xffffffff;" ::"n"(N) : "memory"); }
DEVINL void l2_prefetch(const void* g, uint32_t bytes) { asm volatile(EL("cp.async.bulk.prefetch.L2.global [%0], %1;") ::"l"(g), "r"(bytes) : "memory"); }
DEVINL void fence_async_smem() { asm volatile("fence.proxy.async.shared::cta;" ::: "memory"); }
DEVINL void fence_async_gl() { asm volatile("fence.proxy.async.global;" ::: "memory"); }
DEVINL void cluster_wait() { asm volatile("barrier.cluster.wait.aligned;" ::: "memory"); }
DEVINL void bar_sync(int id, int n) { asm volatile("bar.sync %0, %1;" ::"r"(id), "r"(n) : "memory"); }
DEVINL void bar_arrive(int id, int n) { asm volatile("bar.arrive %0, %1;" ::"r"(id), "r"(n) : "memory"); }
DEVINL uint32_t ld_acquire(const uint32_t* p) { uint32_t v; asm volatile("ld.acquire.gpu.global.u32 %0, [%1];" : "=r"(v) : "l"(p) : "memory"); return v; }
DEVINL void watch(const uint32_t* p, uint32_t target, uint32_t all, uint32_t tag, uint32_t slot) {
  uint32_t seen = 0;
#pragma unroll 1
  for (uint32_t n = 0; n < 200000u && seen != all; n++) {
    const uint32_t m = __ballot_sync(~0u, (int)(ld_acquire(p) - target) >= 0) & all;
    if (m != seen) { seen = m; asm volatile("st.release.cta.shared.u32 [%0], %1;" ::"r"(slot), "r"(tag << 16 | m) : "memory"); }
  }
}
template <bool RELAXED = false> DEVINL void await_bit(uint32_t slot, uint32_t tag, int j, uint32_t& rdy) {
  if ((rdy >> j) & 1) return;
#pragma unroll 1
  for (uint32_t n = 0; n < 8000000u; n++) {
    uint32_t v;
    asm volatile("ld.acquire.cta.shared.u32 %0, [%1];" : "=r"(v) : "r"(slot) : "memory");
    if ((v >> 16) == tag && ((v >> j) & 1)) { rdy = v; break; }
    if (RELAXED) __nanosleep(200);
  }
  asm volatile("fence.proxy.async.global;" ::: "memory");
}
DEVINL void poll_ge(const uint32_t* p, uint32_t target) {
#pragma unroll 1
  for (uint32_t n = 0; n < 200000u; n++) if (__all_sync(~0u, (int)(ld_acquire(p) - target) >= 0)) break;
}
DEVINL int lane_id() { int v; asm volatile("mov.u32 %0, %%laneid;" : "=r"(v)); return v; }
__host__ DEVINL int remap(int v) {
  const int c = v >> 1, u = c - 36, r = (u * 37) >> 8;
  const int L = max(c - 4 + max(r + 1, 0), (c - 4) >> 31 & (32 + 8 * c));
  return 2 * L + (v & 1);
}
DEVINL int block_id() { int v; asm volatile("mov.u32 %0, %%ctaid.x;" : "=r"(v)); return v; }
#define cta_id() prm.map[block_id()]
#define IDS() const int lane = lane_id(), b = cta_id(), bm = b >> 4, bn = b & 15, rank = b & 1, pm = 2 * bm + (bn >> 3), pn = bn & 7, po = pm & 1; \
  (void)lane; (void)bm; (void)bn; (void)rank; (void)pm; (void)pn; (void)po
DEVINL void st_tagged(unsigned long long* p, uint32_t v, uint32_t tag) {
  asm volatile("{\n.reg .b64 t;\nmov.b64 t, {%1, %2};\nst.relaxed.gpu.global.b64 [%0], t;\n}" ::"l"(p), "r"(v), "r"(tag) : "memory");
}
DEVINL float ex2(float x) { float y; asm("ex2.approx.ftz.f32 %0, %1;" : "=f"(y) : "f"(x)); return y; }
DEVINL float rcp(float x) { float y; asm("rcp.approx.ftz.f32 %0, %1;" : "=f"(y) : "f"(x)); return y; }
DEVINL uint32_t pack2(float lo, float hi) { uint32_t r; asm("cvt.rn.bf16x2.f32 %0, %1, %2;" : "=r"(r) : "f"(hi), "f"(lo)); return r; }
DEVINL float bf_lo(uint32_t w) { return __uint_as_float(w << 16); }
DEVINL float bf_hi(uint32_t w) { return __uint_as_float(w & 0xFFFF0000u); }
DEVINL float bf_round(float x) { return bf_lo(pack2(x, 0.f)); }
DEVINL uint32_t add_bf16x2(uint32_t a, uint32_t b) { uint32_t r; asm("add.rn.bf16x2 %0, %1, %2;" : "=r"(r) : "r"(a), "r"(b)); return r; }
DEVINL uint32_t max_bf2(uint32_t a, uint32_t b) { uint32_t r; asm("max.bf16x2 %0, %1, %2;" : "=r"(r) : "r"(a), "r"(b)); return r; }
DEVINL uint32_t scale_bf2(uint32_t a) {
  uint32_t r;
  asm("{\n.reg .b32 t;\nmul.rn.bf16x2 t, %1, %3;\nfma.rn.bf16x2 %0, %1, %2, t;\n}" : "=r"(r) : "r"(a), "r"(0x3E353E35u), "r"(0x379E379Eu));
  return r;
}
DEVINL void stsm4(uint32_t addr, uint32_t a, uint32_t b, uint32_t c, uint32_t d) {
  asm volatile("stmatrix.sync.aligned.m8n8.x4.shared.b16 [%0], {%1, %2, %3, %4};" ::"r"(addr), "r"(a), "r"(b), "r"(c), "r"(d) : "memory");
}
DEVINL void ldsm4(uint32_t addr, uint32_t (&r)[4]) {
  asm volatile("ldmatrix.sync.aligned.m8n8.x4.shared.b16 {%0, %1, %2, %3}, [%4];" : "=r"(r[0]), "=r"(r[1]), "=r"(r[2]), "=r"(r[3]) : "r"(addr) : "memory");
}
DEVINL void ldsm4t(uint32_t addr, uint32_t (&r)[4]) {
  asm volatile("ldmatrix.sync.aligned.m8n8.x4.trans.shared.b16 {%0, %1, %2, %3}, [%4];" : "=r"(r[0]), "=r"(r[1]), "=r"(r[2]), "=r"(r[3]) : "r"(addr) : "memory");
}
DEVINL void sts128(uint32_t addr, uint32_t a, uint32_t b, uint32_t c, uint32_t d) {
  asm volatile("st.shared.v4.b32 [%0], {%1, %2, %3, %4};" ::"r"(addr), "r"(a), "r"(b), "r"(c), "r"(d) : "memory");
}
DEVINL float4 lds128f(uint32_t addr) { float4 v; asm volatile("ld.shared.v4.f32 {%0, %1, %2, %3}, [%4];" : "=f"(v.x), "=f"(v.y), "=f"(v.z), "=f"(v.w) : "r"(addr) : "memory"); return v; }
DEVINL float lds32f(uint32_t addr) { float v; asm volatile("ld.shared.f32 %0, [%1];" : "=f"(v) : "r"(addr) : "memory"); return v; }
DEVINL float2 lds64f(uint32_t addr) { float2 v; asm volatile("ld.shared.v2.f32 {%0, %1}, [%2];" : "=f"(v.x), "=f"(v.y) : "r"(addr) : "memory"); return v; }
DEVINL void mma16816(float (&d)[4], uint32_t a0, uint32_t a1, uint32_t a2, uint32_t a3, uint32_t b0, uint32_t b1) {
  asm("mma.sync.aligned.m16n8k16.row.col.f32.bf16.bf16.f32 {%0, %1, %2, %3}, {%4, %5, %6, %7}, {%8, %9}, {%0, %1, %2, %3};"
               : "+f"(d[0]), "+f"(d[1]), "+f"(d[2]), "+f"(d[3]) : "r"(a0), "r"(a1), "r"(a2), "r"(a3), "r"(b0), "r"(b1));
}
DEVINL void mma1688(float (&d)[4], uint32_t a0, uint32_t a1, uint32_t b0) {
  asm("mma.sync.aligned.m16n8k8.row.col.f32.bf16.bf16.f32 {%0, %1, %2, %3}, {%4, %5}, {%6}, {%0, %1, %2, %3};"
               : "+f"(d[0]), "+f"(d[1]), "+f"(d[2]), "+f"(d[3]) : "r"(a0), "r"(a1), "r"(b0));
}
DEVINL void mma1688h(float (&d)[4], uint32_t a0, uint32_t a1, uint32_t b0) {
  asm("mma.sync.aligned.m16n8k8.row.col.f32.f16.f16.f32 {%0, %1, %2, %3}, {%4, %5}, {%6}, {%0, %1, %2, %3};"
               : "+f"(d[0]), "+f"(d[1]), "+f"(d[2]), "+f"(d[3]) : "r"(a0), "r"(a1), "r"(b0));
}
DEVINL void mma16816h(float (&d)[4], uint32_t a0, uint32_t a1, uint32_t a2, uint32_t a3, uint32_t b0, uint32_t b1) {
  asm("mma.sync.aligned.m16n8k16.row.col.f32.f16.f16.f32 {%0, %1, %2, %3}, {%4, %5, %6, %7}, {%8, %9}, {%0, %1, %2, %3};"
               : "+f"(d[0]), "+f"(d[1]), "+f"(d[2]), "+f"(d[3]) : "r"(a0), "r"(a1), "r"(a2), "r"(a3), "r"(b0), "r"(b1));
}
template <int N> DEVINL void fence_regs(uint32_t (&d)[N]) {
#pragma unroll
  for (int i = 0; i < N; i++) asm volatile("" : "+r"(d[i])::"memory");
}
template <int N> DEVINL void fence_regs(float (&d)[N]) {
#pragma unroll
  for (int i = 0; i < N; i++) asm volatile("" : "+f"(d[i])::"memory");
}

__device__ __align__(1024) bf16 g_xs[2048 * 1024];
__device__ __align__(1024) bf16 g_os[2048 * 1024];
__device__ __align__(1024) bf16 g_k[32 * 2048 * 32];
__device__ __align__(1024) bf16 g_v[32 * 2048 * 32];
__device__ __align__(128) float2 g_stats[8 * 2048];
__device__ __align__(16) float g_csp[2 * 16 * 8 * 192];
__device__ __align__(128) float g_kn[2 * 128 * 32];
__device__ unsigned long long g_halo[2 * 128 * 32 * 32];
__device__ __align__(128) uint32_t g_cnt[256 * 32];
__device__ uint32_t g_epoch;

DEVINL uint32_t* cnt_x(int l, int bm) { return g_cnt + (l * 8 + bm) * 32; }
DEVINL uint32_t* cnt_o(int l, int pm, int h) { return g_cnt + (32 + (l * 16 + pm) * 2 + h) * 32; }
DEVINL uint32_t* cnt_kv(int lb, int bn) { return g_cnt + (160 + lb * 16 + bn) * 32; }
DEVINL uint32_t* cnt_ad(int bn) { return g_cnt + (192 + bn) * 32; }
DEVINL uint32_t* cnt_cs(int t, int bn) { return g_cnt + (208 + t * 16 + bn) * 32; }

DEVINL int qord(int i, int l, int pn) { return l == 0 ? i : i < 4 ? ((2 * pn) ^ (i & 2)) + (i & 1) : i - 4 < 2 * (pn & 6) ? i - 4 : i; }
DEVINL int pord(int i, int l, int p) { return (l & 1) || i > p ? i : i ? i - 1 : p; }
struct Params {
  CUtensorMap m[17];
  const bf16* x0;
  const bf16* wq[2];
  const bf16* wo[2];
  uint32_t* epoch;
  uint32_t zero;
  int map[128];
};
enum { M_X0A = 0, M_XSA, M_WQA, M_WQB, M_WOA, M_WOB, M_OS, M_K, M_V, M_X0R, M_XSR, M_XSO, M_OUT, M_XST, M_X0H, M_K4, M_V4, M_COUNT };

constexpr uint32_t QSTG = 57344;
constexpr uint32_t T0 = 65536, TSTG = 32768;
constexpr uint32_t ONES = 229376;
constexpr uint32_t PSTG = 32768;
constexpr uint32_t ASC = 17408;
constexpr uint32_t RSTD = 229376, MEAN = 230400, COLS = 230912, KMAX = 231680, B_QD = 231688, B_OW = 231704, BARS = 232192, SMEM_BYTES = 232448;
constexpr uint32_t B_QF = BARS, B_QE = BARS + 32, B_TF = BARS + 64, B_TE = BARS + 96, B_PF = BARS + 128, B_PE = BARS + 176,
                   B_RF = BARS + 224, W_X = BARS + 232, W_O = BARS + 236, B_QL = BARS + 240, B_PA = BARS + 248;
enum { NB_ST = 1, NB_KV = 2  , NB_DONE = 3, NB_SC = 4, NB_SIG = 5  , NB_KN = 9  , NB_X = 11, NB_HALO = 12  , NB_X0 = 15 };

DEVINL uint32_t pslot_b(uint32_t s, int l) { return ((((l & 1) ? 0x32DC45u : 0x468795u) >> (4 * s)) & 15) * 16384u; }
DEVINL uint32_t pslot_a(uint32_t s, int l) { return ((((l & 1) ? 0xBA8796u : 0x32DCBAu) >> (4 * s)) & 15) * 16384u; }

constexpr float QSCALE = 0.17677669529663687f * 1.4426950408889634f;

DEVINL uint32_t hfma2(uint32_t a, uint32_t b, uint32_t c) { uint32_t r; asm("fma.rn.f16x2 %0, %1, %2, %3;" : "=r"(r) : "r"(a), "r"(b), "r"(c)); return r; }
DEVINL uint32_t pack2h(float lo, float hi) { uint32_t r; asm("cvt.rn.f16x2.f32 %0, %1, %2;" : "=r"(r) : "f"(hi), "f"(lo)); return r; }
DEVINL uint32_t h2_to_bf2(uint32_t h) {
  float a, b;
  asm("{\n.reg .b16 l, h;\nmov.b32 {l, h}, %2;\ncvt.f32.f16 %0, l;\ncvt.f32.f16 %1, h;\n}" : "=f"(a), "=f"(b) : "r"(h));
  return pack2(a, b);
}
DEVINL uint32_t exp2_h2(uint32_t s) {
  const uint32_t r = hfma2(s, 0x00800080u, 0x007E007Eu);
  const uint32_t g = hfma2(hfma2(r, 0xF800F800u, 0x33FD33FDu), 0x44004400u, s);
  return __funnelshift_l(r, r, 7) + hfma2(hfma2(g, g, 0x0DE10DE1u), g, 0x00300030u);
}
constexpr uint32_t NOT_F16 = 0x7FC00000u, K_LO = 0x35000000u  ;
DEVINL uint32_t f16_class(uint32_t norm2, uint32_t lo) { return norm2 - lo > 0x4E800000u - lo ? NOT_F16 : norm2; }

DEVINL void attn_slow(const uint32_t (&q)[8], float up, int head, const float* kn, float (&res)[20], int lane) {
  const int g = lane >> 2, qd = lane & 3;
  const bf16* kb = g_k + (size_t)head * 2048 * 32;
  const bf16* vb = g_v + (size_t)head * 2048 * 32;
  float o[4][4], m0 = -INFINITY, m1 = -INFINITY, l0 = 0.f, l1 = 0.f;
#pragma unroll
  for (int j = 0; j < 4; j++) { o[j][0] = o[j][1] = o[j][2] = o[j][3] = 0.f; }
#pragma unroll 1
  for (int k0 = 0; k0 < 2048; k0 += 16) {
    float s[2][4];
    const bool kh = __float_as_uint(__ldcg(kn + (k0 >> 8) * 32 + ((k0 >> 6) & 1) * 8 + ((k0 >> 7) & 1) * 4 + ((k0 >> 4) & 3))) != NOT_F16;
#pragma unroll
    for (int nt = 0; nt < 2; nt++) {
      s[nt][0] = s[nt][1] = s[nt][2] = s[nt][3] = 0.f;
      const uint32_t* kp = (const uint32_t*)(kb + (size_t)(k0 + nt * 8 + g) * 32) + qd;
      uint32_t kf[4];
#pragma unroll
      for (int i = 0; i < 4; i++) { kf[i] = __ldcg(kp + 4 * i); if (kh) kf[i] = h2_to_bf2(kf[i]); }
      mma16816(s[nt], q[0], q[1], q[2], q[3], kf[0], kf[1]);
      mma16816(s[nt], q[4], q[5], q[6], q[7], kf[2], kf[3]);
      s[nt][0] *= up; s[nt][1] *= up; s[nt][2] *= up; s[nt][3] *= up;
    }
    float a0 = fmaxf(fmaxf(s[0][0], s[0][1]), fmaxf(s[1][0], s[1][1]));
    float a1 = fmaxf(fmaxf(s[0][2], s[0][3]), fmaxf(s[1][2], s[1][3]));
    a0 = fmaxf(a0, __shfl_xor_sync(~0u, a0, 1)); a0 = fmaxf(a0, __shfl_xor_sync(~0u, a0, 2));
    a1 = fmaxf(a1, __shfl_xor_sync(~0u, a1, 1)); a1 = fmaxf(a1, __shfl_xor_sync(~0u, a1, 2));
    const float n0 = fmaxf(m0, a0), n1 = fmaxf(m1, a1);
    const float c0 = (m0 == n0) ? 1.f : ex2(m0 - n0), c1 = (m1 == n1) ? 1.f : ex2(m1 - n1);
    m0 = n0; m1 = n1;
    const uint32_t p0 = pack2(ex2(s[0][0] - n0), ex2(s[0][1] - n0)), p1 = pack2(ex2(s[0][2] - n1), ex2(s[0][3] - n1));
    const uint32_t p2 = pack2(ex2(s[1][0] - n0), ex2(s[1][1] - n0)), p3 = pack2(ex2(s[1][2] - n1), ex2(s[1][3] - n1));
    l0 = l0 * c0 + bf_lo(p0) + bf_hi(p0) + bf_lo(p2) + bf_hi(p2);
    l1 = l1 * c1 + bf_lo(p1) + bf_hi(p1) + bf_lo(p3) + bf_hi(p3);
#pragma unroll
    for (int j = 0; j < 4; j++) {
      o[j][0] *= c0; o[j][1] *= c0; o[j][2] *= c1; o[j][3] *= c1;
      const unsigned short* vp = (const unsigned short*)(vb + (size_t)(k0 + 2 * qd) * 32 + j * 8 + g);
      const uint32_t b0 = (uint32_t)__ldcg(vp) | ((uint32_t)__ldcg(vp + 32) << 16);
      const uint32_t b1 = (uint32_t)__ldcg(vp + 256) | ((uint32_t)__ldcg(vp + 288) << 16);
      mma16816(o[j], p0, p1, p2, p3, b0, b1);
    }
  }
  l0 += __shfl_xor_sync(~0u, l0, 1); l0 += __shfl_xor_sync(~0u, l0, 2);
  l1 += __shfl_xor_sync(~0u, l1, 1); l1 += __shfl_xor_sync(~0u, l1, 2);
#pragma unroll
  for (int j = 0; j < 4; j++) { res[4 * j] = o[j][0]; res[4 * j + 1] = o[j][1]; res[4 * j + 2] = o[j][2]; res[4 * j + 3] = o[j][3]; }
  res[16] = l0; res[18] = l1;
}

__global__ void __cluster_dims__(2, 1, 1) __launch_bounds__(384, 1) fused_kernel(const __grid_constant__ Params prm) {
  extern __shared__ __align__(1024) char smem[];
  const uint32_t sb = (uint32_t)__cvta_generic_to_shared(smem);
  const int tid = threadIdx.x;
  const int wid = __shfl_sync(0xffffffffu, tid >> 5, 0), wg = wid >> 2, w = wid & 3;
  const int bm = remap(blockIdx.x) >> 4, bn = remap(blockIdx.x) & 15;
  auto first_tile = [&](int kt) {
    e_expect_tx(sb + B_QF + 8 * kt, QSTG);
    tma_ld(sb + kt * QSTG, &prm.m[M_X0A], kt * 64, bm * 256, sb + B_QF + 8 * kt);
    tma_ld3(sb + kt * QSTG + 32768, &prm.m[M_WQA], bn * 64, kt * 64, 0, sb + B_QF + 8 * kt);
  };
  if (wid == 8) {
    e_init(sb + B_QF, 1);
    asm volatile("fence.mbarrier_init.release.cluster;" ::: "memory");
    first_tile(0);
  }
  if (wid < 8) {
#pragma unroll
    for (int i = 0; i < 4; i++) {
      const uint32_t cnt = (uint32_t)((i == 0 ? 0x14112140 : i == 1 ? 0x04112141 : i == 2 ? 0x14412141 : 0x24412141) >> (4 * wid)) & 7;
      if (cnt) e_init(sb + BARS + 32 * wid + 8 * i, cnt);
    }
    if (wid < 3) e_init(sb + B_QD + wid * 8, wid < 2 ? 1 : 2);
    if (tid == 255) *(uint2*)(smem + W_X) = make_uint2(0u, 0u);
    asm volatile("fence.mbarrier_init.release.cluster;" ::: "memory");
  }
  const uint32_t epoch = *(volatile uint32_t*)prm.epoch;
  __syncthreads();
  asm volatile("barrier.cluster.arrive.relaxed.aligned;" ::: "memory");

  if (wg == 2) {
    asm volatile("setmaxnreg.dec.sync.aligned.u32 56;");
    const uint32_t ep1 = epoch + 1;
    if (w == 0) {
      first_tile(1);
      mbar_wait(sb + B_QF, 0);
      first_tile(2); first_tile(3);
#pragma unroll 1
      for (int kt = 4; kt < 16; kt++) l2_prefetch(prm.wq[0] + kt * 196608 + blockIdx.x * 1536, 3072);
      cluster_wait();
#pragma unroll 1
      for (int l = 0; l < 4; l++) {
        IDS();
        const CUtensorMap* mw = &prm.m[M_WQA + (l & 1)];
        const CUtensorMap* mh = &prm.m[l == 0 ? M_X0H : M_XSO];
        const CUtensorMap* mo = &prm.m[M_WOA + (l & 1)];
        auto q_b = [&](int i) {
          const int s = i & 3;
          mbar_wait(sb + B_QE + 8 * s, ((i >> 2) & 1) ^ 1);
          e_expect_tx(sb + B_QF + 8 * s, QSTG);
          tma_ld3(sb + s * QSTG + 32768, mw, bn * 64, qord(i, l, pn) * 64, 0, sb + B_QF + 8 * s);
        };
        uint32_t rdy = l ? 0u : ~0u;
        auto q_a = [&](int i) {
          const int kt = qord(i, l, pn);
          await_bit(sb + W_X, l, kt >> 1, rdy);
          tma_ld_mc(sb + (i & 3) * QSTG + rank * 16384, mh, kt * 64, bm * 256 + rank * 128, sb + B_QF + 8 * (i & 3));
        };
        if (l > 0) {
#pragma unroll 1
          for (int i = 0; i < 4; i++) {
            const int kt = qord(i, l, pn);
            await_bit(sb + W_X, l, kt >> 1, rdy);
            e_expect_tx(sb + B_QF + 8 * i, 16384);
            tma_ld(sb + i * QSTG + (po ^ 1) * 16384, &prm.m[M_XSO], kt * 64, (pm ^ 1) * 128, sb + B_QF + 8 * i);
          }
        }
#pragma unroll 1
        for (int i = 4; i < 16; i++) {
          q_b(i); q_a(i);
          if (l == 0 && i >= 8 && i < 12) l2_prefetch(prm.wq[1] + (blockIdx.x * 4 + i - 8) * 6144, 12288);
          if (l < 2 && i == 12) l2_prefetch(prm.wo[l] + blockIdx.x * 8192, 16384);
        }
        if (l & 1) {
          if (l == 3) poll_ge(cnt_ad(bn), ep1 * 16);
          const int krow = 2 * bn * 2048 + bm * 256;
          uint32_t* kvc = cnt_kv(l >> 1, bn);
#pragma unroll 1
          for (int m = 1; m >= 0; m--) {
            bar_sync(m ? NB_ST : NB_KV, 288);
#pragma unroll
            for (int i = 0; i < 4; i++) tma_st(&prm.m[M_K4 + (i >> 1)], 0, krow + (i & 1) * 128 + m * 64, sb + T0 + i * 8192 + m * 4096);
            if (m) {
              sts128(sb + ONES + lane * 32, 0x3f803f80u, 0x3f803f80u, 0x3f803f80u, 0x3f803f80u);
              sts128(sb + ONES + lane * 32 + 16, 0x3f803f80u, 0x3f803f80u, 0x3f803f80u, 0x3f803f80u);
              fence_async_smem();
              __syncwarp();
            }
          }
          e_arrive(sb + B_TF);
          bulk_commit(); bulk_wait_n<0>();
          e_red(kvc + bm);
          bar_sync(NB_KV + 12, 288);
          uint32_t seen = 0;
#pragma unroll 1
          for (int it = 1; it < 16; it++) {
            const int s = it & 3, blk = it;
            if (it == 4) { tma_st(&prm.m[M_K], 0, krow + 2048, sb); tma_st(&prm.m[M_V], 0, krow + 2048, sb + 16384); bulk_commit(); }
            if (it == 5) { bulk_wait_n<0>(); e_red(kvc + bm); }
            if (it == 12) { e_expect_tx(sb + B_RF, 32768); tma_ld3(sb, &prm.m[M_XSR], 0, pm * 128, 2 * pn, sb + B_RF); }
            if (it == 2 || it == 3) mbar_wait(sb + B_TF + 8 * (it - 1), 0);
            mbar_wait_long(sb + B_TE + 8 * s, ((it >> 2) & 1) ^ 1);
            if (it < 8) {
#pragma unroll 1
              for (uint32_t n = 0; n < 200000u && !((seen >> it) & 1); n++)
                seen = __ballot_sync(~0u, (int)(ld_acquire(kvc + ((bm + lane) & 7)) - (ep1 * 2 - 1)) >= 0);
              fence_async_gl();
            } else if (it == 8) { poll_ge(kvc + (lane & 7), ep1 * 2); fence_async_gl(); bar_arrive(NB_HALO, 64); }
            else if (it == 15) bar_arrive(NB_HALO + 1, 64);
            const int row = (2 * bn + (it >> 3)) * 2048 + ((bm + blk) & 7) * 256;
            e_expect_tx(sb + B_TF + 8 * s, 32768);
            tma_ld(sb + T0 + s * TSTG, &prm.m[M_K], 0, row, sb + B_TF + 8 * s);
            tma_ld(sb + T0 + s * TSTG + 16384, &prm.m[M_V], 0, row, sb + B_TF + 8 * s);
          }
        }
        auto p_b = [&](int i, uint32_t s, uint32_t par) {
          const int kt = pord(i, l, bn >> 1);
          mbar_wait(sb + B_PE + 8 * s, par ^ 1);
          e_expect_tx(sb + B_PF + 8 * s, PSTG);
          tma_ld5(sb + pslot_b(s, l), mo, kt >> 3, 2 * (kt & 7), 2 * pn, sb + B_PF + 8 * s);
        };
        auto p_a = [&](int i, uint32_t s) {
          const int kt = pord(i, l, bn >> 1);
          await_bit(sb + W_O, l + 1, kt, rdy);
          tma_ld_mc(sb + pslot_a(s, l) + rank * 8192, &prm.m[M_OS], kt * 64, pm * 128 + rank * 64, sb + B_PF + 8 * s);
        };
        auto p_a2 = [&](int i) {
          const int kt = pord(i, l, bn >> 1);
          await_bit(sb + W_O, l + 1, kt, rdy);
          tma_ld(sb + pslot_a(i, l), &prm.m[M_OS], kt * 64, pm * 128, sb + B_PF + 8 * i);
          tma_ld(sb + pslot_a(i, l) + 8192, &prm.m[M_OS], kt * 64, pm * 128 + 64, sb + B_PF + 8 * i);
        };
        rdy = 0;
        if (l & 1) {
#pragma unroll 1
          for (int u = 0; u < 6; u++) { const int i = (0x105432 >> (4 * u)) & 7; if (u == 4) mbar_wait_long(sb + B_TE, 1); p_b(i, i, i < 4 ? 1 : 0); }
#pragma unroll 1
          for (int u = 0; u < 6; u++) {
            const int i = (0x543120 >> (4 * u)) & 7;
            if (!(u & 1)) mbar_wait_long(sb + B_TE + 8 + 4 * u, 1);
            p_a2(i);
          }
        } else {
#pragma unroll 1
          for (int u = 0; u < 5; u++) { const int i = (0x32140 >> (4 * u)) & 7; if (!(u & 5)) mbar_wait(sb + B_QE + 8 + 4 * u, 1); p_b(i, i, 0); }
          mbar_wait(sb + B_QE + 24, 1);
          mbar_wait(sb + B_OW, (l >> 1) & 1);
          fence_async_gl();
          rdy = 1u << (bn >> 1);
#pragma unroll 1
          for (int i = 0; i < 4; i++) { p_a(i, i); }
          bar_sync(NB_DONE, 96);
          e_arrive_both(sb + B_PA);
          p_b(5, 5, 0);
          mbar_wait(sb + B_PA, (l >> 1) & 1);
          p_a(4, 4); p_a(5, 5);
        }
        uint32_t s = 0, lap = 1;
#pragma unroll 1
        for (int i = 6; i < 16; i++) {
          if (i == 12 && !(l & 1)) { e_expect_tx(sb + B_RF, 32768); tma_ld3(sb, &prm.m[l == 0 ? M_X0R : M_XSR], 0, pm * 128, 2 * pn, sb + B_RF); }
          p_b(i, s, ((s < 4 ? l : 0) + lap) & 1);
          p_a(i, s);
          if (++s == 6) { s = 0; lap++; }
        }
        const CUtensorMap* mn = &prm.m[M_WQA + ((l + 1) & 1)];
        if (l < 3) {
          mbar_wait(sb + B_PE + 8 * 4, 1); mbar_wait(sb + B_PE + 8 * 5, 1);
          tma_ld3(sb + 32768, mn, bn * 64, 2 * pn * 64, 0, sb + B_QL);
          mbar_wait(sb + B_PE + 8 * 0, l & 1);
          tma_ld3(sb + QSTG + 32768, mn, bn * 64, (2 * pn + 1) * 64, 0, sb + B_QL);
          mbar_wait(sb + B_PE + 8 * 1, l & 1);
          e_expect_tx(sb + B_QD, 40960);
          tma_ld3(sb + 2 * QSTG + 32768, mn, bn * 64, ((2 * pn) ^ 2) * 64, 0, sb + B_QD);
          bar_sync(NB_X, 288);
          e_expect_tx(sb + B_QL, 49152);
          e_expect_tx(sb + B_QD + 8, 40960);
          tma_ld3(sb + 3 * QSTG + 32768, mn, bn * 64, (((2 * pn) ^ 2) + 1) * 64, 0, sb + B_QD + 8);
        }
      }
      if (blockIdx.x == 0 && lane_id() == 0) *(volatile uint32_t*)prm.epoch = ep1;
    } else {
      const int hw = w - 1;
      if (hw == 1 && lane_id() < M_COUNT) asm volatile("prefetch.tensormap [%0];" ::"l"(&prm.m[lane_id()]) : "memory");
      cluster_wait();
      mbar_wait(sb + B_QF, 0);
#pragma unroll 1
      for (int l = 0; l < 4; l++) {
        IDS();
        if (hw == 2 && l > 0) watch(cnt_x(l, bm) + (lane & 7), ep1 * 2, 0xFFu, l, sb + W_X);
        if (l == 0) {
#pragma unroll 1
          for (int r = 2 * hw; r < 16; r += 6) {
            const uint4* p = (const uint4*)(prm.x0 + (size_t)(b * 16 + r) * 1024) + lane;
            float s1[2] = {0.f, 0.f}, s2[2] = {0.f, 0.f};
#pragma unroll
            for (int i = 0; i < 8; i++) {
              const uint4 v = __ldg(p + 32 * i);
              const uint32_t u[4] = {v.x, v.y, v.z, v.w};
#pragma unroll
              for (int k = 0; k < 4; k++) { const float a = bf_lo(u[k]), c = bf_hi(u[k]); s1[i >> 2] += a + c; s2[i >> 2] = fmaf(a, a, fmaf(c, c, s2[i >> 2])); }
            }
#pragma unroll
            for (int o = 16; o; o >>= 1)
#pragma unroll
              for (int rr = 0; rr < 2; rr++) { s1[rr] += __shfl_xor_sync(~0u, s1[rr], o); s2[rr] += __shfl_xor_sync(~0u, s2[rr], o); }
            if (lane == 0) *(float4*)&g_stats[b * 16 + r] = make_float4(s1[0], s2[0], s1[1], s2[1]);
          }
        }
        if (l == 1) { uint32_t rdy = 0; await_bit<true>(sb + W_X, 1, pn, rdy); mbar_hint(sb + B_QF + 8, 0); }
        if (l < 2) {
          float cs[8];
#pragma unroll
          for (int i = 0; i < 8; i++) cs[i] = 0.f;
          const uint4* wp = (const uint4*)(prm.wq[l] + (size_t)(bm * 128 + (lane >> 3)) * 3072 + hw * 1024 + bn * 64) + (lane & 7);
#pragma unroll 8
          for (int i = 0; i < 32; i++) {
            const uint4 v = __ldg(wp + (size_t)i * 4 * 384);
            cs[0] += bf_lo(v.x); cs[1] += bf_hi(v.x); cs[2] += bf_lo(v.y); cs[3] += bf_hi(v.y);
            cs[4] += bf_lo(v.z); cs[5] += bf_hi(v.z); cs[6] += bf_lo(v.w); cs[7] += bf_hi(v.w);
          }
#pragma unroll
          for (int i = 0; i < 8; i++) { cs[i] += __shfl_xor_sync(~0u, cs[i], 8); cs[i] += __shfl_xor_sync(~0u, cs[i], 16); }
          if (lane < 8) {
            float4* d = (float4*)(g_csp + ((l * 16 + bn) * 8 + bm) * 192 + hw * 64 + lane * 8);
            d[0] = make_float4(cs[0], cs[1], cs[2], cs[3]); d[1] = make_float4(cs[4], cs[5], cs[6], cs[7]);
          }
          __syncwarp();
          asm volatile("fence.acq_rel.gpu;" ::: "memory");
          e_red_relaxed(cnt_cs(l, bn));
          if (l == 0) e_red_relaxed(cnt_x(0, bm) + pn);
          poll_ge(lane < 8 && l == 0 ? cnt_x(0, bm) + lane : cnt_cs(l, bn), ep1 * (lane < 8 && l == 0 ? 6 : 24));
        }
        if (l > 0) {
          uint32_t rdy = 0;
#pragma unroll 1
          for (int j = 0; j < 8; j++) await_bit<true>(sb + W_X, l, j, rdy);
        }
#pragma unroll 1
        for (int it = hw * 32 + lane; it < 176; it += 96) {
          const bool rows = it < 128;
          const float4* p = rows ? (const float4*)(g_stats + bm * 256) + it : (const float4*)(g_csp + ((l & 1) * 16 + bn) * 8 * 192) + (it - 128);
          const int stride = rows ? 1024 : 48, np = rows && l == 0 ? 1 : 8;
          float4 a = make_float4(0.f, 0.f, 0.f, 0.f);
#pragma unroll
          for (int k = 0; k < 8; k++) if (k < np) { const float4 v = __ldcg(p + k * stride); a.x += v.x; a.y += v.y; a.z += v.z; a.w += v.w; }
          if (rows) {
            const float m0 = a.x * (1.f / 1024.f), m1 = a.z * (1.f / 1024.f);
            const float v0 = fmaxf(a.y * (1.f / 1024.f) - m0 * m0, 0.f), v1 = fmaxf(a.w * (1.f / 1024.f) - m1 * m1, 0.f);
            const float r0 = __fdividef(1.f, bf_round(sqrtf(bf_round(bf_round(v0) + 1e-5f)))), r1 = __fdividef(1.f, bf_round(sqrtf(bf_round(bf_round(v1) + 1e-5f))));
            *(float2*)(smem + RSTD + it * 8) = make_float2(r0, r1);
            *(uint32_t*)(smem + MEAN + it * 4) = pack2(-m0, -m1);
          } else {
            float2* d = (float2*)(smem + COLS) + ((it - 128) >> 2) * 8 + (it & 1) * 4 + ((it >> 1) & 1);
            d[0] = make_float2(a.y, a.x); d[2] = make_float2(a.w, a.z);
          }
        }
        __syncwarp();
        if (lane == 0) asm volatile("red.release.cta.shared.add.u32 [%0], 0x100;" ::"r"(sb + W_X) : "memory");
        if (hw == 2) {
          if (!(l & 1)) {
            bar_sync(NB_ST, 288);
            const volatile unsigned long long* hp = g_halo + ((size_t)(l >> 1) * 128 + b - 16) * 1024 + lane;
#pragma unroll 1
            for (int h = 0; h < 2; h++) {
              uint32_t t[16];
#pragma unroll
              for (int i = 0; i < 16; i++) t[i] = 0;
#pragma unroll 1
              for (uint32_t n = bm ? 0 : 100000u; n < 100000u; n++) {
                uint32_t miss = 0;
#pragma unroll
                for (int i = 0; i < 16; i++) {
                  const unsigned long long v = hp[h * 512 + i * 32];
                  t[i] = (uint32_t)v; miss |= (uint32_t)(v >> 32) ^ ep1;
                }
                if (__all_sync(~0u, !miss)) break;
              }
              const uint32_t r = (lane & 7) + ((lane >> 3) & 1) * 8, rv = lane >> 2;
#pragma unroll
              for (int jj = 0; jj < 2; jj++) stsm4(sb + 2 * h * ASC + r * 64 + (((2 * jj + (lane >> 4)) ^ ((r >> 1) & 3)) << 4), t[4 * jj], t[4 * jj + 1], t[4 * jj + 2], t[4 * jj + 3]);
              const uint32_t ad = sb + (2 * h + 1) * ASC + rv * 64 + (((lane & 3) ^ ((rv >> 1) & 3)) << 4);
              sts128(ad, t[8], t[10], t[12], t[14]); sts128(ad + 512, t[9], t[11], t[13], t[15]);
              bar_arrive(NB_HALO + h, 64);
            }
          } else {
            bar_sync(NB_HALO, 64);
            const uint4* kp = (const uint4*)(g_kn + ((l >> 1) * 128 + bn * 8) * 32) + 2 * lane;
            const uint4 v = __ldcg(kp), u = __ldcg(kp + 1);
            const uint32_t mx = max(max(max(v.x, v.y), max(v.z, v.w)), max(max(u.x, u.y), max(u.z, u.w)));
            const uint32_t m0 = __reduce_max_sync(~0u, (lane & 2) ? 0u : mx), m1 = __reduce_max_sync(~0u, (lane & 2) ? mx : 0u);
            if (lane == 0) *(uint2*)(smem + KMAX) = make_uint2(m0, m1);
            __syncwarp();
            bar_arrive(NB_KN, 160); bar_arrive(NB_KN + 1, 160);
            bar_sync(NB_HALO + 1, 64);
            watch(cnt_o(l, pm, 0) + (lane & 7), ep1 * 2, 0xFFu, l + 1, sb + W_O);
          }
        } else {
          bar_sync(NB_SIG + 2 * hw, 160); bar_sync(NB_SIG + 2 * hw + 1, 160);
          if (!(l & 1)) bar_arrive(NB_DONE, 96);
          if (hw == (l & 1)) bar_arrive((l & 1) ? NB_DONE : NB_KN, 64);
          asm volatile("fence.acq_rel.gpu;" ::: "memory");
          e_red_relaxed(cnt_o(l, 2 * bm, hw) + (bn >> 1));
          e_red_relaxed(cnt_o(l, 2 * bm + 1, hw) + (bn >> 1));
          if (hw == 0 && !(l & 1)) e_arrive_both(sb + B_OW);
          if (hw == 1 && l == 1) { e_red_relaxed(cnt_ad(bn)); e_red_relaxed(cnt_ad(bn)); }
        }
        if (hw == 2) { bar_sync((l & 1) ? NB_DONE : NB_KN, 64); watch(cnt_o(l, pm, (lane >> 3) & 1) + (lane & 7), ep1 * 2, 0xFFFFu, l + 1, sb + W_O); }
        if (l < 3) {
          bar_sync(NB_X0, 352);
          if (hw == 0) {
            e_red(cnt_x(l + 1, bm) + pn);
          } else if (hw == 1) {
            mbar_wait(sb + B_PE + 8 * 3, l & 1);
            push_peer(sb + 2 * QSTG + po * 16384, sb + po * 16384, sb + B_QD, rank ^ 1);
            push_peer(sb + 3 * QSTG + po * 16384, sb + QSTG + po * 16384, sb + B_QD + 8, rank ^ 1);
          }
        }
      }
    }
  } else {
    asm volatile("setmaxnreg.inc.sync.aligned.u32 224;");
    const uint32_t zero = prm.zero;
    cluster_wait();
    const uint32_t ep1 = __shfl_sync(~0u, epoch + 1, 0);
#pragma unroll 1
    for (int l = 0; l < 4; l++) {
      {
        float acc[2][96];
#pragma unroll
        for (int i = 0; i < 96; i++) { acc[0][i] = 0.f; acc[1][i] = 0.f; }
        fence_regs(acc[0]); fence_regs(acc[1]);
        const bool early = l > 0 && wg == ((cta_id() >> 3) & 1);
#pragma unroll 1
        for (int kt = 0; kt < 14; kt++) {
          const int s = kt & 3;
          if (l > 0 && kt < 4 && kt != 1) mbar_wait(sb + (kt ? B_QD - 16 + 8 * kt : B_QL), (l + 1) & 1);
          if (!(early && kt < 4)) mbar_wait(sb + B_QF + 8 * s, (kt >> 2) & 1);
          const uint64_t da = mkdesc(sb + s * QSTG + wg * 16384, 16, 1024, 1), db = mkdesc(sb + s * QSTG + 32768, 8192, 1024, 1);
          wg_fence();
#pragma unroll
          for (int k = 0; k < 4; k++)
#pragma unroll
            for (int m = 0; m < 2; m++) wgmma_m64n192k16_ss_tb(acc[m], da + m * 512 + k * 2, db + k * 128, 1);
          wg_commit();
          wg_wait<1>();
          if (early && kt < 5) {
#pragma unroll 1
            for (int i = kt == 3 ? 0 : 3; i < kt; i++) { mbar_wait(sb + B_QF + 8 * i, 0); if (w == 0) e_arrive_both(sb + B_QE + 8 * i); }
          } else if (kt > 0 && w == 0) e_arrive_both(sb + B_QE + 8 * ((kt - 1) & 3));
          if (kt == 11 + 2 * wg) {
#pragma unroll 1
            for (uint32_t n = 0; n < 4000000u; n++) {
              uint32_t v;
              asm volatile("ld.acquire.cta.shared.u32 %0, [%1];" : "=r"(v) : "r"(sb + W_X) : "memory");
              if ((v >> 8) == (uint32_t)(l * 256 + 3)) break;
            }
            const int lane = lane_id();
            float nm[4];
#pragma unroll
            for (int i = 0; i < 4; i++) nm[i] = bf_lo(*(volatile unsigned short*)(smem + MEAN + (wg * 128 + w * 16 + (lane >> 2) + (i >> 1) * 64 + (i & 1) * 8) * 2));
            wg_wait<0>();
            fence_regs(acc[0]); fence_regs(acc[1]);
#pragma unroll
            for (int j = 0; j < 12; j++) {
              const float4 c = lds128f(sb + COLS + j * 64 + (lane & 3) * 16);
#pragma unroll
              for (int m = 0; m < 2; m++) {
                float* a = &acc[m][8 * j];
                a[0] = fmaf(nm[2 * m], c.y, a[0]); a[1] = fmaf(nm[2 * m], c.x, a[1]); a[2] = fmaf(nm[2 * m + 1], c.y, a[2]); a[3] = fmaf(nm[2 * m + 1], c.x, a[3]);
                a[4] = fmaf(nm[2 * m], c.w, a[4]); a[5] = fmaf(nm[2 * m], c.z, a[5]); a[6] = fmaf(nm[2 * m + 1], c.w, a[6]); a[7] = fmaf(nm[2 * m + 1], c.z, a[7]);
              }
            }
            fence_regs(acc[0]); fence_regs(acc[1]);
          }
        }
        auto part = [&](int s, int m, int k0, int k1) {
          const uint64_t da = mkdesc(sb + s * QSTG + wg * 16384 + m * 8192, 16, 1024, 1), db = mkdesc(sb + s * QSTG + 32768, 8192, 1024, 1);
          wg_fence();
#pragma unroll
          for (int k = k0; k < k1; k++) wgmma_m64n192k16_ss_tb(acc[m], da + k * 2, db + k * 128, 1);
          wg_commit();
        };
        mbar_wait(sb + B_QF + 16, 1);
        part(2, 1, 0, 4);
        wg_wait<1>();
        if (w == 0) e_arrive_both(sb + B_QE + 8);
        if (!(l & 1)) bar_arrive(NB_ST, 288);
        mbar_wait(sb + B_QF + 24, 1);
        part(3, 1, 0, 4);
        part(2, 0, 0, 2);
        IDS();
        const int g = lane >> 2, qd = lane & 3;
        float rs[2][2];
#pragma unroll
        for (int i = 0; i < 4; i++) rs[i >> 1][i & 1] = lds32f(sb + RSTD + (wg * 128 + w * 16 + g + (i >> 1) * 64 + (i & 1) * 8) * 4);
        auto scale = [&](int gi, int m, float sc) {
          const float r0 = rs[m][0] * sc, r1 = rs[m][1] * sc;
#pragma unroll
          for (int i = 0; i < 16; i++) acc[m][16 * gi + i] *= (i & 2) ? r1 : r0;
        };
        auto pack_b = [&](int gi, int m, uint32_t (&t)[8]) {
#pragma unroll
          for (int i = 0; i < 8; i++) t[i] = pack2(acc[m][16 * gi + 2 * i], acc[m][16 * gi + 2 * i + 1]);
        };
        auto norm_tile = [&](int gi, int m, uint32_t (&t)[8]) { scale(gi, m, 1.f); pack_b(gi, m, t); };
        auto pack_h = [&](int gi, int m, uint32_t (&t)[8]) {
#pragma unroll
          for (int i = 0; i < 8; i++) t[i] = pack2h(acc[m][16 * gi + 2 * i], acc[m][16 * gi + 2 * i + 1]);
        };
        uint32_t q[2][2][8], qn[2][2];
        const uint32_t srow = (lane & 7) + ((lane >> 3) & 1) * 8;
        const uint32_t row0 = wg * 128 + w * 16;
        auto put_kv = [&](int h, int v, int m, const uint32_t (&t)[8]) {
          const uint32_t base = sb + ((l & 1) ? (h ? 0 : T0) + v * 16384 : (2 * h + v) * ASC + 1024) + (row0 + m * 64) * 64;
          if (!v) {
#pragma unroll
            for (int jj = 0; jj < 2; jj++) stsm4(base + srow * 64 + (((2 * jj + (lane >> 4)) ^ ((srow >> 1) & 3)) << 4), t[4 * jj], t[4 * jj + 1], t[4 * jj + 2], t[4 * jj + 3]);
          } else {
            const uint32_t ad = base + g * 64 + ((qd ^ (g >> 1)) << 4);
            sts128(ad, t[0], t[2], t[4], t[6]); sts128(ad + 512, t[1], t[3], t[5], t[7]);
          }
        };
        auto send_halo = [&](int h, int v, const uint32_t (&t)[8]) {
          unsigned long long* hp = g_halo + ((size_t)(l >> 1) * 128 + b) * 1024 + h * 512 + v * 256 + lane;
#pragma unroll
          for (int i = 0; i < 8; i++) st_tagged(hp + i * 32, t[i], ep1);
        };
        auto put_kn = [&](int h, int m, uint32_t kn) {
          if (lane == 0) g_kn[((l >> 1) * 128 + bn * 8 + bm) * 32 + 16 * h + 8 * m + wg * 4 + w] = __uint_as_float(kn);
        };
        auto conv_tile1 = [&](int h) {
          uint32_t t[8], tv[8], kn = NOT_F16;
          norm_tile(4 + h, 1, tv);
          put_kv(h, 1, 1, tv);
          scale(2 + h, 1, 1.f);
          part(2 + h, 0, 2, 4);
          if (l & 1) {
            float n[2] = {0.f, 0.f};
#pragma unroll
            for (int i = 0; i < 16; i++) n[(i >> 1) & 1] = fmaf(acc[1][32 + 16 * h + i], acc[1][32 + 16 * h + i], n[(i >> 1) & 1]);
            const float a = ((qd & 1) ? n[1] : n[0]) + __shfl_xor_sync(~0u, (qd & 1) ? n[0] : n[1], 1);
            scale(h, 1, QSCALE / 128.f);
            kn = f16_class(__reduce_max_sync(~0u, __float_as_uint(a + __shfl_xor_sync(~0u, a, 2))), K_LO);
            put_kn(h, 1, kn);
          } else scale(h, 1, 1.f);
          if (kn == NOT_F16) pack_b(2 + h, 1, t); else pack_h(2 + h, 1, t);
          put_kv(h, 0, 1, t);
          if (!(l & 1) && row0 == 176 && bm < 7) { send_halo(h, 0, t); send_halo(h, 1, tv); }
        };
        mbar_wait(sb + B_QE + 8, 1);
        wg_wait<1>();
        fence_regs(acc[1]);
        conv_tile1(0);
        part(3, 0, 0, 2);
        if (l & 1) { fence_async_smem(); bar_arrive(NB_ST, 288); }
        conv_tile1(1);
        wg_wait<2>();
        if (w == 0) e_arrive_both(sb + B_QE + 16);
        wg_wait<0>();
        fence_regs(acc[0]);
        if (w == 0) e_arrive_both(sb + B_QE + 24);
        bf16* const op0 = [&] { IDS(); return g_os + (size_t)(bm * 256 + row0 + (lane >> 2)) * 1024 + bn * 32 + (lane & 3) * 8; }();
        auto put_o = [&](int h, int m, const float (&o)[16], float i0, float i1) {
          bf16* op = op0 + m * 65536 + h * 512;
          const uint4 a = make_uint4(pack2(o[0] * i0, o[1] * i0), pack2(o[4] * i0, o[5] * i0), pack2(o[8] * i0, o[9] * i0), pack2(o[12] * i0, o[13] * i0));
          const uint4 c = make_uint4(pack2(o[2] * i1, o[3] * i1), pack2(o[6] * i1, o[7] * i1), pack2(o[10] * i1, o[11] * i1), pack2(o[14] * i1, o[15] * i1));
          *(uint4*)op = a; *(uint4*)(op + 8 * 1024) = c;
          const uint32_t hi = __vimax3_u16x2(__vimax3_u16x2(a.x, a.y, a.z), __vimax3_u16x2(a.w, c.x, c.y), __vmaxu2(c.z, c.w));
          const uint32_t lo = __vimax3_s16x2(__vimax3_s16x2(a.x, a.y, a.z), __vimax3_s16x2(a.w, c.x, c.y), __vmaxs2(c.z, c.w));
          return __vmaxu2(hi & 0x7FFF7FFFu, lo & 0x7FFF7FFFu);
        };
        if (!(l & 1)) {
          auto conv_kv = [&](int h) {
            uint32_t t[8];
            norm_tile(2 + h, 0, t); put_kv(h, 0, 0, t);
            norm_tile(4 + h, 0, t); put_kv(h, 1, 0, t);
          };
          conv_kv(0);
          norm_tile(0, 0, q[0][0]); pack_b(0, 1, q[0][1]);
          bar_sync(NB_SC, 256);
          const bool e = g & 1, sel = 2 * qd + (g & 1) >= g + 2, first = bm == 0 && row0 == 0;
          const uint32_t pm_a = e ? 0x1044 : 0x4410, pm_b = e ? 0x3244 : 0x4432, pm_lo = sel ? pm_b : 0x4444, pm_hi = sel ? 0x4444 : pm_b;
          const uint32_t ka = sb + (row0 + (lane & 7)) * 64 + (((lane >> 3) ^ ((lane >> 1) & 3)) << 4);
          const uint32_t va0 = sb + ASC + (row0 + srow) * 64 + (((lane >> 4) ^ ((lane >> 1) & 3)) << 4);
#pragma unroll 1
          for (int h = 0; h < 2; h++) {
            if (row0 == 0) bar_sync(NB_HALO + h, 64);
            float s[2][4][4];
            uint32_t vf[2][4][4], pf[2][2][4];
#pragma unroll
            for (int m = 0; m < 2; m++)
#pragma unroll
              for (int nt = 0; nt < 4; nt++) {
                uint32_t kf[4];
                ldsm4(ka + h * (2 * ASC) + (m * 64 + 8 * nt) * 64, kf);
                s[m][nt][0] = s[m][nt][1] = s[m][nt][2] = s[m][nt][3] = 0.f;
                mma16816(s[m][nt], q[0][m][0], q[0][m][1], q[0][m][2], q[0][m][3], kf[0], kf[1]);
                mma16816(s[m][nt], q[0][m][4], q[0][m][5], q[0][m][6], q[0][m][7], kf[2], kf[3]);
              }
#pragma unroll
            for (int m = 0; m < 2; m++)
#pragma unroll
              for (int i = 0; i < 4; i++) {
                ldsm4t(((va0 + h * (2 * ASC)) ^ (32 * (i & 1))) + (m * 64 + 16 * (i >> 1)) * 64, vf[m][i]);
              }
            float va[4], vb[4], mx[4];
            uint32_t ua[2], ub[2], um[2];
#pragma unroll
            for (int m = 0; m < 2; m++) {
              float a[2], c[2];
#pragma unroll
              for (int hh = 0; hh < 2; hh++) {
                a[hh] = e ? s[m][hh + 1][2 * hh + 1] : s[m][hh + 1][2 * hh];
                const float lo = e ? s[m][hh][2 * hh + 1] : s[m][hh][2 * hh], hi = e ? s[m][hh + 2][2 * hh + 1] : s[m][hh + 2][2 * hh];
                c[hh] = sel ? lo : hi;
              }
              ua[m] = scale_bf2(pack2(a[0], a[1])); ub[m] = scale_bf2(pack2(c[0], c[1]));
              if (m == 0) { ua[0] = first ? (ua[0] & 0xFFFF0000u) | 0xFF80u : ua[0]; ub[0] = first && sel ? 0xFF80FF80u : ub[0]; }
              um[m] = max_bf2(ua[m], ub[m]);
            }
#pragma unroll
            for (int m = 0; m < 2; m++) um[m] = max_bf2(um[m], __shfl_xor_sync(~0u, um[m], 1));
#pragma unroll
            for (int m = 0; m < 2; m++) um[m] = max_bf2(um[m], __shfl_xor_sync(~0u, um[m], 2));
#pragma unroll
            for (int i = 0; i < 4; i++) {
              const int m = i >> 1;
              const float top = (i & 1) ? bf_hi(um[m]) : bf_lo(um[m]);
              va[i] = ex2((((i & 1) ? bf_hi(ua[m]) : bf_lo(ua[m])) - top) * 1.4426950408889634f);
              vb[i] = ex2((((i & 1) ? bf_hi(ub[m]) : bf_lo(ub[m])) - top) * 1.4426950408889634f);
              mx[i] = va[i] + vb[i];
            }
#pragma unroll
            for (int i = 0; i < 4; i++) mx[i] += __shfl_xor_sync(~0u, mx[i], 1);
#pragma unroll
            for (int i = 0; i < 4; i++) mx[i] += __shfl_xor_sync(~0u, mx[i], 2);
#pragma unroll
            for (int i = 0; i < 4; i++) {
              const int m = i >> 1, hh = i & 1;
              const float inv = rcp(mx[i]);
              const uint32_t t = pack2(va[i] * inv, vb[i] * inv);
              pf[m][hh][hh + 1] = __byte_perm(t, 0, pm_a); pf[m][hh][hh] = __byte_perm(t, 0, pm_lo); pf[m][hh][hh + 2] = __byte_perm(t, 0, pm_hi); pf[m][hh][3 - 3 * hh] = t & zero;
            }
#pragma unroll
            for (int m = 0; m < 2; m++) {
              float o[4][4];
#pragma unroll
              for (int j = 0; j < 4; j++) o[j][0] = o[j][1] = o[j][2] = o[j][3] = 0.f;
#pragma unroll
              for (int i = 0; i < 4; i++) {
                const int kk = i >> 1, jj = 2 * (i & 1);
                mma16816(o[jj], pf[m][0][2 * kk], pf[m][1][2 * kk], pf[m][0][2 * kk + 1], pf[m][1][2 * kk + 1], vf[m][i][0], vf[m][i][1]);
                mma16816(o[jj + 1], pf[m][0][2 * kk], pf[m][1][2 * kk], pf[m][0][2 * kk + 1], pf[m][1][2 * kk + 1], vf[m][i][2], vf[m][i][3]);
              }
              const float of[16] = {o[0][0], o[0][1], o[0][2], o[0][3], o[1][0], o[1][1], o[1][2], o[1][3], o[2][0], o[2][1], o[2][2], o[2][3], o[3][0], o[3][1], o[3][2], o[3][3]};
              put_o(h, m, of, 1.f, 1.f);
            }
            bar_arrive(NB_SIG + 2 * h + wg, 160);
            if (h == 0) {
              conv_kv(1);
              norm_tile(1, 0, q[0][0]); pack_b(1, 1, q[0][1]);
              bar_sync(NB_SC, 256);
            }
          }
        } else {
          auto conv_h = [&](int gi, int m, uint32_t (&t)[8]) {
            pack_h(gi, m, t);
            float d0[4] = {0.f, 0.f, 0.f, 0.f}, d1[4] = {0.f, 0.f, 0.f, 0.f};
            if (gi == 2) {
              mma16816h(d0, t[0], t[1], t[2], t[3], t[0], t[2]); mma16816h(d1, t[0], t[1], t[2], t[3], t[1], t[3]);
              mma16816h(d0, t[4], t[5], t[6], t[7], t[4], t[6]); mma16816h(d1, t[4], t[5], t[6], t[7], t[5], t[7]);
            } else {
#pragma unroll
              for (int i = 0; i < 8; i += 2) { mma1688h(d0, t[i], t[i + 1], t[i]); mma1688h(d1, t[i], t[i + 1], t[i + 1]); }
            }
            return f16_class(__reduce_max_sync(~0u, max(max(__float_as_int(d0[0]), __float_as_int(d0[1])), max(__float_as_int(d1[2]), __float_as_int(d1[3])))), K_LO);
          };
          uint32_t tk[8], tv[8];
          scale(2, 0, 1.f);
          uint32_t kn = conv_h(2, 0, tk);
          norm_tile(4, 0, tv);
          put_kv(0, 1, 0, tv);
          put_kn(0, 0, kn);
          if (kn == NOT_F16) pack_b(2, 0, tk);
          put_kv(0, 0, 0, tk);
          fence_async_smem();
          bar_arrive(NB_KV, 288);
          mbar_wait(sb + B_QF + 24, 1);
          scale(3, 0, 1.f); scale(0, 0, QSCALE); scale(1, 0, QSCALE);
          kn = conv_h(3, 0, tk);
#pragma unroll
          for (int i = 0; i < 4; i++) qn[i >> 1][i & 1] = conv_h(i >> 1, i & 1, q[i >> 1][i & 1]);
          norm_tile(5, 0, tv);
          if (max(max(max(qn[0][0], qn[0][1]), max(qn[1][0], qn[1][1])), kn) == NOT_F16) {
#pragma unroll
            for (int i = 0; i < 4; i++) if (qn[i >> 1][i & 1] == NOT_F16) pack_b(i >> 1, i & 1, q[i >> 1][i & 1]);
            if (kn == NOT_F16) pack_b(3, 0, tk);
          }
          fence_regs(tv);
          const bool elected = w == 0 && lane == 0;
          const uint64_t kd0 = mkdesc(sb + T0, 16, 512, 2);
          const uint64_t vd0 = mkdesc(sb + T0 + 16384, ONES - (T0 + 16384), 512, 2);
          constexpr uint64_t VSTEP = 64 - (64ull << 16);
          float o[2][20], SA[2][16];
          uint32_t SB[2][8], PA[4], PB[4];
          auto qk = [&](int b, int k, uint64_t d, int h = 0) {
            wgmma_m64n32k16_rs_nb_h(SA[b], q[h][0][4 * k], q[h][0][4 * k + 1], q[h][0][4 * k + 2], q[h][0][4 * k + 3], d + 2 * k, k ? 1 : zero);
            wgmma_m64n32k16_rs_nb_hh(SB[b], q[h][1][4 * k], q[h][1][4 * k + 1], q[h][1][4 * k + 2], q[h][1][4 * k + 3], d + 2 * k, k ? 1 : zero);
          };
          auto pv = [&](int m, const uint32_t (&Px)[4], uint64_t vd, int keep = 1) { wgmma_m64n40k16_rs_tb(o[m], Px[0], Px[1], Px[2], Px[3], vd, keep); };
          mbar_wait(sb + B_TF, 0);
#pragma unroll
          for (int i = 0; i < 4; i++) PA[i] = PB[i] = zero;
          wg_fence();
          wgmma_m64n40k16_rs_tb_z(o[0], PA[0], PA[1], PA[2], PA[3], vd0, 0); wgmma_m64n40k16_rs_tb_z(o[1], PB[0], PB[1], PB[2], PB[3], vd0 + VSTEP, 0);
#pragma unroll
          for (int b = 1; b >= 0; b--) {
            wgmma_m64n32k16_rs_nb_z_h(SA[b], q[0][0][0], q[0][0][1], q[0][0][2], q[0][0][3], kd0 + 128 * b, 0);
            wgmma_m64n32k16_rs_nb_z_hh(SB[b], q[0][1][0], q[0][1][1], q[0][1][2], q[0][1][3], kd0 + 128 * b, 0);
          }
          qk(0, 1, kd0); wg_commit();
          put_kv(1, 1, 0, tv); put_kv(1, 0, 0, tk); put_kn(1, 0, kn);
          fence_async_smem();
          bar_arrive(NB_KV + 12, 288);
          wg_wait<0>();
          fence_regs(SA[0]); fence_regs(SB[0]); fence_regs(SA[1]); fence_regs(SB[1]); fence_regs(o[0]); fence_regs(o[1]);
#pragma unroll 1
          for (int pass = 0; pass < 2; pass++) {
            uint32_t kc = (uint32_t)kd0, vc = (uint32_t)vd0, vp = (uint32_t)(vd0 + VSTEP);
#pragma unroll 1
            for (int it = 1; it <= 8; it++) {
              const uint32_t sn = it & 3, par = (it >> 2) & 1, kn = it < 8 ? (uint32_t)kd0 + sn * 2048 : kc;
              const uint64_t hi = kd0 & 0xFFFFFFFF00000000ull, kd = hi | kc, vd = hi | vc, kdn = hi | kn, vdp = hi | vp;
              kc = kn; vp = vc + (uint32_t)(16 * VSTEP); vc = (uint32_t)vd0 + sn * 32 * (uint32_t)VSTEP;
              bool landed = false;
#pragma unroll
              for (int r = 0; r < 16; r++) {
                const int c = r >> 1, ro = r & 1;
                if (r == 14 && !landed) mbar_wait(sb + B_TF + 8 * sn, par);
                wg_fence();
                qk(~c & 1, ro, c < 7 ? kd + (c + 1) * 128 : kdn);
                if (ro) wg_commit();
                const uint64_t vx = (r ? vd : vdp) + (r - 1) * VSTEP;
                const int keep = r ? 1 : it - 1;
                pv(0, PA, vx, keep); pv(1, PB, vx, keep);
                wg_commit();
                if (r == 12) landed = mbar_test(sb + B_TF + 8 * sn, par) || it == 8;
#pragma unroll
                for (int i = 0; i < 4; i++) {
                  PA[i] = pack2(ex2(SA[c & 1][8 * ro + 2 * i]), ex2(SA[c & 1][8 * ro + 2 * i + 1]));
                  PB[i] = exp2_h2(SB[c & 1][4 * ro + i]);
                }
                if (r == 15) wg_wait<0>(); else if (ro) wg_wait<1>();
                if (ro) { fence_regs(SA[~c & 1]); fence_regs(SB[~c & 1]); }
                if (r == 2 && elected && it > 1) mbar_arrive(sb + B_TE + 8 * ((sn + 2) & 3));
              }
            }
            int badm = 0;
            if (pass == 0) mbar_wait(sb + B_TF, 0);
            wg_fence();
            pv(0, PA, vd0 + 111 * VSTEP); pv(1, PB, vd0 + 111 * VSTEP); wg_commit();
            qk(0, 0, kd0, 1); qk(0, 1, kd0, 1); wg_commit();
            if (pass == 0) bar_sync(NB_KN + wg, 160);
            const float kmax = *(volatile float*)(smem + KMAX + 4 * pass);
            wg_wait<1>(); fence_regs(o[0]); fence_regs(o[1]);
            if (w == 0) e_arrive(sb + B_TE + 8 * 3);
#pragma unroll
            for (int m = 0; m < 2; m++) {
              const float of[16] = {o[m][0], o[m][1], o[m][2], o[m][3], o[m][4], o[m][5], o[m][6], o[m][7], o[m][8], o[m][9], o[m][10], o[m][11], o[m][12], o[m][13], o[m][14], o[m][15]};
              const uint32_t chk = put_o(pass, m, of, rcp(o[m][16]), rcp(o[m][18]));
              const bool bad = !(__uint_as_float(qn[0][m]) * kmax <= (m ? 0.875f * 0.875f : 112.f * 112.f)) || !(fminf(o[m][16], o[m][18]) >= 9.3e-10f) ||
                               !(o[m][16] + o[m][18] <= 3e38f) || ((chk + 0x00800080u) & 0x80008000u);
              badm |= __any_sync(~0u, bad) << m;
            }
            wg_wait<0>(); fence_regs(SA[0]); fence_regs(SB[0]);
            if (badm) {
#pragma unroll 1
              for (int m = 0; m < 2; m++) if ((badm >> m) & 1) {
                uint32_t qq[8]; float res[20];
#pragma unroll
                for (int i = 0; i < 8; i++) { qq[i] = m ? q[0][1][i] : q[0][0][i]; if ((m ? qn[0][1] : qn[0][0]) != NOT_F16) qq[i] = h2_to_bf2(qq[i]); }
                attn_slow(qq, m ? 128.f : 1.f, 2 * (cta_id() & 15) + pass, g_kn + ((l >> 1) * 128 + (cta_id() & 15) * 8) * 32 + 16 * pass, res, lane_id());
                const float of[16] = {res[0], res[1], res[2], res[3], res[4], res[5], res[6], res[7], res[8], res[9], res[10], res[11], res[12], res[13], res[14], res[15]};
                put_o(pass, m, of, rcp(res[16]), rcp(res[18]));
              }
            }
            bar_arrive(NB_SIG + 2 * pass + wg, 160);
            qn[0][0] = qn[1][0]; qn[0][1] = qn[1][1];
#pragma unroll
            for (int m = 0; m < 2; m++)
#pragma unroll
              for (int i = 0; i < 8; i++) q[0][m][i] = q[1][m][i];
#pragma unroll
            for (int i = 0; i < 4; i++) PA[i] = PB[i] = zero;
          }
        }
      }
      {
        float acc[64];
#pragma unroll
        for (int i = 0; i < 64; i++) acc[i] = 0.f;
        fence_regs(acc);
        uint32_t s = 0, lap = 0;
#pragma unroll 1
        for (int kt = 0; kt < 16; kt++) {
          mbar_wait(sb + B_PF + 8 * s, ((s < 4 ? l : 0) + lap) & 1);
          const uint64_t da = mkdesc(sb + pslot_a(s, l) + wg * 8192, 16, 1024, 1), db = mkdesc(sb + pslot_b(s, l), 8192, 1024, 1);
          wg_fence();
#pragma unroll
          for (int k = 0; k < 4; k++) wgmma_m64n128k16_ss_tb(acc, da + k * 2, db + k * 128, 1);
          wg_commit();
          wg_wait<1>();
          if (kt > 0 && w == 0) e_arrive_both(sb + B_PE + 8 * (s ? s - 1 : 5));
          if (++s == 6) { s = 0; lap++; }
        }
        IDS();
        const int g = lane >> 2, qd = lane & 3;
        const int r0 = wg * 64 + w * 16;
        const uint32_t r = r0 + (lane & 7) + ((lane >> 3) & 1) * 8;
        uint32_t x[8][4];
        mbar_wait(sb + B_RF, l & 1);
        mbar_wait(sb + B_PE + 8, l & 1);
#pragma unroll
        for (int jj = 0; jj < 8; jj++) ldsm4(sb + (jj >> 2) * 16384 + r * 128 + ((((2 * jj + (lane >> 4)) & 7) ^ (r & 7)) << 4), x[jj]);
        wg_wait<0>();
        fence_regs(acc);
        if (w == 0) e_arrive_both(sb + B_PE + 8 * 3);
        const CUtensorMap* mo = &prm.m[l == 3 ? M_OUT : M_XST];
#pragma unroll
        for (int jj = 0; jj < 8; jj++) {
#pragma unroll
          for (int i = 0; i < 4; i++) x[jj][i] = add_bf16x2(x[jj][i], pack2(acc[8 * jj + 2 * i], acc[8 * jj + 2 * i + 1]));
          stsm4(sb + (jj >> 2) * QSTG + po * 16384 + r * 128 + ((((2 * jj + (lane >> 4)) & 7) ^ (r & 7)) << 4), x[jj][0], x[jj][1], x[jj][2], x[jj][3]);
          if ((jj & 3) == 3) { fence_async_smem(); __syncwarp(); tma_st(mo, pn * 128 + (jj >> 2) * 64, pm * 128 + r0, sb + (jj >> 2) * QSTG + po * 16384 + r0 * 128); }
        }
        bulk_commit();
        if (l < 3) {
          float s1[4] = {0.f, 0.f, 0.f, 0.f}, s2[4][4];
#pragma unroll
          for (int i = 0; i < 16; i++) s2[i >> 2][i & 3] = 0.f;
#pragma unroll
          for (int jj = 0; jj < 8; jj++) {
            mma16816(s1, x[jj][0], x[jj][1], x[jj][2], x[jj][3], 0x3f803f80u, 0x3f803f80u);
#pragma unroll
            for (int i = 0; i < 4; i++) mma1688(s2[i], x[jj][i & 2], x[jj][i | 1], x[jj][i]);
          }
          if (qd == (g >> 1)) {
            float2* sp = g_stats + pn * 2048 + pm * 128 + r0 + g;
            sp[0] = make_float2(s1[0], (g & 1) ? s2[0][1] + s2[2][1] : s2[0][0] + s2[2][0]);
            sp[8] = make_float2(s1[2], (g & 1) ? s2[1][3] + s2[3][3] : s2[1][2] + s2[3][2]);
          }
          __syncwarp();
          bar_arrive(NB_X, 288);
        }
        bulk_wait_n<0>();
        if (l < 3) bar_arrive(NB_X0, 352);
      }
    }
  }
  asm volatile("barrier.cluster.arrive.relaxed.aligned;\nbarrier.cluster.wait.aligned;" ::: "memory");
}

typedef CUresult (*EncodeFn)(CUtensorMap*, CUtensorMapDataType, cuuint32_t, void*, const cuuint64_t*, const cuuint64_t*, const cuuint32_t*,
                             const cuuint32_t*, CUtensorMapInterleave, CUtensorMapSwizzle, CUtensorMapL2promotion, CUtensorMapFloatOOBfill);

static void make_map(EncodeFn fn, CUtensorMap* m, const void* ptr, int rank, const uint64_t* dims, const uint64_t* strides, const uint32_t* box, CUtensorMapSwizzle sw) {
  cuuint64_t d[5], st[4];
  cuuint32_t bx[5], es[5];
  for (int i = 0; i < rank; i++) { d[i] = dims[i]; bx[i] = box[i]; es[i] = 1; if (i) st[i - 1] = strides[i - 1] * 2; }
  fn(m, CU_TENSOR_MAP_DATA_TYPE_BFLOAT16, rank, (void*)ptr, d, st, bx, es, CU_TENSOR_MAP_INTERLEAVE_NONE, sw,
     CU_TENSOR_MAP_L2_PROMOTION_L2_128B, CU_TENSOR_MAP_FLOAT_OOB_FILL_NONE);
}
static void map2(EncodeFn fn, CUtensorMap* m, const void* ptr, uint64_t inner, uint64_t outer, uint32_t bi, uint32_t bo, CUtensorMapSwizzle sw) {
  const uint64_t d[2] = {inner, outer}, st[1] = {inner};
  const uint32_t bx[2] = {bi, bo};
  make_map(fn, m, ptr, 2, d, st, bx, sw);
}

extern "C" void kernel_launch(void* const* d_in, const int* in_sizes, int n_in, void* d_out, int out_size) {
  (void)in_sizes; (void)n_in; (void)out_size;
  static EncodeFn enc = nullptr;
  static void *xs, *os, *kk, *vv, *ep;
  if (!enc) {
    void* p = nullptr;
    cudaDriverEntryPointQueryResult qr;
    cudaGetDriverEntryPoint("cuTensorMapEncodeTiled", &p, cudaEnableDefault, &qr);
    enc = (EncodeFn)p;
    cudaGetSymbolAddress(&xs, g_xs); cudaGetSymbolAddress(&os, g_os); cudaGetSymbolAddress(&kk, g_k); cudaGetSymbolAddress(&vv, g_v); cudaGetSymbolAddress(&ep, g_epoch);
    cudaFuncSetAttribute(fused_kernel, cudaFuncAttributeMaxDynamicSharedMemorySize, SMEM_BYTES);
  }
  Params prm;
  const CUtensorMapSwizzle S128 = CU_TENSOR_MAP_SWIZZLE_128B, S64 = CU_TENSOR_MAP_SWIZZLE_64B;
  map2(enc, &prm.m[M_X0A], d_in[0], 1024, 2048, 64, 256, S128);
  map2(enc, &prm.m[M_XSA], xs, 1024, 2048, 64, 256, S128);
  for (int t = 0; t < 2; t++) {
    const uint64_t d3[3] = {1024, 1024, 3}, s3[2] = {3072, 1024};
    const uint32_t b3[3] = {64, 64, 3};
    make_map(enc, &prm.m[M_WQA + t], d_in[1 + 3 * t], 3, d3, s3, b3, S128);
    const uint64_t d5[5] = {64, 32, 2, 16, 16}, s5[4] = {1024, 32 * 1024, 64 * 1024, 64};
    const uint32_t b5[5] = {64, 32, 1, 2, 2};
    make_map(enc, &prm.m[M_WOA + t], d_in[2 + 3 * t], 5, d5, s5, b5, S128);
    const uint64_t dr[3] = {64, 2048, 16}, sr[2] = {1024, 64};
    const uint32_t br[3] = {64, 128, 2};
    make_map(enc, &prm.m[M_X0R + t], t ? xs : d_in[0], 3, dr, sr, br, S128);
  }
  map2(enc, &prm.m[M_OS], os, 1024, 2048, 64, 64, S128);
  map2(enc, &prm.m[M_K], kk, 32, 65536, 32, 256, S64);
  map2(enc, &prm.m[M_V], vv, 32, 65536, 32, 256, S64);
  map2(enc, &prm.m[M_K4], kk, 32, 65536, 32, 64, S64);
  map2(enc, &prm.m[M_V4], vv, 32, 65536, 32, 64, S64);
  map2(enc, &prm.m[M_XSO], xs, 1024, 2048, 64, 128, S128);
  map2(enc, &prm.m[M_X0H], d_in[0], 1024, 2048, 64, 128, S128);
  map2(enc, &prm.m[M_XST], xs, 1024, 2048, 64, 16, S128);
  map2(enc, &prm.m[M_OUT], d_out, 1024, 2048, 64, 16, S128);
  prm.x0 = (const bf16*)d_in[0];
  prm.wq[0] = (const bf16*)d_in[1]; prm.wq[1] = (const bf16*)d_in[4];
  prm.wo[0] = (const bf16*)d_in[2]; prm.wo[1] = (const bf16*)d_in[5];
  prm.epoch = (uint32_t*)ep;
  prm.zero = 0;
  for (int i = 0; i < 128; i++) prm.map[i] = remap(i);
  fused_kernel<<<128, 384, SMEM_BYTES>>>(prm);
}
```

```cpp
#include <cuda_runtime.h>
#include <cuda_bf16.h>
#include <cuda.h>
#include <stdint.h>

typedef __nv_bfloat16 bf16;

__device__ __forceinline__ void wgmma_m64n192k16_ss_tb(float (&d)[96], uint64_t da, uint64_t db, int scale_d) {
  asm volatile("{\n.reg .pred p;\nsetp.ne.b32 p, %98, 0;\n"
    "wgmma.mma_async.sync.aligned.m64n192k16.f32.bf16.bf16 "
    "{%0, %1, %2, %3, %4, %5, %6, %7, %8, %9, %10, %11, %12, %13, %14, %15, "
    "%16, %17, %18, %19, %20, %21, %22, %23, %24, %25, %26, %27, %28, %29, %30, %31, "
    "%32, %33, %34, %35, %36, %37, %38, %39, %40, %41, %42, %43, %44, %45, %46, %47, "
    "%48, %49, %50, %51, %52, %53, %54, %55, %56, %57, %58, %59, %60, %61, %62, %63, "
    "%64, %65, %66, %67, %68, %69, %70, %71, %72, %73, %74, %75, %76, %77, %78, %79, "
    "%80, %81, %82, %83, %84, %85, %86, %87, %88, %89, %90, %91, %92, %93, %94, %95}, "
    "%96, %97, p, 1, 1, 0, 1;\n}\n"
    : "+f"(d[0]), "+f"(d[1]), "+f"(d[2]), "+f"(d[3]), "+f"(d[4]), "+f"(d[5]), "+f"(d[6]), "+f"(d[7]),
      "+f"(d[8]), "+f"(d[9]), "+f"(d[10]), "+f"(d[11]), "+f"(d[12]), "+f"(d[13]), "+f"(d[14]), "+f"(d[15]),
      "+f"(d[16]), "+f"(d[17]), "+f"(d[18]), "+f"(d[19]), "+f"(d[20]), "+f"(d[21]), "+f"(d[22]), "+f"(d[23]),
      "+f"(d[24]), "+f"(d[25]), "+f"(d[26]), "+f"(d[27]), "+f"(d[28]), "+f"(d[29]), "+f"(d[30]), "+f"(d[31]),
      "+f"(d[32]), "+f"(d[33]), "+f"(d[34]), "+f"(d[35]), "+f"(d[36]), "+f"(d[37]), "+f"(d[38]), "+f"(d[39]),
      "+f"(d[40]), "+f"(d[41]), "+f"(d[42]), "+f"(d[43]), "+f"(d[44]), "+f"(d[45]), "+f"(d[46]), "+f"(d[47]),
      "+f"(d[48]), "+f"(d[49]), "+f"(d[50]), "+f"(d[51]), "+f"(d[52]), "+f"(d[53]), "+f"(d[54]), "+f"(d[55]),
      "+f"(d[56]), "+f"(d[57]), "+f"(d[58]), "+f"(d[59]), "+f"(d[60]), "+f"(d[61]), "+f"(d[62]), "+f"(d[63]),
      "+f"(d[64]), "+f"(d[65]), "+f"(d[66]), "+f"(d[67]), "+f"(d[68]), "+f"(d[69]), "+f"(d[70]), "+f"(d[71]),
      "+f"(d[72]), "+f"(d[73]), "+f"(d[74]), "+f"(d[75]), "+f"(d[76]), "+f"(d[77]), "+f"(d[78]), "+f"(d[79]),
      "+f"(d[80]), "+f"(d[81]), "+f"(d[82]), "+f"(d[83]), "+f"(d[84]), "+f"(d[85]), "+f"(d[86]), "+f"(d[87]),
      "+f"(d[88]), "+f"(d[89]), "+f"(d[90]), "+f"(d[91]), "+f"(d[92]), "+f"(d[93]), "+f"(d[94]), "+f"(d[95])
    : "l"(da), "l"(db), "r"(scale_d));
}

__device__ __forceinline__ void wgmma_m64n128k16_ss_tb(float (&d)[64], uint64_t da, uint64_t db, int scale_d) {
  asm volatile("{\n.reg .pred p;\nsetp.ne.b32 p, %66, 0;\n"
    "wgmma.mma_async.sync.aligned.m64n128k16.f32.bf16.bf16 "
    "{%0, %1, %2, %3, %4, %5, %6, %7, %8, %9, %10, %11, %12, %13, %14, %15, "
    "%16, %17, %18, %19, %20, %21, %22, %23, %24, %25, %26, %27, %28, %29, %30, %31, "
    "%32, %33, %34, %35, %36, %37, %38, %39, %40, %41, %42, %43, %44, %45, %46, %47, "
    "%48, %49, %50, %51, %52, %53, %54, %55, %56, %57, %58, %59, %60, %61, %62, %63}, "
    "%64, %65, p, 1, 1, 0, 1;\n}\n"
    : "+f"(d[0]), "+f"(d[1]), "+f"(d[2]), "+f"(d[3]), "+f"(d[4]), "+f"(d[5]), "+f"(d[6]), "+f"(d[7]),
      "+f"(d[8]), "+f"(d[9]), "+f"(d[10]), "+f"(d[11]), "+f"(d[12]), "+f"(d[13]), "+f"(d[14]), "+f"(d[15]),
      "+f"(d[16]), "+f"(d[17]), "+f"(d[18]), "+f"(d[19]), "+f"(d[20]), "+f"(d[21]), "+f"(d[22]), "+f"(d[23]),
      "+f"(d[24]), "+f"(d[25]), "+f"(d[26]), "+f"(d[27]), "+f"(d[28]), "+f"(d[29]), "+f"(d[30]), "+f"(d[31]),
      "+f"(d[32]), "+f"(d[33]), "+f"(d[34]), "+f"(d[35]), "+f"(d[36]), "+f"(d[37]), "+f"(d[38]), "+f"(d[39]),
      "+f"(d[40]), "+f"(d[41]), "+f"(d[42]), "+f"(d[43]), "+f"(d[44]), "+f"(d[45]), "+f"(d[46]), "+f"(d[47]),
      "+f"(d[48]), "+f"(d[49]), "+f"(d[50]), "+f"(d[51]), "+f"(d[52]), "+f"(d[53]), "+f"(d[54]), "+f"(d[55]),
      "+f"(d[56]), "+f"(d[57]), "+f"(d[58]), "+f"(d[59]), "+f"(d[60]), "+f"(d[61]), "+f"(d[62]), "+f"(d[63])
    : "l"(da), "l"(db), "r"(scale_d));
}

__device__ __forceinline__ void wgmma_m64n32k16_rs_nb_h(float (&d)[16], uint32_t a0, uint32_t a1, uint32_t a2, uint32_t a3, uint64_t db, int scale_d) {
  asm volatile("{\n.reg .pred p;\nsetp.ne.b32 p, %21, 0;\n"
    "wgmma.mma_async.sync.aligned.m64n32k16.f32.f16.f16 "
    "{%0, %1, %2, %3, %4, %5, %6, %7, %8, %9, %10, %11, %12, %13, %14, %15}, "
    "{%16, %17, %18, %19}, %20, p, 1, 1, 0;\n}\n"
    : "+f"(d[0]), "+f"(d[1]), "+f"(d[2]), "+f"(d[3]), "+f"(d[4]), "+f"(d[5]), "+f"(d[6]), "+f"(d[7]),
      "+f"(d[8]), "+f"(d[9]), "+f"(d[10]), "+f"(d[11]), "+f"(d[12]), "+f"(d[13]), "+f"(d[14]), "+f"(d[15])
    : "r"(a0), "r"(a1), "r"(a2), "r"(a3), "l"(db), "r"(scale_d));
}

__device__ __forceinline__ void wgmma_m64n32k16_rs_nb_hh(uint32_t (&d)[8], uint32_t a0, uint32_t a1, uint32_t a2, uint32_t a3, uint64_t db, int scale_d) {
  asm volatile("{\n.reg .pred p;\nsetp.ne.b32 p, %13, 0;\n"
    "wgmma.mma_async.sync.aligned.m64n32k16.f16.f16.f16 "
    "{%0, %1, %2, %3, %4, %5, %6, %7}, "
    "{%8, %9, %10, %11}, %12, p, 1, 1, 0;\n}\n"
    : "+r"(d[0]), "+r"(d[1]), "+r"(d[2]), "+r"(d[3]), "+r"(d[4]), "+r"(d[5]), "+r"(d[6]), "+r"(d[7])
    : "r"(a0), "r"(a1), "r"(a2), "r"(a3), "l"(db), "r"(scale_d));
}

__device__ __forceinline__ void wgmma_m64n40k16_rs_tb(float (&d)[20], uint32_t a0, uint32_t a1, uint32_t a2, uint32_t a3, uint64_t db, int scale_d) {
  asm volatile("{\n.reg .pred p;\nsetp.ne.b32 p, %25, 0;\n"
    "wgmma.mma_async.sync.aligned.m64n40k16.f32.bf16.bf16 "
    "{%0, %1, %2, %3, %4, %5, %6, %7, %8, %9, %10, %11, %12, %13, %14, %15, "
    "%16, %17, %18, %19}, "
    "{%20, %21, %22, %23}, %24, p, 1, 1, 1;\n}\n"
    : "+f"(d[0]), "+f"(d[1]), "+f"(d[2]), "+f"(d[3]), "+f"(d[4]), "+f"(d[5]), "+f"(d[6]), "+f"(d[7]),
      "+f"(d[8]), "+f"(d[9]), "+f"(d[10]), "+f"(d[11]), "+f"(d[12]), "+f"(d[13]), "+f"(d[14]), "+f"(d[15]),
      "+f"(d[16]), "+f"(d[17]), "+f"(d[18]), "+f"(d[19])
    : "r"(a0), "r"(a1), "r"(a2), "r"(a3), "l"(db), "r"(scale_d));
}

__device__ __forceinline__ void wgmma_m64n40k16_rs_tb_z(float (&d)[20], uint32_t a0, uint32_t a1, uint32_t a2, uint32_t a3, uint64_t db, int scale_d) {
  asm volatile("{\n.reg .pred p;\nsetp.ne.b32 p, %25, 0;\n"
    "wgmma.mma_async.sync.aligned.m64n40k16.f32.bf16.bf16 "
    "{%0, %1, %2, %3, %4, %5, %6, %7, %8, %9, %10, %11, %12, %13, %14, %15, "
    "%16, %17, %18, %19}, "
    "{%20, %21, %22, %23}, %24, p, 1, 1, 1;\n}\n"
    : "=f"(d[0]), "=f"(d[1]), "=f"(d[2]), "=f"(d[3]), "=f"(d[4]), "=f"(d[5]), "=f"(d[6]), "=f"(d[7]),
      "=f"(d[8]), "=f"(d[9]), "=f"(d[10]), "=f"(d[11]), "=f"(d[12]), "=f"(d[13]), "=f"(d[14]), "=f"(d[15]),
      "=f"(d[16]), "=f"(d[17]), "=f"(d[18]), "=f"(d[19])
    : "r"(a0), "r"(a1), "r"(a2), "r"(a3), "l"(db), "r"(scale_d));
}

__device__ __forceinline__ void wgmma_m64n32k16_rs_nb_z_h(float (&d)[16], uint32_t a0, uint32_t a1, uint32_t a2, uint32_t a3, uint64_t db, int scale_d) {
  asm volatile("{\n.reg .pred p;\nsetp.ne.b32 p, %21, 0;\n"
    "wgmma.mma_async.sync.aligned.m64n32k16.f32.f16.f16 "
    "{%0, %1, %2, %3, %4, %5, %6, %7, %8, %9, %10, %11, %12, %13, %14, %15}, "
    "{%16, %17, %18, %19}, %20, p, 1, 1, 0;\n}\n"
    : "=f"(d[0]), "=f"(d[1]), "=f"(d[2]), "=f"(d[3]), "=f"(d[4]), "=f"(d[5]), "=f"(d[6]), "=f"(d[7]),
      "=f"(d[8]), "=f"(d[9]), "=f"(d[10]), "=f"(d[11]), "=f"(d[12]), "=f"(d[13]), "=f"(d[14]), "=f"(d[15])
    : "r"(a0), "r"(a1), "r"(a2), "r"(a3), "l"(db), "r"(scale_d));
}

__device__ __forceinline__ void wgmma_m64n32k16_rs_nb_z_hh(uint32_t (&d)[8], uint32_t a0, uint32_t a1, uint32_t a2, uint32_t a3, uint64_t db, int scale_d) {
  asm volatile("{\n.reg .pred p;\nsetp.ne.b32 p, %13, 0;\n"
    "wgmma.mma_async.sync.aligned.m64n32k16.f16.f16.f16 "
    "{%0, %1, %2, %3, %4, %5, %6, %7}, "
    "{%8, %9, %10, %11}, %12, p, 1, 1, 0;\n}\n"
    : "=r"(d[0]), "=r"(d[1]), "=r"(d[2]), "=r"(d[3]), "=r"(d[4]), "=r"(d[5]), "=r"(d[6]), "=r"(d[7])
    : "r"(a0), "r"(a1), "r"(a2), "r"(a3), "l"(db), "r"(scale_d));
}

#define DEVINL __device__ __forceinline__
DEVINL void wg_fence() { asm volatile("wgmma.fence.sync.aligned;" ::: "memory"); }
DEVINL void wg_commit() { asm volatile("wgmma.commit_group.sync.aligned;" ::: "memory"); }
template <int N> DEVINL void wg_wait() { asm volatile("wgmma.wait_group.sync.aligned %0;" ::"n"(N) : "memory"); }
DEVINL uint64_t mkdesc(uint32_t addr, uint32_t lbo, uint32_t sbo, int sw) {
  return (uint64_t)((addr & 0x3FFFF) >> 4) | ((uint64_t)(lbo >> 4) << 16) | ((uint64_t)(sbo >> 4) << 32) | ((uint64_t)sw << 62);
}
DEVINL void mbar_arrive(uint32_t bar) { asm volatile("mbarrier.arrive.shared::cta.b64 _, [%0];" ::"r"(bar) : "memory"); }
DEVINL void arrive_if_gt(uint32_t bar, uint32_t a, uint32_t b) {
  asm volatile("{\n.reg .pred p;\nsetp.gt.u32 p, %1, %2;\n@p mbarrier.arrive.shared::cta.b64 _, [%0];\n}" ::"r"(bar), "r"(a), "r"(b) : "memory");
}
DEVINL bool mbar_try(uint32_t bar, uint32_t parity) {
  uint32_t ok;
  asm volatile("{\n.reg .pred p;\nmbarrier.try_wait.parity.shared::cta.b64 p, [%1], %2;\nselp.u32 %0, 1, 0, p;\n}" : "=r"(ok) : "r"(bar), "r"(parity) : "memory");
  return ok;
}
DEVINL bool mbar_test(uint32_t bar, uint32_t parity) {
  uint32_t ok;
  asm volatile("{\n.reg .pred p;\nmbarrier.test_wait.parity.shared::cta.b64 p, [%1], %2;\nselp.u32 %0, 1, 0, p;\n}" : "=r"(ok) : "r"(bar), "r"(parity) : "memory");
  return ok;
}
DEVINL void mbar_hint(uint32_t bar, uint32_t parity) {
#pragma unroll 1
  for (uint32_t n = 0; n < 16u; n++) if (mbar_try(bar, parity)) break;
}
DEVINL void mbar_wait(uint32_t bar, uint32_t parity) {
#pragma unroll 1
  for (uint32_t n = 0; n < 100000u; n++) if (mbar_try(bar, parity)) break;
}
DEVINL void mbar_wait_long(uint32_t bar, uint32_t parity) {
#pragma unroll 1
  for (uint32_t n = 0; n < 100000u; n++) {
    uint32_t ok;
    asm volatile("{\n.reg .pred p;\nmbarrier.try_wait.parity.shared::cta.b64 p, [%1], %2, %3;\nselp.u32 %0, 1, 0, p;\n}" : "=r"(ok) : "r"(bar), "r"(parity), "r"(4000) : "memory");
    if (ok) break;
  }
}
#define EL(txt) "{\n.reg .pred pe;\nelect.sync _|pe, 0xffffffff;\n@pe " txt "\n}"
DEVINL void e_expect_tx(uint32_t bar, uint32_t bytes) { asm volatile(EL("mbarrier.arrive.expect_tx.shared::cta.b64 _, [%0], %1;") ::"r"(bar), "r"(bytes) : "memory"); }
DEVINL void e_init(uint32_t bar, uint32_t cnt) { asm volatile(EL("mbarrier.init.shared::cta.b64 [%0], %1;") ::"r"(bar), "r"(cnt) : "memory"); }
DEVINL void e_arrive(uint32_t bar) { asm volatile(EL("mbarrier.arrive.shared::cta.b64 _, [%0];") ::"r"(bar) : "memory"); }
DEVINL void e_red(uint32_t* p) { asm volatile(EL("red.release.gpu.global.add.u32 [%0], 1;") ::"l"(p) : "memory"); }
DEVINL void e_red_relaxed(uint32_t* p) { asm volatile(EL("red.relaxed.gpu.global.add.u32 [%0], 1;") ::"l"(p) : "memory"); }
DEVINL void tma_ld(uint32_t dst, const CUtensorMap* m, int c0, int c1, uint32_t bar) {
  asm volatile(EL("cp.async.bulk.tensor.2d.shared::cluster.global.mbarrier::complete_tx::bytes [%0], [%1, {%3, %4}], [%2];")
               ::"r"(dst), "l"(m), "r"(bar), "r"(c0), "r"(c1) : "memory");
}
DEVINL void tma_ld3(uint32_t dst, const CUtensorMap* m, int c0, int c1, int c2, uint32_t bar) {
  asm volatile(EL("cp.async.bulk.tensor.3d.shared::cluster.global.mbarrier::complete_tx::bytes [%0], [%1, {%3, %4, %5}], [%2];")
               ::"r"(dst), "l"(m), "r"(bar), "r"(c0), "r"(c1), "r"(c2) : "memory");
}
DEVINL void tma_ld5(uint32_t dst, const CUtensorMap* m, int c2, int c3, int c4, uint32_t bar) {
  asm volatile(EL("cp.async.bulk.tensor.5d.shared::cluster.global.mbarrier::complete_tx::bytes [%0], [%1, {0, 0, %3, %4, %5}], [%2];")
               ::"r"(dst), "l"(m), "r"(bar), "r"(c2), "r"(c3), "r"(c4) : "memory");
}
DEVINL void tma_ld_mc(uint32_t dst, const CUtensorMap* m, int c0, int c1, uint32_t bar) {
  asm volatile(EL("cp.async.bulk.tensor.2d.shared::cluster.global.mbarrier::complete_tx::bytes.multicast::cluster [%0], [%1, {%3, %4}], [%2], %5;")
               ::"r"(dst), "l"(m), "r"(bar), "r"(c0), "r"(c1), "h"((uint16_t)3) : "memory");
}
DEVINL void e_arrive_both(uint32_t bar) {
  asm volatile("{\n.reg .pred pe;\n.reg .b32 r0, r1;\nelect.sync _|pe, 0xffffffff;\nmapa.shared::cluster.u32 r0, %0, 0;\nmapa.shared::cluster.u32 r1, %0, 1;\n"
               "@pe mbarrier.arrive.shared::cluster.b64 _, [r0];\n@pe mbarrier.arrive.shared::cluster.b64 _, [r1];\n}" ::"r"(bar) : "memory");
}
DEVINL void push_peer(uint32_t dst, uint32_t src, uint32_t bar, uint32_t peer) {
  asm volatile("{\n.reg .pred pe;\n.reg .b32 d, b;\nelect.sync _|pe, 0xffffffff;\nmapa.shared::cluster.u32 d, %0, %3;\nmapa.shared::cluster.u32 b, %2, %3;\n"
               "@pe cp.async.bulk.shared::cluster.shared::cta.mbarrier::complete_tx::bytes [d], [%1], 16384, [b];\n}" ::"r"(dst), "r"(src), "r"(bar), "r"(peer) : "memory");
}
DEVINL void tma_st(const CUtensorMap* m, int c0, int c1, uint32_t src) {
  asm volatile(EL("cp.async.bulk.tensor.2d.global.shared::cta.bulk_group [%0, {%2, %3}], [%1];") ::"l"(m), "r"(src), "r"(c0), "r"(c1) : "memory");
}
DEVINL void bulk_commit() { asm volatile("cp.async.bulk.commit_group;" ::: "memory"); }
template <int N> DEVINL void bulk_wait_n() { asm volatile("cp.async.bulk.wait_group %0;\nbar.warp.sync 0xffffffff;" ::"n"(N) : "memory"); }
DEVINL void l2_prefetch(const void* g, uint32_t bytes) { asm volatile(EL("cp.async.bulk.prefetch.L2.global [%0], %1;") ::"l"(g), "r"(bytes) : "memory"); }
DEVINL void fence_async_smem() { asm volatile("fence.proxy.async.shared::cta;" ::: "memory"); }
DEVINL void fence_async_gl() { asm volatile("fence.proxy.async.global;" ::: "memory"); }
DEVINL void cluster_wait() { asm volatile("barrier.cluster.wait.aligned;" ::: "memory"); }
DEVINL void bar_sync(int id, int n) { asm volatile("bar.sync %0, %1;" ::"r"(id), "r"(n) : "memory"); }
DEVINL void bar_arrive(int id, int n) { asm volatile("bar.arrive %0, %1;" ::"r"(id), "r"(n) : "memory"); }
DEVINL uint32_t ld_acquire(const uint32_t* p) { uint32_t v; asm volatile("ld.acquire.gpu.global.u32 %0, [%1];" : "=r"(v) : "l"(p) : "memory"); return v; }
DEVINL void watch(const uint32_t* p, uint32_t target, uint32_t all, uint32_t tag, uint32_t slot) {
  uint32_t seen = 0;
#pragma unroll 1
  for (uint32_t n = 0; n < 200000u && seen != all; n++) {
    const uint32_t m = __ballot_sync(~0u, (int)(ld_acquire(p) - target) >= 0) & all;
    if (m != seen) { seen = m; asm volatile("st.release.cta.shared.u32 [%0], %1;" ::"r"(slot), "r"(tag << 16 | m) : "memory"); }
  }
}
template <bool RELAXED = false> DEVINL void await_bit(uint32_t slot, uint32_t tag, int j, uint32_t& rdy) {
  if ((rdy >> j) & 1) return;
#pragma unroll 1
  for (uint32_t n = 0; n < 8000000u; n++) {
    uint32_t v;
    asm volatile("ld.acquire.cta.shared.u32 %0, [%1];" : "=r"(v) : "r"(slot) : "memory");
    if ((v >> 16) == tag && ((v >> j) & 1)) { rdy = v; break; }
    if (RELAXED) __nanosleep(200);
  }
  asm volatile("fence.proxy.async.global;" ::: "memory");
}
DEVINL void poll_ge(const uint32_t* p, uint32_t target) {
#pragma unroll 1
  for (uint32_t n = 0; n < 200000u; n++) if (__all_sync(~0u, (int)(ld_acquire(p) - target) >= 0)) break;
}
DEVINL int lane_id() { int v; asm volatile("mov.u32 %0, %%laneid;" : "=r"(v)); return v; }
__host__ DEVINL int remap(int v) {
  const int c = v >> 1, u = c - 36, r = (u * 37) >> 8;
  const int L = max(c - 4 + max(r + 1, 0), (c - 4) >> 31 & (32 + 8 * c));
  return 2 * L + (v & 1);
}
DEVINL int block_id() { int v; asm volatile("mov.u32 %0, %%ctaid.x;" : "=r"(v)); return v; }
#define cta_id() prm.map[block_id()]
#define IDS() const int lane = lane_id(), b = cta_id(), bm = b >> 4, bn = b & 15, rank = b & 1, pm = 2 * bm + (bn >> 3), pn = bn & 7, po = pm & 1; \
  (void)lane; (void)bm; (void)bn; (void)rank; (void)pm; (void)pn; (void)po
DEVINL void st_tagged(unsigned long long* p, uint32_t v, uint32_t tag) {
  asm volatile("{\n.reg .b64 t;\nmov.b64 t, {%1, %2};\nst.relaxed.gpu.global.b64 [%0], t;\n}" ::"l"(p), "r"(v), "r"(tag) : "memory");
}
DEVINL float ex2(float x) { float y; asm("ex2.approx.ftz.f32 %0, %1;" : "=f"(y) : "f"(x)); return y; }
DEVINL float rcp(float x) { float y; asm("rcp.approx.ftz.f32 %0, %1;" : "=f"(y) : "f"(x)); return y; }
DEVINL uint32_t pack2(float lo, float hi) { uint32_t r; asm("cvt.rn.bf16x2.f32 %0, %1, %2;" : "=r"(r) : "f"(hi), "f"(lo)); return r; }
DEVINL float bf_lo(uint32_t w) { return __uint_as_float(w << 16); }
DEVINL float bf_hi(uint32_t w) { return __uint_as_float(w & 0xFFFF0000u); }
DEVINL float bf_round(float x) { return bf_lo(pack2(x, 0.f)); }
DEVINL uint32_t add_bf16x2(uint32_t a, uint32_t b) { uint32_t r; asm("add.rn.bf16x2 %0, %1, %2;" : "=r"(r) : "r"(a), "r"(b)); return r; }
DEVINL uint32_t max_bf2(uint32_t a, uint32_t b) { uint32_t r; asm("max.bf16x2 %0, %1, %2;" : "=r"(r) : "r"(a), "r"(b)); return r; }
DEVINL uint32_t scale_bf2(uint32_t a) {
  uint32_t r;
  asm("{\n.reg .b32 t;\nmul.rn.bf16x2 t, %1, %3;\nfma.rn.bf16x2 %0, %1, %2, t;\n}" : "=r"(r) : "r"(a), "r"(0x3E353E35u), "r"(0x379E379Eu));
  return r;
}
DEVINL void stsm4(uint32_t addr, uint32_t a, uint32_t b, uint32_t c, uint32_t d) {
  asm volatile("stmatrix.sync.aligned.m8n8.x4.shared.b16 [%0], {%1, %2, %3, %4};" ::"r"(addr), "r"(a), "r"(b), "r"(c), "r"(d) : "memory");
}
DEVINL void ldsm4(uint32_t addr, uint32_t (&r)[4]) {
  asm volatile("ldmatrix.sync.aligned.m8n8.x4.shared.b16 {%0, %1, %2, %3}, [%4];" : "=r"(r[0]), "=r"(r[1]), "=r"(r[2]), "=r"(r[3]) : "r"(addr) : "memory");
}
DEVINL void ldsm4t(uint32_t addr, uint32_t (&r)[4]) {
  asm volatile("ldmatrix.sync.aligned.m8n8.x4.trans.shared.b16 {%0, %1, %2, %3}, [%4];" : "=r"(r[0]), "=r"(r[1]), "=r"(r[2]), "=r"(r[3]) : "r"(addr) : "memory");
}
DEVINL void sts128(uint32_t addr, uint32_t a, uint32_t b, uint32_t c, uint32_t d) {
  asm volatile("st.shared.v4.b32 [%0], {%1, %2, %3, %4};" ::"r"(addr), "r"(a), "r"(b), "r"(c), "r"(d) : "memory");
}
DEVINL float4 lds128f(uint32_t addr) { float4 v; asm volatile("ld.shared.v4.f32 {%0, %1, %2, %3}, [%4];" : "=f"(v.x), "=f"(v.y), "=f"(v.z), "=f"(v.w) : "r"(addr) : "memory"); return v; }
DEVINL float lds32f(uint32_t addr) { float v; asm volatile("ld.shared.f32 %0, [%1];" : "=f"(v) : "r"(addr) : "memory"); return v; }
DEVINL float2 lds64f(uint32_t addr) { float2 v; asm volatile("ld.shared.v2.f32 {%0, %1}, [%2];" : "=f"(v.x), "=f"(v.y) : "r"(addr) : "memory"); return v; }
DEVINL void mma16816(float (&d)[4], uint32_t a0, uint32_t a1, uint32_t a2, uint32_t a3, uint32_t b0, uint32_t b1) {
  asm("mma.sync.aligned.m16n8k16.row.col.f32.bf16.bf16.f32 {%0, %1, %2, %3}, {%4, %5, %6, %7}, {%8, %9}, {%0, %1, %2, %3};"
               : "+f"(d[0]), "+f"(d[1]), "+f"(d[2]), "+f"(d[3]) : "r"(a0), "r"(a1), "r"(a2), "r"(a3), "r"(b0), "r"(b1));
}
DEVINL void mma1688(float (&d)[4], uint32_t a0, uint32_t a1, uint32_t b0) {
  asm("mma.sync.aligned.m16n8k8.row.col.f32.bf16.bf16.f32 {%0, %1, %2, %3}, {%4, %5}, {%6}, {%0, %1, %2, %3};"
               : "+f"(d[0]), "+f"(d[1]), "+f"(d[2]), "+f"(d[3]) : "r"(a0), "r"(a1), "r"(b0));
}
DEVINL void mma1688h(float (&d)[4], uint32_t a0, uint32_t a1, uint32_t b0) {
  asm("mma.sync.aligned.m16n8k8.row.col.f32.f16.f16.f32 {%0, %1, %2, %3}, {%4, %5}, {%6}, {%0, %1, %2, %3};"
               : "+f"(d[0]), "+f"(d[1]), "+f"(d[2]), "+f"(d[3]) : "r"(a0), "r"(a1), "r"(b0));
}
DEVINL void mma16816h(float (&d)[4], uint32_t a0, uint32_t a1, uint32_t a2, uint32_t a3, uint32_t b0, uint32_t b1) {
  asm("mma.sync.aligned.m16n8k16.row.col.f32.f16.f16.f32 {%0, %1, %2, %3}, {%4, %5, %6, %7}, {%8, %9}, {%0, %1, %2, %3};"
               : "+f"(d[0]), "+f"(d[1]), "+f"(d[2]), "+f"(d[3]) : "r"(a0), "r"(a1), "r"(a2), "r"(a3), "r"(b0), "r"(b1));
}
template <int N> DEVINL void fence_regs(uint32_t (&d)[N]) {
#pragma unroll
  for (int i = 0; i < N; i++) asm volatile("" : "+r"(d[i])::"memory");
}
template <int N> DEVINL void fence_regs(float (&d)[N]) {
#pragma unroll
  for (int i = 0; i < N; i++) asm volatile("" : "+f"(d[i])::"memory");
}

__device__ __align__(1024) bf16 g_xs[2048 * 1024];
__device__ __align__(1024) bf16 g_os[2048 * 1024];
__device__ __align__(1024) bf16 g_k[32 * 2048 * 32];
__device__ __align__(1024) bf16 g_v[32 * 2048 * 32];
__device__ __align__(128) float2 g_stats[8 * 2048];
__device__ __align__(16) float g_csp[2 * 16 * 8 * 192];
__device__ __align__(128) float g_kn[2 * 128 * 32];
__device__ unsigned long long g_halo[2 * 128 * 32 * 32];
__device__ __align__(128) uint32_t g_cnt[256 * 32];
__device__ uint32_t g_epoch;

DEVINL uint32_t* cnt_x(int l, int bm) { return g_cnt + (l * 8 + bm) * 32; }
DEVINL uint32_t* cnt_o(int l, int pm, int h) { return g_cnt + (32 + (l * 16 + pm) * 2 + h) * 32; }
DEVINL uint32_t* cnt_kv(int lb, int bn) { return g_cnt + (160 + lb * 16 + bn) * 32; }
DEVINL uint32_t* cnt_ad(int bn) { return g_cnt + (192 + bn) * 32; }
DEVINL uint32_t* cnt_cs(int t, int bn) { return g_cnt + (208 + t * 16 + bn) * 32; }

DEVINL int qord(int i, int l, int pn) { return l == 0 ? i : i < 4 ? ((2 * pn) ^ (i & 2)) + (i & 1) : i - 4 < 2 * (pn & 6) ? i - 4 : i; }
DEVINL int pord(int i, int l, int p) { return (l & 1) || i > p ? i : i ? i - 1 : p; }
struct Params {
  CUtensorMap m[17];
  const bf16* x0;
  const bf16* wq[2];
  const bf16* wo[2];
  uint32_t* epoch;
  uint32_t zero;
  int map[128];
};
enum { M_X0A = 0, M_XSA, M_WQA, M_WQB, M_WOA, M_WOB, M_OS, M_K, M_V, M_X0R, M_XSR, M_XSO, M_OUT, M_XST, M_X0H, M_K4, M_V4, M_COUNT };

constexpr uint32_t QSTG = 57344;
constexpr uint32_t T0 = 65536, TSTG = 32768;
constexpr uint32_t ONES = 229376;
constexpr uint32_t PSTG = 32768;
constexpr uint32_t ASC = 17408;
constexpr uint32_t RSTD = 229376, MEAN = 230400, COLS = 230912, KMAX = 231680, B_QD = 231688, B_OW = 231704, W_C = 231712, BARS = 232192, SMEM_BYTES = 232448;
constexpr uint32_t B_QF = BARS, B_QE = BARS + 32, B_TF = BARS + 64, B_TE = BARS + 96, B_PF = BARS + 128, B_PE = BARS + 176,
                   B_RF = BARS + 224, W_X = BARS + 232, W_O = BARS + 236, B_QL = BARS + 240, B_PA = BARS + 248;
enum { NB_ST = 1, NB_KV = 2  , NB_DONE = 3, NB_SC = 4, NB_SIG = 5  , NB_KN = 9  , NB_X = 11, NB_HALO = 12  , NB_X0 = 15 };

DEVINL uint32_t pslot_b(uint32_t s, int l) { return ((((l & 1) ? 0x32DC45u : 0x468795u) >> (4 * s)) & 15) * 16384u; }
DEVINL uint32_t pslot_a(uint32_t s, int l) { return ((((l & 1) ? 0xBA8796u : 0x32DCBAu) >> (4 * s)) & 15) * 16384u; }

constexpr float QSCALE = 0.17677669529663687f * 1.4426950408889634f;

DEVINL uint32_t hfma2(uint32_t a, uint32_t b, uint32_t c) { uint32_t r; asm("fma.rn.f16x2 %0, %1, %2, %3;" : "=r"(r) : "r"(a), "r"(b), "r"(c)); return r; }
DEVINL uint32_t pack2h(float lo, float hi) { uint32_t r; asm("cvt.rn.f16x2.f32 %0, %1, %2;" : "=r"(r) : "f"(hi), "f"(lo)); return r; }
DEVINL uint32_t h2_to_bf2(uint32_t h) {
  float a, b;
  asm("{\n.reg .b16 l, h;\nmov.b32 {l, h}, %2;\ncvt.f32.f16 %0, l;\ncvt.f32.f16 %1, h;\n}" : "=f"(a), "=f"(b) : "r"(h));
  return pack2(a, b);
}
DEVINL uint32_t exp2_h2(uint32_t s, uint32_t cc) {
  uint32_t r, v;
  asm("{\n.reg .b16 l, h;\n.reg .b32 t;\nmov.b32 {l, h}, %2;\nmov.b32 t, {l, l};\nfma.rn.f16x2 %0, %1, t, %3;\n}" : "=r"(r) : "r"(s), "r"(cc), "r"(0x007E007Eu));
  asm("{\n.reg .b16 l, h;\n.reg .b32 t;\nmov.b32 {l, h}, %2;\nmov.b32 t, {h, h};\nfma.rn.f16x2 %0, %1, t, %3;\n}" : "=r"(v) : "r"(r), "r"(cc), "r"(0x33FD33FDu));
  const uint32_t g = hfma2(v, 0x44004400u, s);
  return __funnelshift_l(r, r, 7) + hfma2(hfma2(g, g, 0x0DE10DE1u), g, 0x00300030u);
}
constexpr uint32_t NOT_F16 = 0x7FC00000u, K_LO = 0x35000000u  ;
DEVINL uint32_t f16_class(uint32_t norm2, uint32_t lo) { return norm2 - lo > 0x4E800000u - lo ? NOT_F16 : norm2; }

DEVINL void attn_slow(const uint32_t (&q)[8], float up, int head, const float* kn, float (&res)[20], int lane) {
  const int g = lane >> 2, qd = lane & 3;
  const bf16* kb = g_k + (size_t)head * 2048 * 32;
  const bf16* vb = g_v + (size_t)head * 2048 * 32;
  float o[4][4], m0 = -INFINITY, m1 = -INFINITY, l0 = 0.f, l1 = 0.f;
#pragma unroll
  for (int j = 0; j < 4; j++) { o[j][0] = o[j][1] = o[j][2] = o[j][3] = 0.f; }
#pragma unroll 1
  for (int k0 = 0; k0 < 2048; k0 += 16) {
    float s[2][4];
    const bool kh = __float_as_uint(__ldcg(kn + (k0 >> 8) * 32 + ((k0 >> 6) & 1) * 8 + ((k0 >> 7) & 1) * 4 + ((k0 >> 4) & 3))) != NOT_F16;
#pragma unroll
    for (int nt = 0; nt < 2; nt++) {
      s[nt][0] = s[nt][1] = s[nt][2] = s[nt][3] = 0.f;
      const uint32_t* kp = (const uint32_t*)(kb + (size_t)(k0 + nt * 8 + g) * 32) + qd;
      uint32_t kf[4];
#pragma unroll
      for (int i = 0; i < 4; i++) { kf[i] = __ldcg(kp + 4 * i); if (kh) kf[i] = h2_to_bf2(kf[i]); }
      mma16816(s[nt], q[0], q[1], q[2], q[3], kf[0], kf[1]);
      mma16816(s[nt], q[4], q[5], q[6], q[7], kf[2], kf[3]);
      s[nt][0] *= up; s[nt][1] *= up; s[nt][2] *= up; s[nt][3] *= up;
    }
    float a0 = fmaxf(fmaxf(s[0][0], s[0][1]), fmaxf(s[1][0], s[1][1]));
    float a1 = fmaxf(fmaxf(s[0][2], s[0][3]), fmaxf(s[1][2], s[1][3]));
    a0 = fmaxf(a0, __shfl_xor_sync(~0u, a0, 1)); a0 = fmaxf(a0, __shfl_xor_sync(~0u, a0, 2));
    a1 = fmaxf(a1, __shfl_xor_sync(~0u, a1, 1)); a1 = fmaxf(a1, __shfl_xor_sync(~0u, a1, 2));
    const float n0 = fmaxf(m0, a0), n1 = fmaxf(m1, a1);
    const float c0 = (m0 == n0) ? 1.f : ex2(m0 - n0), c1 = (m1 == n1) ? 1.f : ex2(m1 - n1);
    m0 = n0; m1 = n1;
    const uint32_t p0 = pack2(ex2(s[0][0] - n0), ex2(s[0][1] - n0)), p1 = pack2(ex2(s[0][2] - n1), ex2(s[0][3] - n1));
    const uint32_t p2 = pack2(ex2(s[1][0] - n0), ex2(s[1][1] - n0)), p3 = pack2(ex2(s[1][2] - n1), ex2(s[1][3] - n1));
    l0 = l0 * c0 + bf_lo(p0) + bf_hi(p0) + bf_lo(p2) + bf_hi(p2);
    l1 = l1 * c1 + bf_lo(p1) + bf_hi(p1) + bf_lo(p3) + bf_hi(p3);
#pragma unroll
    for (int j = 0; j < 4; j++) {
      o[j][0] *= c0; o[j][1] *= c0; o[j][2] *= c1; o[j][3] *= c1;
      const unsigned short* vp = (const unsigned short*)(vb + (size_t)(k0 + 2 * qd) * 32 + j * 8 + g);
      const uint32_t b0 = (uint32_t)__ldcg(vp) | ((uint32_t)__ldcg(vp + 32) << 16);
      const uint32_t b1 = (uint32_t)__ldcg(vp + 256) | ((uint32_t)__ldcg(vp + 288) << 16);
      mma16816(o[j], p0, p1, p2, p3, b0, b1);
    }
  }
  l0 += __shfl_xor_sync(~0u, l0, 1); l0 += __shfl_xor_sync(~0u, l0, 2);
  l1 += __shfl_xor_sync(~0u, l1, 1); l1 += __shfl_xor_sync(~0u, l1, 2);
#pragma unroll
  for (int j = 0; j < 4; j++) { res[4 * j] = o[j][0]; res[4 * j + 1] = o[j][1]; res[4 * j + 2] = o[j][2]; res[4 * j + 3] = o[j][3]; }
  res[16] = l0; res[18] = l1;
}

__global__ void __cluster_dims__(2, 1, 1) __launch_bounds__(384, 1) fused_kernel(const __grid_constant__ Params prm) {
  extern __shared__ __align__(1024) char smem[];
  const uint32_t sb = (uint32_t)__cvta_generic_to_shared(smem);
  const int tid = threadIdx.x;
  const int wid = __shfl_sync(0xffffffffu, tid >> 5, 0), wg = wid >> 2, w = wid & 3;
  const int bm = remap(blockIdx.x) >> 4, bn = remap(blockIdx.x) & 15;
  auto first_tile = [&](int kt) {
    e_expect_tx(sb + B_QF + 8 * kt, QSTG);
    tma_ld(sb + kt * QSTG, &prm.m[M_X0A], kt * 64, bm * 256, sb + B_QF + 8 * kt);
    tma_ld3(sb + kt * QSTG + 32768, &prm.m[M_WQA], bn * 64, kt * 64, 0, sb + B_QF + 8 * kt);
  };
  if (wid == 8) {
    e_init(sb + B_QF, 1);
    asm volatile("fence.mbarrier_init.release.cluster;" ::: "memory");
    first_tile(0);
  }
  if (wid < 8) {
#pragma unroll
    for (int i = 0; i < 4; i++) {
      const uint32_t cnt = (uint32_t)((i == 0 ? 0x14112140 : i == 1 ? 0x04112141 : i == 2 ? 0x14412141 : 0x24412141) >> (4 * wid)) & 7;
      if (cnt) e_init(sb + BARS + 32 * wid + 8 * i, cnt);
    }
    if (wid < 3) e_init(sb + B_QD + wid * 8, wid < 2 ? 1 : 2);
    if (tid == 255) { *(uint2*)(smem + W_X) = make_uint2(0u, 0u); *(uint2*)(smem + W_C) = make_uint2(0xF8000080u, 0xF8000080u); }
    asm volatile("fence.mbarrier_init.release.cluster;" ::: "memory");
  }
  const uint32_t epoch = *(volatile uint32_t*)prm.epoch;
  __syncthreads();
  asm volatile("barrier.cluster.arrive.relaxed.aligned;" ::: "memory");

  if (wg == 2) {
    asm volatile("setmaxnreg.dec.sync.aligned.u32 56;");
    const uint32_t ep1 = epoch + 1;
    if (w == 0) {
      first_tile(1);
      mbar_wait(sb + B_QF, 0);
      first_tile(2); first_tile(3);
#pragma unroll 1
      for (int kt = 4; kt < 16; kt++) l2_prefetch(prm.wq[0] + kt * 196608 + blockIdx.x * 1536, 3072);
      cluster_wait();
#pragma unroll 1
      for (int l = 0; l < 4; l++) {
        IDS();
        const CUtensorMap* mw = &prm.m[M_WQA + (l & 1)];
        const CUtensorMap* mh = &prm.m[l == 0 ? M_X0H : M_XSO];
        const CUtensorMap* mo = &prm.m[M_WOA + (l & 1)];
        auto q_b = [&](int i) {
          const int s = i & 3;
          mbar_wait(sb + B_QE + 8 * s, ((i >> 2) & 1) ^ 1);
          e_expect_tx(sb + B_QF + 8 * s, QSTG);
          tma_ld3(sb + s * QSTG + 32768, mw, bn * 64, qord(i, l, pn) * 64, 0, sb + B_QF + 8 * s);
        };
        uint32_t rdy = l ? 0u : ~0u;
        auto q_a = [&](int i) {
          const int kt = qord(i, l, pn);
          await_bit(sb + W_X, l, kt >> 1, rdy);
          tma_ld_mc(sb + (i & 3) * QSTG + rank * 16384, mh, kt * 64, bm * 256 + rank * 128, sb + B_QF + 8 * (i & 3));
        };
        if (l > 0) {
#pragma unroll 1
          for (int i = 0; i < 4; i++) {
            const int kt = qord(i, l, pn);
            await_bit(sb + W_X, l, kt >> 1, rdy);
            e_expect_tx(sb + B_QF + 8 * i, 16384);
            tma_ld(sb + i * QSTG + (po ^ 1) * 16384, &prm.m[M_XSO], kt * 64, (pm ^ 1) * 128, sb + B_QF + 8 * i);
          }
        }
#pragma unroll 1
        for (int i = 4; i < 16; i++) {
          q_b(i); q_a(i);
          if (l == 0 && i >= 8 && i < 12) l2_prefetch(prm.wq[1] + (blockIdx.x * 4 + i - 8) * 6144, 12288);
          if (l < 2 && i == 12) l2_prefetch(prm.wo[l] + blockIdx.x * 8192, 16384);
        }
        if (l & 1) {
          if (l == 3) poll_ge(cnt_ad(bn), ep1 * 16);
          const int krow = 2 * bn * 2048 + bm * 256;
          uint32_t* kvc = cnt_kv(l >> 1, bn);
#pragma unroll 1
          for (int m = 1; m >= 0; m--) {
            bar_sync(m ? NB_ST : NB_KV, 288);
#pragma unroll
            for (int i = 0; i < 4; i++) tma_st(&prm.m[M_K4 + (i >> 1)], 0, krow + (i & 1) * 128 + m * 64, sb + T0 + i * 8192 + m * 4096);
            if (m) {
              sts128(sb + ONES + lane * 32, 0x3f803f80u, 0x3f803f80u, 0x3f803f80u, 0x3f803f80u);
              sts128(sb + ONES + lane * 32 + 16, 0x3f803f80u, 0x3f803f80u, 0x3f803f80u, 0x3f803f80u);
              fence_async_smem();
              __syncwarp();
            }
          }
          e_arrive(sb + B_TF);
          bulk_commit(); bulk_wait_n<0>();
          e_red(kvc + bm);
          bar_sync(NB_KV + 12, 288);
          uint32_t seen = 0;
#pragma unroll 1
          for (int it = 1; it < 16; it++) {
            const int s = it & 3, blk = it;
            if (it == 4) { tma_st(&prm.m[M_K], 0, krow + 2048, sb); tma_st(&prm.m[M_V], 0, krow + 2048, sb + 16384); bulk_commit(); }
            if (it == 5) { bulk_wait_n<0>(); e_red(kvc + bm); }
            if (it == 12) { e_expect_tx(sb + B_RF, 32768); tma_ld3(sb, &prm.m[M_XSR], 0, pm * 128, 2 * pn, sb + B_RF); }
            if (it == 2 || it == 3) mbar_wait(sb + B_TF + 8 * (it - 1), 0);
            mbar_wait_long(sb + B_TE + 8 * s, ((it >> 2) & 1) ^ 1);
            if (it < 8) {
#pragma unroll 1
              for (uint32_t n = 0; n < 200000u && !((seen >> it) & 1); n++)
                seen = __ballot_sync(~0u, (int)(ld_acquire(kvc + ((bm + lane) & 7)) - (ep1 * 2 - 1)) >= 0);
              fence_async_gl();
            } else if (it == 8) { poll_ge(kvc + (lane & 7), ep1 * 2); fence_async_gl(); bar_arrive(NB_HALO, 64); }
            else if (it == 15) bar_arrive(NB_HALO + 1, 64);
            const int row = (2 * bn + (it >> 3)) * 2048 + ((bm + blk) & 7) * 256;
            e_expect_tx(sb + B_TF + 8 * s, 32768);
            tma_ld(sb + T0 + s * TSTG, &prm.m[M_K], 0, row, sb + B_TF + 8 * s);
            tma_ld(sb + T0 + s * TSTG + 16384, &prm.m[M_V], 0, row, sb + B_TF + 8 * s);
          }
        }
        auto p_b = [&](int i, uint32_t s, uint32_t par) {
          const int kt = pord(i, l, bn >> 1);
          mbar_wait(sb + B_PE + 8 * s, par ^ 1);
          e_expect_tx(sb + B_PF + 8 * s, PSTG);
          tma_ld5(sb + pslot_b(s, l), mo, kt >> 3, 2 * (kt & 7), 2 * pn, sb + B_PF + 8 * s);
        };
        auto p_a = [&](int i, uint32_t s) {
          const int kt = pord(i, l, bn >> 1);
          await_bit(sb + W_O, l + 1, kt, rdy);
          tma_ld_mc(sb + pslot_a(s, l) + rank * 8192, &prm.m[M_OS], kt * 64, pm * 128 + rank * 64, sb + B_PF + 8 * s);
        };
        auto p_a2 = [&](int i) {
          const int kt = pord(i, l, bn >> 1);
          await_bit(sb + W_O, l + 1, kt, rdy);
          tma_ld(sb + pslot_a(i, l), &prm.m[M_OS], kt * 64, pm * 128, sb + B_PF + 8 * i);
          tma_ld(sb + pslot_a(i, l) + 8192, &prm.m[M_OS], kt * 64, pm * 128 + 64, sb + B_PF + 8 * i);
        };
        rdy = 0;
        if (l & 1) {
#pragma unroll 1
          for (int u = 0; u < 6; u++) { const int i = (0x105432 >> (4 * u)) & 7; if (u == 4) mbar_wait_long(sb + B_TE, 1); p_b(i, i, i < 4 ? 1 : 0); }
#pragma unroll 1
          for (int u = 0; u < 6; u++) {
            const int i = (0x543120 >> (4 * u)) & 7;
            if (!(u & 1)) mbar_wait_long(sb + B_TE + 8 + 4 * u, 1);
            p_a2(i);
          }
        } else {
#pragma unroll 1
          for (int u = 0; u < 5; u++) { const int i = (0x32140 >> (4 * u)) & 7; if (!(u & 5)) mbar_wait(sb + B_QE + 8 + 4 * u, 1); p_b(i, i, 0); }
          mbar_wait(sb + B_QE + 24, 1);
          mbar_wait(sb + B_OW, (l >> 1) & 1);
          fence_async_gl();
          rdy = 1u << (bn >> 1);
#pragma unroll 1
          for (int i = 0; i < 4; i++) { p_a(i, i); }
          bar_sync(NB_DONE, 96);
          e_arrive_both(sb + B_PA);
          p_b(5, 5, 0);
          mbar_wait(sb + B_PA, (l >> 1) & 1);
          p_a(4, 4); p_a(5, 5);
        }
        uint32_t s = 0, lap = 1;
#pragma unroll 1
        for (int i = 6; i < 16; i++) {
          if (i == 12 && !(l & 1)) { e_expect_tx(sb + B_RF, 32768); tma_ld3(sb, &prm.m[l == 0 ? M_X0R : M_XSR], 0, pm * 128, 2 * pn, sb + B_RF); }
          p_b(i, s, ((s < 4 ? l : 0) + lap) & 1);
          p_a(i, s);
          if (++s == 6) { s = 0; lap++; }
        }
        const CUtensorMap* mn = &prm.m[M_WQA + ((l + 1) & 1)];
        if (l < 3) {
          mbar_wait(sb + B_PE + 8 * 4, 1); mbar_wait(sb + B_PE + 8 * 5, 1);
          tma_ld3(sb + 32768, mn, bn * 64, 2 * pn * 64, 0, sb + B_QL);
          mbar_wait(sb + B_PE + 8 * 0, l & 1);
          tma_ld3(sb + QSTG + 32768, mn, bn * 64, (2 * pn + 1) * 64, 0, sb + B_QL);
          mbar_wait(sb + B_PE + 8 * 1, l & 1);
          e_expect_tx(sb + B_QD, 40960);
          tma_ld3(sb + 2 * QSTG + 32768, mn, bn * 64, ((2 * pn) ^ 2) * 64, 0, sb + B_QD);
          bar_sync(NB_X, 288);
          e_expect_tx(sb + B_QL, 49152);
          e_expect_tx(sb + B_QD + 8, 40960);
          tma_ld3(sb + 3 * QSTG + 32768, mn, bn * 64, (((2 * pn) ^ 2) + 1) * 64, 0, sb + B_QD + 8);
        }
      }
      if (blockIdx.x == 0 && lane_id() == 0) *(volatile uint32_t*)prm.epoch = ep1;
    } else {
      const int hw = w - 1;
      if (hw == 1 && lane_id() < M_COUNT) asm volatile("prefetch.tensormap [%0];" ::"l"(&prm.m[lane_id()]) : "memory");
      cluster_wait();
      mbar_wait(sb + B_QF, 0);
#pragma unroll 1
      for (int l = 0; l < 4; l++) {
        IDS();
        if (hw == 2 && l > 0) watch(cnt_x(l, bm) + (lane & 7), ep1 * 2, 0xFFu, l, sb + W_X);
        if (l == 0) {
#pragma unroll 1
          for (int r = 2 * hw; r < 16; r += 6) {
            const uint4* p = (const uint4*)(prm.x0 + (size_t)(b * 16 + r) * 1024) + lane;
            float s1[2] = {0.f, 0.f}, s2[2] = {0.f, 0.f};
#pragma unroll
            for (int i = 0; i < 8; i++) {
              const uint4 v = __ldg(p + 32 * i);
              const uint32_t u[4] = {v.x, v.y, v.z, v.w};
#pragma unroll
              for (int k = 0; k < 4; k++) { const float a = bf_lo(u[k]), c = bf_hi(u[k]); s1[i >> 2] += a + c; s2[i >> 2] = fmaf(a, a, fmaf(c, c, s2[i >> 2])); }
            }
#pragma unroll
            for (int o = 16; o; o >>= 1)
#pragma unroll
              for (int rr = 0; rr < 2; rr++) { s1[rr] += __shfl_xor_sync(~0u, s1[rr], o); s2[rr] += __shfl_xor_sync(~0u, s2[rr], o); }
            if (lane == 0) *(float4*)&g_stats[b * 16 + r] = make_float4(s1[0], s2[0], s1[1], s2[1]);
          }
        }
        if (l == 1) { uint32_t rdy = 0; await_bit<true>(sb + W_X, 1, pn, rdy); mbar_hint(sb + B_QF + 8, 0); }
        if (l < 2) {
          float cs[8];
#pragma unroll
          for (int i = 0; i < 8; i++) cs[i] = 0.f;
          const uint4* wp = (const uint4*)(prm.wq[l] + (size_t)(bm * 128 + (lane >> 3)) * 3072 + hw * 1024 + bn * 64) + (lane & 7);
#pragma unroll 8
          for (int i = 0; i < 32; i++) {
            const uint4 v = __ldg(wp + (size_t)i * 4 * 384);
            cs[0] += bf_lo(v.x); cs[1] += bf_hi(v.x); cs[2] += bf_lo(v.y); cs[3] += bf_hi(v.y);
            cs[4] += bf_lo(v.z); cs[5] += bf_hi(v.z); cs[6] += bf_lo(v.w); cs[7] += bf_hi(v.w);
          }
#pragma unroll
          for (int i = 0; i < 8; i++) { cs[i] += __shfl_xor_sync(~0u, cs[i], 8); cs[i] += __shfl_xor_sync(~0u, cs[i], 16); }
          if (lane < 8) {
            float4* d = (float4*)(g_csp + ((l * 16 + bn) * 8 + bm) * 192 + hw * 64 + lane * 8);
            d[0] = make_float4(cs[0], cs[1], cs[2], cs[3]); d[1] = make_float4(cs[4], cs[5], cs[6], cs[7]);
          }
          __syncwarp();
          asm volatile("fence.acq_rel.gpu;" ::: "memory");
          e_red_relaxed(cnt_cs(l, bn));
          if (l == 0) e_red_relaxed(cnt_x(0, bm) + pn);
          poll_ge(lane < 8 && l == 0 ? cnt_x(0, bm) + lane : cnt_cs(l, bn), ep1 * (lane < 8 && l == 0 ? 6 : 24));
        }
        if (l > 0) {
          uint32_t rdy = 0;
#pragma unroll 1
          for (int j = 0; j < 8; j++) await_bit<true>(sb + W_X, l, j, rdy);
        }
#pragma unroll 1
        for (int it = hw * 32 + lane; it < 176; it += 96) {
          const bool rows = it < 128;
          const float4* p = rows ? (const float4*)(g_stats + bm * 256) + it : (const float4*)(g_csp + ((l & 1) * 16 + bn) * 8 * 192) + (it - 128);
          const int stride = rows ? 1024 : 48, np = rows && l == 0 ? 1 : 8;
          float4 a = make_float4(0.f, 0.f, 0.f, 0.f);
#pragma unroll
          for (int k = 0; k < 8; k++) if (k < np) { const float4 v = __ldcg(p + k * stride); a.x += v.x; a.y += v.y; a.z += v.z; a.w += v.w; }
          if (rows) {
            const float m0 = a.x * (1.f / 1024.f), m1 = a.z * (1.f / 1024.f);
            const float v0 = fmaxf(a.y * (1.f / 1024.f) - m0 * m0, 0.f), v1 = fmaxf(a.w * (1.f / 1024.f) - m1 * m1, 0.f);
            const float r0 = __fdividef(1.f, bf_round(sqrtf(bf_round(bf_round(v0) + 1e-5f)))), r1 = __fdividef(1.f, bf_round(sqrtf(bf_round(bf_round(v1) + 1e-5f))));
            *(float2*)(smem + RSTD + it * 8) = make_float2(r0, r1);
            *(uint32_t*)(smem + MEAN + it * 4) = pack2(-m0, -m1);
          } else {
            float2* d = (float2*)(smem + COLS) + ((it - 128) >> 2) * 8 + (it & 1) * 4 + ((it >> 1) & 1);
            d[0] = make_float2(a.y, a.x); d[2] = make_float2(a.w, a.z);
          }
        }
        __syncwarp();
        if (lane == 0) asm volatile("red.release.cta.shared.add.u32 [%0], 0x100;" ::"r"(sb + W_X) : "memory");
        if (hw == 2) {
          if (!(l & 1)) {
            bar_sync(NB_ST, 288);
            const volatile unsigned long long* hp = g_halo + ((size_t)(l >> 1) * 128 + b - 16) * 1024 + lane;
#pragma unroll 1
            for (int h = 0; h < 2; h++) {
              uint32_t t[16];
#pragma unroll
              for (int i = 0; i < 16; i++) t[i] = 0;
#pragma unroll 1
              for (uint32_t n = bm ? 0 : 100000u; n < 100000u; n++) {
                uint32_t miss = 0;
#pragma unroll
                for (int i = 0; i < 16; i++) {
                  const unsigned long long v = hp[h * 512 + i * 32];
                  t[i] = (uint32_t)v; miss |= (uint32_t)(v >> 32) ^ ep1;
                }
                if (__all_sync(~0u, !miss)) break;
              }
              const uint32_t r = (lane & 7) + ((lane >> 3) & 1) * 8, rv = lane >> 2;
#pragma unroll
              for (int jj = 0; jj < 2; jj++) stsm4(sb + 2 * h * ASC + r * 64 + (((2 * jj + (lane >> 4)) ^ ((r >> 1) & 3)) << 4), t[4 * jj], t[4 * jj + 1], t[4 * jj + 2], t[4 * jj + 3]);
              const uint32_t ad = sb + (2 * h + 1) * ASC + rv * 64 + (((lane & 3) ^ ((rv >> 1) & 3)) << 4);
              sts128(ad, t[8], t[10], t[12], t[14]); sts128(ad + 512, t[9], t[11], t[13], t[15]);
              bar_arrive(NB_HALO + h, 64);
            }
          } else {
            bar_sync(NB_HALO, 64);
            const uint4* kp = (const uint4*)(g_kn + ((l >> 1) * 128 + bn * 8) * 32) + 2 * lane;
            const uint4 v = __ldcg(kp), u = __ldcg(kp + 1);
            const uint32_t mx = max(max(max(v.x, v.y), max(v.z, v.w)), max(max(u.x, u.y), max(u.z, u.w)));
            const uint32_t m0 = __reduce_max_sync(~0u, (lane & 2) ? 0u : mx), m1 = __reduce_max_sync(~0u, (lane & 2) ? mx : 0u);
            if (lane == 0) *(uint2*)(smem + KMAX) = make_uint2(m0, m1);
            __syncwarp();
            bar_arrive(NB_KN, 160); bar_arrive(NB_KN + 1, 160);
            bar_sync(NB_HALO + 1, 64);
            watch(cnt_o(l, pm, 0) + (lane & 7), ep1 * 2, 0xFFu, l + 1, sb + W_O);
          }
        } else {
          bar_sync(NB_SIG + 2 * hw, 160); bar_sync(NB_SIG + 2 * hw + 1, 160);
          if (!(l & 1)) bar_arrive(NB_DONE, 96);
          if (hw == (l & 1)) bar_arrive((l & 1) ? NB_DONE : NB_KN, 64);
          asm volatile("fence.acq_rel.gpu;" ::: "memory");
          e_red_relaxed(cnt_o(l, 2 * bm, hw) + (bn >> 1));
          e_red_relaxed(cnt_o(l, 2 * bm + 1, hw) + (bn >> 1));
          if (hw == 0 && !(l & 1)) e_arrive_both(sb + B_OW);
          if (hw == 1 && l == 1) { e_red_relaxed(cnt_ad(bn)); e_red_relaxed(cnt_ad(bn)); }
        }
        if (hw == 2) { bar_sync((l & 1) ? NB_DONE : NB_KN, 64); watch(cnt_o(l, pm, (lane >> 3) & 1) + (lane & 7), ep1 * 2, 0xFFFFu, l + 1, sb + W_O); }
        if (l < 3) {
          bar_sync(NB_X0, 352);
          if (hw == 0) {
            e_red(cnt_x(l + 1, bm) + pn);
          } else if (hw == 1) {
            mbar_wait(sb + B_PE + 8 * 3, l & 1);
            push_peer(sb + 2 * QSTG + po * 16384, sb + po * 16384, sb + B_QD, rank ^ 1);
            push_peer(sb + 3 * QSTG + po * 16384, sb + QSTG + po * 16384, sb + B_QD + 8, rank ^ 1);
          }
        }
      }
    }
  } else {
    asm volatile("setmaxnreg.inc.sync.aligned.u32 224;");
    const uint32_t zero = prm.zero;
    cluster_wait();
    const uint32_t ep1 = __shfl_sync(~0u, epoch + 1, 0);
#pragma unroll 1
    for (int l = 0; l < 4; l++) {
      {
        float acc[2][96];
#pragma unroll
        for (int i = 0; i < 96; i++) { acc[0][i] = 0.f; acc[1][i] = 0.f; }
        fence_regs(acc[0]); fence_regs(acc[1]);
        const bool early = l > 0 && wg == ((cta_id() >> 3) & 1);
#pragma unroll 1
        for (int kt = 0; kt < 14; kt++) {
          const int s = kt & 3;
          if (l > 0 && kt < 4 && kt != 1) mbar_wait(sb + (kt ? B_QD - 16 + 8 * kt : B_QL), (l + 1) & 1);
          if (!(early && kt < 4)) mbar_wait(sb + B_QF + 8 * s, (kt >> 2) & 1);
          const uint64_t da = mkdesc(sb + s * QSTG + wg * 16384, 16, 1024, 1), db = mkdesc(sb + s * QSTG + 32768, 8192, 1024, 1);
          wg_fence();
#pragma unroll
          for (int k = 0; k < 4; k++)
#pragma unroll
            for (int m = 0; m < 2; m++) wgmma_m64n192k16_ss_tb(acc[m], da + m * 512 + k * 2, db + k * 128, 1);
          wg_commit();
          wg_wait<1>();
          if (early && kt < 5) {
#pragma unroll 1
            for (int i = kt == 3 ? 0 : 3; i < kt; i++) { mbar_wait(sb + B_QF + 8 * i, 0); if (w == 0) e_arrive_both(sb + B_QE + 8 * i); }
          } else if (kt > 0 && w == 0) e_arrive_both(sb + B_QE + 8 * ((kt - 1) & 3));
          if (kt == 11 + 2 * wg) {
#pragma unroll 1
            for (uint32_t n = 0; n < 4000000u; n++) {
              uint32_t v;
              asm volatile("ld.acquire.cta.shared.u32 %0, [%1];" : "=r"(v) : "r"(sb + W_X) : "memory");
              if ((v >> 8) == (uint32_t)(l * 256 + 3)) break;
            }
            const int lane = lane_id();
            float nm[4];
#pragma unroll
            for (int i = 0; i < 4; i++) nm[i] = bf_lo(*(volatile unsigned short*)(smem + MEAN + (wg * 128 + w * 16 + (lane >> 2) + (i >> 1) * 64 + (i & 1) * 8) * 2));
            wg_wait<0>();
            fence_regs(acc[0]); fence_regs(acc[1]);
#pragma unroll
            for (int j = 0; j < 12; j++) {
              const float4 c = lds128f(sb + COLS + j * 64 + (lane & 3) * 16);
#pragma unroll
              for (int m = 0; m < 2; m++) {
                float* a = &acc[m][8 * j];
                a[0] = fmaf(nm[2 * m], c.y, a[0]); a[1] = fmaf(nm[2 * m], c.x, a[1]); a[2] = fmaf(nm[2 * m + 1], c.y, a[2]); a[3] = fmaf(nm[2 * m + 1], c.x, a[3]);
                a[4] = fmaf(nm[2 * m], c.w, a[4]); a[5] = fmaf(nm[2 * m], c.z, a[5]); a[6] = fmaf(nm[2 * m + 1], c.w, a[6]); a[7] = fmaf(nm[2 * m + 1], c.z, a[7]);
              }
            }
            fence_regs(acc[0]); fence_regs(acc[1]);
          }
        }
        auto part = [&](int s, int m, int k0, int k1) {
          const uint64_t da = mkdesc(sb + s * QSTG + wg * 16384 + m * 8192, 16, 1024, 1), db = mkdesc(sb + s * QSTG + 32768, 8192, 1024, 1);
          wg_fence();
#pragma unroll
          for (int k = k0; k < k1; k++) wgmma_m64n192k16_ss_tb(acc[m], da + k * 2, db + k * 128, 1);
          wg_commit();
        };
        mbar_wait(sb + B_QF + 16, 1);
        part(2, 1, 0, 4);
        wg_wait<1>();
        if (w == 0) e_arrive_both(sb + B_QE + 8);
        if (!(l & 1)) bar_arrive(NB_ST, 288);
        mbar_wait(sb + B_QF + 24, 1);
        part(3, 1, 0, 4);
        part(2, 0, 0, 2);
        IDS();
        const int g = lane >> 2, qd = lane & 3;
        float rs[2][2];
#pragma unroll
        for (int i = 0; i < 4; i++) rs[i >> 1][i & 1] = lds32f(sb + RSTD + (wg * 128 + w * 16 + g + (i >> 1) * 64 + (i & 1) * 8) * 4);
        auto scale = [&](int gi, int m, float sc) {
          const float r0 = rs[m][0] * sc, r1 = rs[m][1] * sc;
#pragma unroll
          for (int i = 0; i < 16; i++) acc[m][16 * gi + i] *= (i & 2) ? r1 : r0;
        };
        auto pack_b = [&](int gi, int m, uint32_t (&t)[8]) {
#pragma unroll
          for (int i = 0; i < 8; i++) t[i] = pack2(acc[m][16 * gi + 2 * i], acc[m][16 * gi + 2 * i + 1]);
        };
        auto norm_tile = [&](int gi, int m, uint32_t (&t)[8]) { scale(gi, m, 1.f); pack_b(gi, m, t); };
        auto pack_h = [&](int gi, int m, uint32_t (&t)[8]) {
#pragma unroll
          for (int i = 0; i < 8; i++) t[i] = pack2h(acc[m][16 * gi + 2 * i], acc[m][16 * gi + 2 * i + 1]);
        };
        uint32_t q[2][2][8], qn[2][2];
        const uint32_t srow = (lane & 7) + ((lane >> 3) & 1) * 8;
        const uint32_t row0 = wg * 128 + w * 16;
        auto put_kv = [&](int h, int v, int m, const uint32_t (&t)[8]) {
          const uint32_t base = sb + ((l & 1) ? (h ? 0 : T0) + v * 16384 : (2 * h + v) * ASC + 1024) + (row0 + m * 64) * 64;
          if (!v) {
#pragma unroll
            for (int jj = 0; jj < 2; jj++) stsm4(base + srow * 64 + (((2 * jj + (lane >> 4)) ^ ((srow >> 1) & 3)) << 4), t[4 * jj], t[4 * jj + 1], t[4 * jj + 2], t[4 * jj + 3]);
          } else {
            const uint32_t ad = base + g * 64 + ((qd ^ (g >> 1)) << 4);
            sts128(ad, t[0], t[2], t[4], t[6]); sts128(ad + 512, t[1], t[3], t[5], t[7]);
          }
        };
        auto send_halo = [&](int h, int v, const uint32_t (&t)[8]) {
          unsigned long long* hp = g_halo + ((size_t)(l >> 1) * 128 + b) * 1024 + h * 512 + v * 256 + lane;
#pragma unroll
          for (int i = 0; i < 8; i++) st_tagged(hp + i * 32, t[i], ep1);
        };
        auto put_kn = [&](int h, int m, uint32_t kn) {
          if (lane == 0) g_kn[((l >> 1) * 128 + bn * 8 + bm) * 32 + 16 * h + 8 * m + wg * 4 + w] = __uint_as_float(kn);
        };
        auto conv_tile1 = [&](int h) {
          uint32_t t[8], tv[8], kn = NOT_F16;
          norm_tile(4 + h, 1, tv);
          put_kv(h, 1, 1, tv);
          scale(2 + h, 1, 1.f);
          part(2 + h, 0, 2, 4);
          if (l & 1) {
            float n[2] = {0.f, 0.f};
#pragma unroll
            for (int i = 0; i < 16; i++) n[(i >> 1) & 1] = fmaf(acc[1][32 + 16 * h + i], acc[1][32 + 16 * h + i], n[(i >> 1) & 1]);
            const float a = ((qd & 1) ? n[1] : n[0]) + __shfl_xor_sync(~0u, (qd & 1) ? n[0] : n[1], 1);
            scale(h, 1, QSCALE / 128.f);
            kn = f16_class(__reduce_max_sync(~0u, __float_as_uint(a + __shfl_xor_sync(~0u, a, 2))), K_LO);
            put_kn(h, 1, kn);
          } else scale(h, 1, 1.f);
          if (kn == NOT_F16) pack_b(2 + h, 1, t); else pack_h(2 + h, 1, t);
          put_kv(h, 0, 1, t);
          if (!(l & 1) && row0 == 176 && bm < 7) { send_halo(h, 0, t); send_halo(h, 1, tv); }
        };
        mbar_wait(sb + B_QE + 8, 1);
        wg_wait<1>();
        fence_regs(acc[1]);
        conv_tile1(0);
        part(3, 0, 0, 2);
        if (l & 1) { fence_async_smem(); bar_arrive(NB_ST, 288); }
        conv_tile1(1);
        wg_wait<2>();
        if (w == 0) e_arrive_both(sb + B_QE + 16);
        wg_wait<0>();
        fence_regs(acc[0]);
        if (w == 0) e_arrive_both(sb + B_QE + 24);
        bf16* const op0 = [&] { IDS(); return g_os + (size_t)(bm * 256 + row0 + (lane >> 2)) * 1024 + bn * 32 + (lane & 3) * 8; }();
        auto put_o = [&](int h, int m, const float (&o)[16], float i0, float i1) {
          bf16* op = op0 + m * 65536 + h * 512;
          const uint4 a = make_uint4(pack2(o[0] * i0, o[1] * i0), pack2(o[4] * i0, o[5] * i0), pack2(o[8] * i0, o[9] * i0), pack2(o[12] * i0, o[13] * i0));
          const uint4 c = make_uint4(pack2(o[2] * i1, o[3] * i1), pack2(o[6] * i1, o[7] * i1), pack2(o[10] * i1, o[11] * i1), pack2(o[14] * i1, o[15] * i1));
          *(uint4*)op = a; *(uint4*)(op + 8 * 1024) = c;
          const uint32_t hi = __vimax3_u16x2(__vimax3_u16x2(a.x, a.y, a.z), __vimax3_u16x2(a.w, c.x, c.y), __vmaxu2(c.z, c.w));
          const uint32_t lo = __vimax3_s16x2(__vimax3_s16x2(a.x, a.y, a.z), __vimax3_s16x2(a.w, c.x, c.y), __vmaxs2(c.z, c.w));
          return __vmaxu2(hi & 0x7FFF7FFFu, lo & 0x7FFF7FFFu);
        };
        if (!(l & 1)) {
          auto conv_kv = [&](int h) {
            uint32_t t[8];
            norm_tile(2 + h, 0, t); put_kv(h, 0, 0, t);
            norm_tile(4 + h, 0, t); put_kv(h, 1, 0, t);
          };
          conv_kv(0);
          norm_tile(0, 0, q[0][0]); pack_b(0, 1, q[0][1]);
          bar_sync(NB_SC, 256);
          const bool e = g & 1, sel = 2 * qd + (g & 1) >= g + 2, first = bm == 0 && row0 == 0;
          const uint32_t pm_a = e ? 0x1044 : 0x4410, pm_b = e ? 0x3244 : 0x4432, pm_lo = sel ? pm_b : 0x4444, pm_hi = sel ? 0x4444 : pm_b;
          const uint32_t ka = sb + (row0 + (lane & 7)) * 64 + (((lane >> 3) ^ ((lane >> 1) & 3)) << 4);
          const uint32_t va0 = sb + ASC + (row0 + srow) * 64 + (((lane >> 4) ^ ((lane >> 1) & 3)) << 4);
#pragma unroll 1
          for (int h = 0; h < 2; h++) {
            if (row0 == 0) bar_sync(NB_HALO + h, 64);
            float s[2][4][4];
            uint32_t vf[2][4][4], pf[2][2][4];
#pragma unroll
            for (int m = 0; m < 2; m++)
#pragma unroll
              for (int nt = 0; nt < 4; nt++) {
                uint32_t kf[4];
                ldsm4(ka + h * (2 * ASC) + (m * 64 + 8 * nt) * 64, kf);
                s[m][nt][0] = s[m][nt][1] = s[m][nt][2] = s[m][nt][3] = 0.f;
                mma16816(s[m][nt], q[0][m][0], q[0][m][1], q[0][m][2], q[0][m][3], kf[0], kf[1]);
                mma16816(s[m][nt], q[0][m][4], q[0][m][5], q[0][m][6], q[0][m][7], kf[2], kf[3]);
              }
#pragma unroll
            for (int m = 0; m < 2; m++)
#pragma unroll
              for (int i = 0; i < 4; i++) {
                ldsm4t(((va0 + h * (2 * ASC)) ^ (32 * (i & 1))) + (m * 64 + 16 * (i >> 1)) * 64, vf[m][i]);
              }
            float va[4], vb[4], mx[4];
            uint32_t ua[2], ub[2], um[2];
#pragma unroll
            for (int m = 0; m < 2; m++) {
              float a[2], c[2];
#pragma unroll
              for (int hh = 0; hh < 2; hh++) {
                a[hh] = e ? s[m][hh + 1][2 * hh + 1] : s[m][hh + 1][2 * hh];
                const float lo = e ? s[m][hh][2 * hh + 1] : s[m][hh][2 * hh], hi = e ? s[m][hh + 2][2 * hh + 1] : s[m][hh + 2][2 * hh];
                c[hh] = sel ? lo : hi;
              }
              ua[m] = scale_bf2(pack2(a[0], a[1])); ub[m] = scale_bf2(pack2(c[0], c[1]));
              if (m == 0) { ua[0] = first ? (ua[0] & 0xFFFF0000u) | 0xFF80u : ua[0]; ub[0] = first && sel ? 0xFF80FF80u : ub[0]; }
              um[m] = max_bf2(ua[m], ub[m]);
            }
#pragma unroll
            for (int m = 0; m < 2; m++) um[m] = max_bf2(um[m], __shfl_xor_sync(~0u, um[m], 1));
#pragma unroll
            for (int m = 0; m < 2; m++) um[m] = max_bf2(um[m], __shfl_xor_sync(~0u, um[m], 2));
#pragma unroll
            for (int i = 0; i < 4; i++) {
              const int m = i >> 1;
              const float top = (i & 1) ? bf_hi(um[m]) : bf_lo(um[m]);
              va[i] = ex2((((i & 1) ? bf_hi(ua[m]) : bf_lo(ua[m])) - top) * 1.4426950408889634f);
              vb[i] = ex2((((i & 1) ? bf_hi(ub[m]) : bf_lo(ub[m])) - top) * 1.4426950408889634f);
              mx[i] = va[i] + vb[i];
            }
#pragma unroll
            for (int i = 0; i < 4; i++) mx[i] += __shfl_xor_sync(~0u, mx[i], 1);
#pragma unroll
            for (int i = 0; i < 4; i++) mx[i] += __shfl_xor_sync(~0u, mx[i], 2);
#pragma unroll
            for (int i = 0; i < 4; i++) {
              const int m = i >> 1, hh = i & 1;
              const float inv = rcp(mx[i]);
              const uint32_t t = pack2(va[i] * inv, vb[i] * inv);
              pf[m][hh][hh + 1] = __byte_perm(t, 0, pm_a); pf[m][hh][hh] = __byte_perm(t, 0, pm_lo); pf[m][hh][hh + 2] = __byte_perm(t, 0, pm_hi); pf[m][hh][3 - 3 * hh] = t & zero;
            }
#pragma unroll
            for (int m = 0; m < 2; m++) {
              float o[4][4];
#pragma unroll
              for (int j = 0; j < 4; j++) o[j][0] = o[j][1] = o[j][2] = o[j][3] = 0.f;
#pragma unroll
              for (int i = 0; i < 4; i++) {
                const int kk = i >> 1, jj = 2 * (i & 1);
                mma16816(o[jj], pf[m][0][2 * kk], pf[m][1][2 * kk], pf[m][0][2 * kk + 1], pf[m][1][2 * kk + 1], vf[m][i][0], vf[m][i][1]);
                mma16816(o[jj + 1], pf[m][0][2 * kk], pf[m][1][2 * kk], pf[m][0][2 * kk + 1], pf[m][1][2 * kk + 1], vf[m][i][2], vf[m][i][3]);
              }
              const float of[16] = {o[0][0], o[0][1], o[0][2], o[0][3], o[1][0], o[1][1], o[1][2], o[1][3], o[2][0], o[2][1], o[2][2], o[2][3], o[3][0], o[3][1], o[3][2], o[3][3]};
              put_o(h, m, of, 1.f, 1.f);
            }
            bar_arrive(NB_SIG + 2 * h + wg, 160);
            if (h == 0) {
              conv_kv(1);
              norm_tile(1, 0, q[0][0]); pack_b(1, 1, q[0][1]);
              bar_sync(NB_SC, 256);
            }
          }
        } else {
          auto conv_h = [&](int gi, int m, uint32_t (&t)[8]) {
            pack_h(gi, m, t);
            float d0[4] = {0.f, 0.f, 0.f, 0.f}, d1[4] = {0.f, 0.f, 0.f, 0.f};
            if (gi == 2) {
              mma16816h(d0, t[0], t[1], t[2], t[3], t[0], t[2]); mma16816h(d1, t[0], t[1], t[2], t[3], t[1], t[3]);
              mma16816h(d0, t[4], t[5], t[6], t[7], t[4], t[6]); mma16816h(d1, t[4], t[5], t[6], t[7], t[5], t[7]);
            } else {
#pragma unroll
              for (int i = 0; i < 8; i += 2) { mma1688h(d0, t[i], t[i + 1], t[i]); mma1688h(d1, t[i], t[i + 1], t[i + 1]); }
            }
            return f16_class(__reduce_max_sync(~0u, max(max(__float_as_int(d0[0]), __float_as_int(d0[1])), max(__float_as_int(d1[2]), __float_as_int(d1[3])))), K_LO);
          };
          uint32_t tk[8], tv[8];
          scale(2, 0, 1.f);
          uint32_t kn = conv_h(2, 0, tk);
          norm_tile(4, 0, tv);
          put_kv(0, 1, 0, tv);
          put_kn(0, 0, kn);
          if (kn == NOT_F16) pack_b(2, 0, tk);
          put_kv(0, 0, 0, tk);
          fence_async_smem();
          bar_arrive(NB_KV, 288);
          mbar_wait(sb + B_QF + 24, 1);
          scale(3, 0, 1.f); scale(0, 0, QSCALE); scale(1, 0, QSCALE);
          kn = conv_h(3, 0, tk);
#pragma unroll
          for (int i = 0; i < 4; i++) qn[i >> 1][i & 1] = conv_h(i >> 1, i & 1, q[i >> 1][i & 1]);
          norm_tile(5, 0, tv);
          if (max(max(max(qn[0][0], qn[0][1]), max(qn[1][0], qn[1][1])), kn) == NOT_F16) {
#pragma unroll
            for (int i = 0; i < 4; i++) if (qn[i >> 1][i & 1] == NOT_F16) pack_b(i >> 1, i & 1, q[i >> 1][i & 1]);
            if (kn == NOT_F16) pack_b(3, 0, tk);
          }
          fence_regs(tv);
          const bool elected = w == 0 && lane == 0;
          uint32_t thr = elected ? 8 : 99;
          asm volatile("" : "+r"(thr));
          thr |= zero;
          uint2 cp;
          asm volatile("ld.shared.v2.u32 {%0, %1}, [%2];" : "=r"(cp.x), "=r"(cp.y) : "r"(sb + W_C));
          const uint64_t kd0 = mkdesc(sb + T0, 16, 512, 2);
          const uint64_t vd0 = mkdesc(sb + T0 + 16384, ONES - (T0 + 16384), 512, 2);
          const uint32_t v0 = (uint32_t)vd0 ^ zero;
          constexpr uint64_t VSTEP = 64 - (64ull << 16);
          float o[2][20], SA[2][16];
          uint32_t SB[2][8], PA[4], PB[4];
          auto qka = [&](int b, int k, uint64_t d, int h = 0) { wgmma_m64n32k16_rs_nb_h(SA[b], q[h][0][4 * k], q[h][0][4 * k + 1], q[h][0][4 * k + 2], q[h][0][4 * k + 3], d + 2 * k, k ? 1 : zero); };
          auto qkb = [&](int b, int k, uint64_t d, int h = 0) { wgmma_m64n32k16_rs_nb_hh(SB[b], q[h][1][4 * k], q[h][1][4 * k + 1], q[h][1][4 * k + 2], q[h][1][4 * k + 3], d + 2 * k, k ? 1 : zero); };
          auto qk = [&](int b, int k, uint64_t d, int h = 0) { qka(b, k, d, h); qkb(b, k, d, h); };
          auto pv = [&](int m, const uint32_t (&Px)[4], uint64_t vd, int keep = 1) { wgmma_m64n40k16_rs_tb(o[m], Px[0], Px[1], Px[2], Px[3], vd, keep); };
          mbar_wait(sb + B_TF, 0);
#pragma unroll
          for (int i = 0; i < 4; i++) PA[i] = PB[i] = zero;
          wg_fence();
          wgmma_m64n40k16_rs_tb_z(o[0], PA[0], PA[1], PA[2], PA[3], vd0, 0); wgmma_m64n40k16_rs_tb_z(o[1], PB[0], PB[1], PB[2], PB[3], vd0 + VSTEP, 0);
#pragma unroll
          for (int b = 1; b >= 0; b--) {
            wgmma_m64n32k16_rs_nb_z_h(SA[b], q[0][0][0], q[0][0][1], q[0][0][2], q[0][0][3], kd0 + 128 * b, 0);
            wgmma_m64n32k16_rs_nb_z_hh(SB[b], q[0][1][0], q[0][1][1], q[0][1][2], q[0][1][3], kd0 + 128 * b, 0);
          }
          qk(0, 1, kd0); wg_commit();
          put_kv(1, 1, 0, tv); put_kv(1, 0, 0, tk); put_kn(1, 0, kn);
          fence_async_smem();
          bar_arrive(NB_KV + 12, 288);
          wg_wait<0>();
          fence_regs(SA[0]); fence_regs(SB[0]); fence_regs(SA[1]); fence_regs(SB[1]); fence_regs(o[0]); fence_regs(o[1]);
#pragma unroll 1
          for (int pass = 0; pass < 2; pass++) {
            uint32_t kc = (uint32_t)kd0, vc = v0, vp = v0, pars = 0x78u | pass << 7;
#pragma unroll 1
            for (uint32_t it = 8; it <= 64; it += 8) {
              const uint32_t s8 = it & 24, par = pars & 1, kn = (uint32_t)kd0 + s8 * 256, tf = (sb + B_TF) ^ s8;
              const uint64_t hi = kd0 & 0xFFFFFFFF00000000ull, kd = hi | kc, vd = hi | vc, kdn = hi | kn, vdp = hi | vp;
              kc = kn; vp = vc + (uint32_t)(15 * VSTEP); vc = v0 + s8 * (uint32_t)(4 * VSTEP); pars >>= 1;
              bool landed = false;
#pragma unroll
              for (int r = 0; r < 16; r++) {
                const int c = r >> 1, ro = r & 1;
                if (r == 14 && !landed) mbar_wait(tf, par);
                wg_fence();
                const uint64_t kx = c < 7 ? kd + (c + 1) * 128 : kdn, vx = r ? vd + (r - 1) * VSTEP : vdp;
                const int keep = r || it != 8;
                if (ro) { qkb(~c & 1, 1, kx); pv(0, PA, vx, keep); pv(1, PB, vx, keep); qka(~c & 1, 1, kx); }
                else { pv(1, PB, vx, keep); qka(~c & 1, 0, kx); qkb(~c & 1, 0, kx); pv(0, PA, vx, keep); }
                wg_commit();
                if (r == 7) landed = mbar_test(tf, par);
#pragma unroll
                for (int i = 0; i < 4; i++) PB[i] = exp2_h2(SB[c & 1][4 * ro + i], (i & 1) ? cp.x : cp.y);
#pragma unroll
                for (int i = 0; i < 4; i++) { const float e0 = ex2(SA[c & 1][8 * ro + 2 * i]); PA[i] = pack2(e0, ex2(SA[c & 1][8 * ro + 2 * i + 1])); }
                if (ro) { wg_wait<0>(); fence_regs(SA[~c & 1]); fence_regs(SB[~c & 1]); } else wg_wait<1>();
                if (r == 5) arrive_if_gt(tf ^ 0x30, it, thr);
              }
            }
            int badm = 0;
            wg_fence();
            pv(0, PA, vd0 + 111 * VSTEP); pv(1, PB, vd0 + 111 * VSTEP); wg_commit();
            qk(0, 0, kd0, 1); qk(0, 1, kd0, 1); wg_commit();
            if (pass == 0) bar_sync(NB_KN + wg, 160);
            const float kmax = *(volatile float*)(smem + KMAX + 4 * pass);
            wg_wait<1>(); fence_regs(o[0]); fence_regs(o[1]);
            if (w == 0) e_arrive(sb + B_TE + 8 * 3);
#pragma unroll
            for (int m = 0; m < 2; m++) {
              const float of[16] = {o[m][0], o[m][1], o[m][2], o[m][3], o[m][4], o[m][5], o[m][6], o[m][7], o[m][8], o[m][9], o[m][10], o[m][11], o[m][12], o[m][13], o[m][14], o[m][15]};
              const uint32_t chk = put_o(pass, m, of, rcp(o[m][16]), rcp(o[m][18]));
              const bool bad = !(__uint_as_float(qn[0][m]) * kmax <= (m ? 0.875f * 0.875f : 112.f * 112.f)) || !(fminf(o[m][16], o[m][18]) >= 9.3e-10f) ||
                               !(o[m][16] + o[m][18] <= 3e38f) || ((chk + 0x00800080u) & 0x80008000u);
              badm |= __any_sync(~0u, bad) << m;
            }
            wg_wait<0>(); fence_regs(SA[0]); fence_regs(SB[0]);
            if (badm) {
#pragma unroll 1
              for (int m = 0; m < 2; m++) if ((badm >> m) & 1) {
                uint32_t qq[8]; float res[20];
#pragma unroll
                for (int i = 0; i < 8; i++) { qq[i] = m ? q[0][1][i] : q[0][0][i]; if ((m ? qn[0][1] : qn[0][0]) != NOT_F16) qq[i] = h2_to_bf2(qq[i]); }
                attn_slow(qq, m ? 128.f : 1.f, 2 * (cta_id() & 15) + pass, g_kn + ((l >> 1) * 128 + (cta_id() & 15) * 8) * 32 + 16 * pass, res, lane_id());
                const float of[16] = {res[0], res[1], res[2], res[3], res[4], res[5], res[6], res[7], res[8], res[9], res[10], res[11], res[12], res[13], res[14], res[15]};
                put_o(pass, m, of, rcp(res[16]), rcp(res[18]));
              }
            }
            bar_arrive(NB_SIG + 2 * pass + wg, 160);
            qn[0][0] = qn[1][0]; qn[0][1] = qn[1][1];
#pragma unroll
            for (int m = 0; m < 2; m++)
#pragma unroll
              for (int i = 0; i < 8; i++) q[0][m][i] = q[1][m][i];
#pragma unroll
            for (int i = 0; i < 4; i++) PA[i] = PB[i] = zero;
          }
        }
      }
      {
        float acc[64];
#pragma unroll
        for (int i = 0; i < 64; i++) acc[i] = 0.f;
        fence_regs(acc);
        uint32_t s = 0, lap = 0;
#pragma unroll 1
        for (int kt = 0; kt < 16; kt++) {
          mbar_wait(sb + B_PF + 8 * s, ((s < 4 ? l : 0) + lap) & 1);
          const uint64_t da = mkdesc(sb + pslot_a(s, l) + wg * 8192, 16, 1024, 1), db = mkdesc(sb + pslot_b(s, l), 8192, 1024, 1);
          wg_fence();
#pragma unroll
          for (int k = 0; k < 4; k++) wgmma_m64n128k16_ss_tb(acc, da + k * 2, db + k * 128, 1);
          wg_commit();
          wg_wait<1>();
          if (kt > 0 && w == 0) e_arrive_both(sb + B_PE + 8 * (s ? s - 1 : 5));
          if (++s == 6) { s = 0; lap++; }
        }
        IDS();
        const int g = lane >> 2, qd = lane & 3;
        const int r0 = wg * 64 + w * 16;
        const uint32_t r = r0 + (lane & 7) + ((lane >> 3) & 1) * 8;
        uint32_t x[8][4];
        mbar_wait(sb + B_RF, l & 1);
        mbar_wait(sb + B_PE + 8, l & 1);
#pragma unroll
        for (int jj = 0; jj < 8; jj++) ldsm4(sb + (jj >> 2) * 16384 + r * 128 + ((((2 * jj + (lane >> 4)) & 7) ^ (r & 7)) << 4), x[jj]);
        wg_wait<0>();
        fence_regs(acc);
        if (w == 0) e_arrive_both(sb + B_PE + 8 * 3);
        const CUtensorMap* mo = &prm.m[l == 3 ? M_OUT : M_XST];
#pragma unroll
        for (int jj = 0; jj < 8; jj++) {
#pragma unroll
          for (int i = 0; i < 4; i++) x[jj][i] = add_bf16x2(x[jj][i], pack2(acc[8 * jj + 2 * i], acc[8 * jj + 2 * i + 1]));
          stsm4(sb + (jj >> 2) * QSTG + po * 16384 + r * 128 + ((((2 * jj + (lane >> 4)) & 7) ^ (r & 7)) << 4), x[jj][0], x[jj][1], x[jj][2], x[jj][3]);
          if ((jj & 3) == 3) { fence_async_smem(); __syncwarp(); tma_st(mo, pn * 128 + (jj >> 2) * 64, pm * 128 + r0, sb + (jj >> 2) * QSTG + po * 16384 + r0 * 128); }
        }
        bulk_commit();
        if (l < 3) {
          float s1[4] = {0.f, 0.f, 0.f, 0.f}, s2[4][4];
#pragma unroll
          for (int i = 0; i < 16; i++) s2[i >> 2][i & 3] = 0.f;
#pragma unroll
          for (int jj = 0; jj < 8; jj++) {
            mma16816(s1, x[jj][0], x[jj][1], x[jj][2], x[jj][3], 0x3f803f80u, 0x3f803f80u);
#pragma unroll
            for (int i = 0; i < 4; i++) mma1688(s2[i], x[jj][i & 2], x[jj][i | 1], x[jj][i]);
          }
          if (qd == (g >> 1)) {
            float2* sp = g_stats + pn * 2048 + pm * 128 + r0 + g;
            sp[0] = make_float2(s1[0], (g & 1) ? s2[0][1] + s2[2][1] : s2[0][0] + s2[2][0]);
            sp[8] = make_float2(s1[2], (g & 1) ? s2[1][3] + s2[3][3] : s2[1][2] + s2[3][2]);
          }
          __syncwarp();
          bar_arrive(NB_X, 288);
        }
        bulk_wait_n<0>();
        if (l < 3) bar_arrive(NB_X0, 352);
      }
    }
  }
  asm volatile("barrier.cluster.arrive.relaxed.aligned;\nbarrier.cluster.wait.aligned;" ::: "memory");
}

typedef CUresult (*EncodeFn)(CUtensorMap*, CUtensorMapDataType, cuuint32_t, void*, const cuuint64_t*, const cuuint64_t*, const cuuint32_t*,
                             const cuuint32_t*, CUtensorMapInterleave, CUtensorMapSwizzle, CUtensorMapL2promotion, CUtensorMapFloatOOBfill);

static void make_map(EncodeFn fn, CUtensorMap* m, const void* ptr, int rank, const uint64_t* dims, const uint64_t* strides, const uint32_t* box, CUtensorMapSwizzle sw) {
  cuuint64_t d[5], st[4];
  cuuint32_t bx[5], es[5];
  for (int i = 0; i < rank; i++) { d[i] = dims[i]; bx[i] = box[i]; es[i] = 1; if (i) st[i - 1] = strides[i - 1] * 2; }
  fn(m, CU_TENSOR_MAP_DATA_TYPE_BFLOAT16, rank, (void*)ptr, d, st, bx, es, CU_TENSOR_MAP_INTERLEAVE_NONE, sw,
     CU_TENSOR_MAP_L2_PROMOTION_L2_128B, CU_TENSOR_MAP_FLOAT_OOB_FILL_NONE);
}
static void map2(EncodeFn fn, CUtensorMap* m, const void* ptr, uint64_t inner, uint64_t outer, uint32_t bi, uint32_t bo, CUtensorMapSwizzle sw) {
  const uint64_t d[2] = {inner, outer}, st[1] = {inner};
  const uint32_t bx[2] = {bi, bo};
  make_map(fn, m, ptr, 2, d, st, bx, sw);
}

extern "C" void kernel_launch(void* const* d_in, const int* in_sizes, int n_in, void* d_out, int out_size) {
  (void)in_sizes; (void)n_in; (void)out_size;
  static EncodeFn enc = nullptr;
  static void *xs, *os, *kk, *vv, *ep;
  if (!enc) {
    void* p = nullptr;
    cudaDriverEntryPointQueryResult qr;
    cudaGetDriverEntryPoint("cuTensorMapEncodeTiled", &p, cudaEnableDefault, &qr);
    enc = (EncodeFn)p;
    cudaGetSymbolAddress(&xs, g_xs); cudaGetSymbolAddress(&os, g_os); cudaGetSymbolAddress(&kk, g_k); cudaGetSymbolAddress(&vv, g_v); cudaGetSymbolAddress(&ep, g_epoch);
    cudaFuncSetAttribute(fused_kernel, cudaFuncAttributeMaxDynamicSharedMemorySize, SMEM_BYTES);
  }
  Params prm;
  const CUtensorMapSwizzle S128 = CU_TENSOR_MAP_SWIZZLE_128B, S64 = CU_TENSOR_MAP_SWIZZLE_64B;
  map2(enc, &prm.m[M_X0A], d_in[0], 1024, 2048, 64, 256, S128);
  map2(enc, &prm.m[M_XSA], xs, 1024, 2048, 64, 256, S128);
  for (int t = 0; t < 2; t++) {
    const uint64_t d3[3] = {1024, 1024, 3}, s3[2] = {3072, 1024};
    const uint32_t b3[3] = {64, 64, 3};
    make_map(enc, &prm.m[M_WQA + t], d_in[1 + 3 * t], 3, d3, s3, b3, S128);
    const uint64_t d5[5] = {64, 32, 2, 16, 16}, s5[4] = {1024, 32 * 1024, 64 * 1024, 64};
    const uint32_t b5[5] = {64, 32, 1, 2, 2};
    make_map(enc, &prm.m[M_WOA + t], d_in[2 + 3 * t], 5, d5, s5, b5, S128);
    const uint64_t dr[3] = {64, 2048, 16}, sr[2] = {1024, 64};
    const uint32_t br[3] = {64, 128, 2};
    make_map(enc, &prm.m[M_X0R + t], t ? xs : d_in[0], 3, dr, sr, br, S128);
  }
  map2(enc, &prm.m[M_OS], os, 1024, 2048, 64, 64, S128);
  map2(enc, &prm.m[M_K], kk, 32, 65536, 32, 256, S64);
  map2(enc, &prm.m[M_V], vv, 32, 65536, 32, 256, S64);
  map2(enc, &prm.m[M_K4], kk, 32, 65536, 32, 64, S64);
  map2(enc, &prm.m[M_V4], vv, 32, 65536, 32, 64, S64);
  map2(enc, &prm.m[M_XSO], xs, 1024, 2048, 64, 128, S128);
  map2(enc, &prm.m[M_X0H], d_in[0], 1024, 2048, 64, 128, S128);
  map2(enc, &prm.m[M_XST], xs, 1024, 2048, 64, 16, S128);
  map2(enc, &prm.m[M_OUT], d_out, 1024, 2048, 64, 16, S128);
  prm.x0 = (const bf16*)d_in[0];
  prm.wq[0] = (const bf16*)d_in[1]; prm.wq[1] = (const bf16*)d_in[4];
  prm.wo[0] = (const bf16*)d_in[2]; prm.wo[1] = (const bf16*)d_in[5];
  prm.epoch = (uint32_t*)ep;
  prm.zero = 0;
  for (int i = 0; i < 128; i++) prm.map[i] = remap(i);
  fused_kernel<<<128, 384, SMEM_BYTES>>>(prm);
}
```

```cpp
#include <cuda_runtime.h>
#include <cuda_bf16.h>
#include <cuda.h>
#include <stdint.h>

typedef __nv_bfloat16 bf16;

__device__ __forceinline__ void wgmma_m64n192k16_ss_tb(float (&d)[96], uint64_t da, uint64_t db, int scale_d) {
  asm volatile("{\n.reg .pred p;\nsetp.ne.b32 p, %98, 0;\n"
    "wgmma.mma_async.sync.aligned.m64n192k16.f32.bf16.bf16 "
    "{%0, %1, %2, %3, %4, %5, %6, %7, %8, %9, %10, %11, %12, %13, %14, %15, "
    "%16, %17, %18, %19, %20, %21, %22, %23, %24, %25, %26, %27, %28, %29, %30, %31, "
    "%32, %33, %34, %35, %36, %37, %38, %39, %40, %41, %42, %43, %44, %45, %46, %47, "
    "%48, %49, %50, %51, %52, %53, %54, %55, %56, %57, %58, %59, %60, %61, %62, %63, "
    "%64, %65, %66, %67, %68, %69, %70, %71, %72, %73, %74, %75, %76, %77, %78, %79, "
    "%80, %81, %82, %83, %84, %85, %86, %87, %88, %89, %90, %91, %92, %93, %94, %95}, "
    "%96, %97, p, 1, 1, 0, 1;\n}\n"
    : "+f"(d[0]), "+f"(d[1]), "+f"(d[2]), "+f"(d[3]), "+f"(d[4]), "+f"(d[5]), "+f"(d[6]), "+f"(d[7]),
      "+f"(d[8]), "+f"(d[9]), "+f"(d[10]), "+f"(d[11]), "+f"(d[12]), "+f"(d[13]), "+f"(d[14]), "+f"(d[15]),
      "+f"(d[16]), "+f"(d[17]), "+f"(d[18]), "+f"(d[19]), "+f"(d[20]), "+f"(d[21]), "+f"(d[22]), "+f"(d[23]),
      "+f"(d[24]), "+f"(d[25]), "+f"(d[26]), "+f"(d[27]), "+f"(d[28]), "+f"(d[29]), "+f"(d[30]), "+f"(d[31]),
      "+f"(d[32]), "+f"(d[33]), "+f"(d[34]), "+f"(d[35]), "+f"(d[36]), "+f"(d[37]), "+f"(d[38]), "+f"(d[39]),
      "+f"(d[40]), "+f"(d[41]), "+f"(d[42]), "+f"(d[43]), "+f"(d[44]), "+f"(d[45]), "+f"(d[46]), "+f"(d[47]),
      "+f"(d[48]), "+f"(d[49]), "+f"(d[50]), "+f"(d[51]), "+f"(d[52]), "+f"(d[53]), "+f"(d[54]), "+f"(d[55]),
      "+f"(d[56]), "+f"(d[57]), "+f"(d[58]), "+f"(d[59]), "+f"(d[60]), "+f"(d[61]), "+f"(d[62]), "+f"(d[63]),
      "+f"(d[64]), "+f"(d[65]), "+f"(d[66]), "+f"(d[67]), "+f"(d[68]), "+f"(d[69]), "+f"(d[70]), "+f"(d[71]),
      "+f"(d[72]), "+f"(d[73]), "+f"(d[74]), "+f"(d[75]), "+f"(d[76]), "+f"(d[77]), "+f"(d[78]), "+f"(d[79]),
      "+f"(d[80]), "+f"(d[81]), "+f"(d[82]), "+f"(d[83]), "+f"(d[84]), "+f"(d[85]), "+f"(d[86]), "+f"(d[87]),
      "+f"(d[88]), "+f"(d[89]), "+f"(d[90]), "+f"(d[91]), "+f"(d[92]), "+f"(d[93]), "+f"(d[94]), "+f"(d[95])
    : "l"(da), "l"(db), "r"(scale_d));
}

__device__ __forceinline__ void wgmma_m64n128k16_ss_tb(float (&d)[64], uint64_t da, uint64_t db, int scale_d) {
  asm volatile("{\n.reg .pred p;\nsetp.ne.b32 p, %66, 0;\n"
    "wgmma.mma_async.sync.aligned.m64n128k16.f32.bf16.bf16 "
    "{%0, %1, %2, %3, %4, %5, %6, %7, %8, %9, %10, %11, %12, %13, %14, %15, "
    "%16, %17, %18, %19, %20, %21, %22, %23, %24, %25, %26, %27, %28, %29, %30, %31, "
    "%32, %33, %34, %35, %36, %37, %38, %39, %40, %41, %42, %43, %44, %45, %46, %47, "
    "%48, %49, %50, %51, %52, %53, %54, %55, %56, %57, %58, %59, %60, %61, %62, %63}, "
    "%64, %65, p, 1, 1, 0, 1;\n}\n"
    : "+f"(d[0]), "+f"(d[1]), "+f"(d[2]), "+f"(d[3]), "+f"(d[4]), "+f"(d[5]), "+f"(d[6]), "+f"(d[7]),
      "+f"(d[8]), "+f"(d[9]), "+f"(d[10]), "+f"(d[11]), "+f"(d[12]), "+f"(d[13]), "+f"(d[14]), "+f"(d[15]),
      "+f"(d[16]), "+f"(d[17]), "+f"(d[18]), "+f"(d[19]), "+f"(d[20]), "+f"(d[21]), "+f"(d[22]), "+f"(d[23]),
      "+f"(d[24]), "+f"(d[25]), "+f"(d[26]), "+f"(d[27]), "+f"(d[28]), "+f"(d[29]), "+f"(d[30]), "+f"(d[31]),
      "+f"(d[32]), "+f"(d[33]), "+f"(d[34]), "+f"(d[35]), "+f"(d[36]), "+f"(d[37]), "+f"(d[38]), "+f"(d[39]),
      "+f"(d[40]), "+f"(d[41]), "+f"(d[42]), "+f"(d[43]), "+f"(d[44]), "+f"(d[45]), "+f"(d[46]), "+f"(d[47]),
      "+f"(d[48]), "+f"(d[49]), "+f"(d[50]), "+f"(d[51]), "+f"(d[52]), "+f"(d[53]), "+f"(d[54]), "+f"(d[55]),
      "+f"(d[56]), "+f"(d[57]), "+f"(d[58]), "+f"(d[59]), "+f"(d[60]), "+f"(d[61]), "+f"(d[62]), "+f"(d[63])
    : "l"(da), "l"(db), "r"(scale_d));
}

__device__ __forceinline__ void wgmma_m64n32k16_rs_nb_h(float (&d)[16], uint32_t a0, uint32_t a1, uint32_t a2, uint32_t a3, uint64_t db, int scale_d) {
  asm volatile("{\n.reg .pred p;\nsetp.ne.b32 p, %21, 0;\n"
    "wgmma.mma_async.sync.aligned.m64n32k16.f32.f16.f16 "
    "{%0, %1, %2, %3, %4, %5, %6, %7, %8, %9, %10, %11, %12, %13, %14, %15}, "
    "{%16, %17, %18, %19}, %20, p, 1, 1, 0;\n}\n"
    : "+f"(d[0]), "+f"(d[1]), "+f"(d[2]), "+f"(d[3]), "+f"(d[4]), "+f"(d[5]), "+f"(d[6]), "+f"(d[7]),
      "+f"(d[8]), "+f"(d[9]), "+f"(d[10]), "+f"(d[11]), "+f"(d[12]), "+f"(d[13]), "+f"(d[14]), "+f"(d[15])
    : "r"(a0), "r"(a1), "r"(a2), "r"(a3), "l"(db), "r"(scale_d));
}

__device__ __forceinline__ void wgmma_m64n32k16_rs_nb_hh(uint32_t (&d)[8], uint32_t a0, uint32_t a1, uint32_t a2, uint32_t a3, uint64_t db, int scale_d) {
  asm volatile("{\n.reg .pred p;\nsetp.ne.b32 p, %13, 0;\n"
    "wgmma.mma_async.sync.aligned.m64n32k16.f16.f16.f16 "
    "{%0, %1, %2, %3, %4, %5, %6, %7}, "
    "{%8, %9, %10, %11}, %12, p, 1, 1, 0;\n}\n"
    : "+r"(d[0]), "+r"(d[1]), "+r"(d[2]), "+r"(d[3]), "+r"(d[4]), "+r"(d[5]), "+r"(d[6]), "+r"(d[7])
    : "r"(a0), "r"(a1), "r"(a2), "r"(a3), "l"(db), "r"(scale_d));
}

__device__ __forceinline__ void wgmma_m64n40k16_rs_tb(float (&d)[20], uint32_t a0, uint32_t a1, uint32_t a2, uint32_t a3, uint64_t db, int scale_d) {
  asm volatile("{\n.reg .pred p;\nsetp.ne.b32 p, %25, 0;\n"
    "wgmma.mma_async.sync.aligned.m64n40k16.f32.bf16.bf16 "
    "{%0, %1, %2, %3, %4, %5, %6, %7, %8, %9, %10, %11, %12, %13, %14, %15, "
    "%16, %17, %18, %19}, "
    "{%20, %21, %22, %23}, %24, p, 1, 1, 1;\n}\n"
    : "+f"(d[0]), "+f"(d[1]), "+f"(d[2]), "+f"(d[3]), "+f"(d[4]), "+f"(d[5]), "+f"(d[6]), "+f"(d[7]),
      "+f"(d[8]), "+f"(d[9]), "+f"(d[10]), "+f"(d[11]), "+f"(d[12]), "+f"(d[13]), "+f"(d[14]), "+f"(d[15]),
      "+f"(d[16]), "+f"(d[17]), "+f"(d[18]), "+f"(d[19])
    : "r"(a0), "r"(a1), "r"(a2), "r"(a3), "l"(db), "r"(scale_d));
}

__device__ __forceinline__ void wgmma_m64n40k16_rs_tb_z(float (&d)[20], uint32_t a0, uint32_t a1, uint32_t a2, uint32_t a3, uint64_t db, int scale_d) {
  asm volatile("{\n.reg .pred p;\nsetp.ne.b32 p, %25, 0;\n"
    "wgmma.mma_async.sync.aligned.m64n40k16.f32.bf16.bf16 "
    "{%0, %1, %2, %3, %4, %5, %6, %7, %8, %9, %10, %11, %12, %13, %14, %15, "
    "%16, %17, %18, %19}, "
    "{%20, %21, %22, %23}, %24, p, 1, 1, 1;\n}\n"
    : "=f"(d[0]), "=f"(d[1]), "=f"(d[2]), "=f"(d[3]), "=f"(d[4]), "=f"(d[5]), "=f"(d[6]), "=f"(d[7]),
      "=f"(d[8]), "=f"(d[9]), "=f"(d[10]), "=f"(d[11]), "=f"(d[12]), "=f"(d[13]), "=f"(d[14]), "=f"(d[15]),
      "=f"(d[16]), "=f"(d[17]), "=f"(d[18]), "=f"(d[19])
    : "r"(a0), "r"(a1), "r"(a2), "r"(a3), "l"(db), "r"(scale_d));
}

__device__ __forceinline__ void wgmma_m64n32k16_rs_nb_z_h(float (&d)[16], uint32_t a0, uint32_t a1, uint32_t a2, uint32_t a3, uint64_t db, int scale_d) {
  asm volatile("{\n.reg .pred p;\nsetp.ne.b32 p, %21, 0;\n"
    "wgmma.mma_async.sync.aligned.m64n32k16.f32.f16.f16 "
    "{%0, %1, %2, %3, %4, %5, %6, %7, %8, %9, %10, %11, %12, %13, %14, %15}, "
    "{%16, %17, %18, %19}, %20, p, 1, 1, 0;\n}\n"
    : "=f"(d[0]), "=f"(d[1]), "=f"(d[2]), "=f"(d[3]), "=f"(d[4]), "=f"(d[5]), "=f"(d[6]), "=f"(d[7]),
      "=f"(d[8]), "=f"(d[9]), "=f"(d[10]), "=f"(d[11]), "=f"(d[12]), "=f"(d[13]), "=f"(d[14]), "=f"(d[15])
    : "r"(a0), "r"(a1), "r"(a2), "r"(a3), "l"(db), "r"(scale_d));
}

__device__ __forceinline__ void wgmma_m64n32k16_rs_nb_z_hh(uint32_t (&d)[8], uint32_t a0, uint32_t a1, uint32_t a2, uint32_t a3, uint64_t db, int scale_d) {
  asm volatile("{\n.reg .pred p;\nsetp.ne.b32 p, %13, 0;\n"
    "wgmma.mma_async.sync.aligned.m64n32k16.f16.f16.f16 "
    "{%0, %1, %2, %3, %4, %5, %6, %7}, "
    "{%8, %9, %10, %11}, %12, p, 1, 1, 0;\n}\n"
    : "=r"(d[0]), "=r"(d[1]), "=r"(d[2]), "=r"(d[3]), "=r"(d[4]), "=r"(d[5]), "=r"(d[6]), "=r"(d[7])
    : "r"(a0), "r"(a1), "r"(a2), "r"(a3), "l"(db), "r"(scale_d));
}

#define DEVINL __device__ __forceinline__
DEVINL void wg_fence() { asm volatile("wgmma.fence.sync.aligned;" ::: "memory"); }
DEVINL void wg_commit() { asm volatile("wgmma.commit_group.sync.aligned;" ::: "memory"); }
template <int N> DEVINL void wg_wait() { asm volatile("wgmma.wait_group.sync.aligned %0;" ::"n"(N) : "memory"); }
DEVINL uint64_t mkdesc(uint32_t addr, uint32_t lbo, uint32_t sbo, int sw) {
  return (uint64_t)((addr & 0x3FFFF) >> 4) | ((uint64_t)(lbo >> 4) << 16) | ((uint64_t)(sbo >> 4) << 32) | ((uint64_t)sw << 62);
}
DEVINL void mbar_arrive(uint32_t bar) { asm volatile("mbarrier.arrive.shared::cta.b64 _, [%0];" ::"r"(bar) : "memory"); }
DEVINL void arrive_if_gt(uint32_t bar, uint32_t a, uint32_t b) {
  asm volatile("{\n.reg .pred p;\nsetp.gt.u32 p, %1, %2;\n@p mbarrier.arrive.shared::cta.b64 _, [%0];\n}" ::"r"(bar), "r"(a), "r"(b) : "memory");
}
DEVINL bool mbar_try(uint32_t bar, uint32_t parity) {
  uint32_t ok;
  asm volatile("{\n.reg .pred p;\nmbarrier.try_wait.parity.shared::cta.b64 p, [%1], %2;\nselp.u32 %0, 1, 0, p;\n}" : "=r"(ok) : "r"(bar), "r"(parity) : "memory");
  return ok;
}
DEVINL bool mbar_test(uint32_t bar, uint32_t parity) {
  uint32_t ok;
  asm volatile("{\n.reg .pred p;\nmbarrier.test_wait.parity.shared::cta.b64 p, [%1], %2;\nselp.u32 %0, 1, 0, p;\n}" : "=r"(ok) : "r"(bar), "r"(parity) : "memory");
  return ok;
}
DEVINL void mbar_hint(uint32_t bar, uint32_t parity) {
#pragma unroll 1
  for (uint32_t n = 0; n < 16u; n++) if (mbar_try(bar, parity)) break;
}
DEVINL void mbar_wait(uint32_t bar, uint32_t parity) {
#pragma unroll 1
  for (uint32_t n = 0; n < 100000u; n++) if (mbar_try(bar, parity)) break;
}
DEVINL void mbar_wait_long(uint32_t bar, uint32_t parity) {
#pragma unroll 1
  for (uint32_t n = 0; n < 100000u; n++) {
    uint32_t ok;
    asm volatile("{\n.reg .pred p;\nmbarrier.try_wait.parity.shared::cta.b64 p, [%1], %2, %3;\nselp.u32 %0, 1, 0, p;\n}" : "=r"(ok) : "r"(bar), "r"(parity), "r"(4000) : "memory");
    if (ok) break;
  }
}
#define EL(txt) "{\n.reg .pred pe;\nelect.sync _|pe, 0xffffffff;\n@pe " txt "\n}"
DEVINL void e_expect_tx(uint32_t bar, uint32_t bytes) { asm volatile(EL("mbarrier.arrive.expect_tx.shared::cta.b64 _, [%0], %1;") ::"r"(bar), "r"(bytes) : "memory"); }
DEVINL void e_init(uint32_t bar, uint32_t cnt) { asm volatile(EL("mbarrier.init.shared::cta.b64 [%0], %1;") ::"r"(bar), "r"(cnt) : "memory"); }
DEVINL void e_arrive(uint32_t bar) { asm volatile(EL("mbarrier.arrive.shared::cta.b64 _, [%0];") ::"r"(bar) : "memory"); }
DEVINL void e_red(uint32_t* p) { asm volatile(EL("red.release.gpu.global.add.u32 [%0], 1;") ::"l"(p) : "memory"); }
DEVINL void e_red_relaxed(uint32_t* p) { asm volatile(EL("red.relaxed.gpu.global.add.u32 [%0], 1;") ::"l"(p) : "memory"); }
DEVINL void tma_ld(uint32_t dst, const CUtensorMap* m, int c0, int c1, uint32_t bar) {
  asm volatile(EL("cp.async.bulk.tensor.2d.shared::cluster.global.mbarrier::complete_tx::bytes [%0], [%1, {%3, %4}], [%2];")
               ::"r"(dst), "l"(m), "r"(bar), "r"(c0), "r"(c1) : "memory");
}
DEVINL void tma_ld3(uint32_t dst, const CUtensorMap* m, int c0, int c1, int c2, uint32_t bar) {
  asm volatile(EL("cp.async.bulk.tensor.3d.shared::cluster.global.mbarrier::complete_tx::bytes [%0], [%1, {%3, %4, %5}], [%2];")
               ::"r"(dst), "l"(m), "r"(bar), "r"(c0), "r"(c1), "r"(c2) : "memory");
}
DEVINL void tma_ld5(uint32_t dst, const CUtensorMap* m, int c2, int c3, int c4, uint32_t bar) {
  asm volatile(EL("cp.async.bulk.tensor.5d.shared::cluster.global.mbarrier::complete_tx::bytes [%0], [%1, {0, 0, %3, %4, %5}], [%2];")
               ::"r"(dst), "l"(m), "r"(bar), "r"(c2), "r"(c3), "r"(c4) : "memory");
}
DEVINL void tma_ld_mc(uint32_t dst, const CUtensorMap* m, int c0, int c1, uint32_t bar) {
  asm volatile(EL("cp.async.bulk.tensor.2d.shared::cluster.global.mbarrier::complete_tx::bytes.multicast::cluster [%0], [%1, {%3, %4}], [%2], %5;")
               ::"r"(dst), "l"(m), "r"(bar), "r"(c0), "r"(c1), "h"((uint16_t)3) : "memory");
}
DEVINL void e_arrive_both(uint32_t bar) {
  asm volatile("{\n.reg .pred pe;\n.reg .b32 r0, r1;\nelect.sync _|pe, 0xffffffff;\nmapa.shared::cluster.u32 r0, %0, 0;\nmapa.shared::cluster.u32 r1, %0, 1;\n"
               "@pe mbarrier.arrive.shared::cluster.b64 _, [r0];\n@pe mbarrier.arrive.shared::cluster.b64 _, [r1];\n}" ::"r"(bar) : "memory");
}
DEVINL void push_peer(uint32_t dst, uint32_t src, uint32_t bar, uint32_t peer) {
  asm volatile("{\n.reg .pred pe;\n.reg .b32 d, b;\nelect.sync _|pe, 0xffffffff;\nmapa.shared::cluster.u32 d, %0, %3;\nmapa.shared::cluster.u32 b, %2, %3;\n"
               "@pe cp.async.bulk.shared::cluster.shared::cta.mbarrier::complete_tx::bytes [d], [%1], 16384, [b];\n}" ::"r"(dst), "r"(src), "r"(bar), "r"(peer) : "memory");
}
DEVINL void tma_st(const CUtensorMap* m, int c0, int c1, uint32_t src) {
  asm volatile(EL("cp.async.bulk.tensor.2d.global.shared::cta.bulk_group [%0, {%2, %3}], [%1];") ::"l"(m), "r"(src), "r"(c0), "r"(c1) : "memory");
}
DEVINL void bulk_commit() { asm volatile("cp.async.bulk.commit_group;" ::: "memory"); }
template <int N> DEVINL void bulk_wait_n() { asm volatile("cp.async.bulk.wait_group %0;\nbar.warp.sync 0xffffffff;" ::"n"(N) : "memory"); }
DEVINL void l2_prefetch(const void* g, uint32_t bytes) { asm volatile(EL("cp.async.bulk.prefetch.L2.global [%0], %1;") ::"l"(g), "r"(bytes) : "memory"); }
DEVINL void fence_async_smem() { asm volatile("fence.proxy.async.shared::cta;" ::: "memory"); }
DEVINL void fence_async_gl() { asm volatile("fence.proxy.async.global;" ::: "memory"); }
DEVINL void cluster_wait() { asm volatile("barrier.cluster.wait.aligned;" ::: "memory"); }
DEVINL void bar_sync(int id, int n) { asm volatile("bar.sync %0, %1;" ::"r"(id), "r"(n) : "memory"); }
DEVINL void bar_arrive(int id, int n) { asm volatile("bar.arrive %0, %1;" ::"r"(id), "r"(n) : "memory"); }
DEVINL uint32_t ld_acquire(const uint32_t* p) { uint32_t v; asm volatile("ld.acquire.gpu.global.u32 %0, [%1];" : "=r"(v) : "l"(p) : "memory"); return v; }
DEVINL void watch(const uint32_t* p, uint32_t target, uint32_t all, uint32_t tag, uint32_t slot) {
  uint32_t seen = 0;
#pragma unroll 1
  for (uint32_t n = 0; n < 200000u && seen != all; n++) {
    const uint32_t m = __ballot_sync(~0u, (int)(ld_acquire(p) - target) >= 0) & all;
    if (m != seen) { seen = m; asm volatile("st.release.cta.shared.u32 [%0], %1;" ::"r"(slot), "r"(tag << 16 | m) : "memory"); }
  }
}
template <bool RELAXED = false> DEVINL void await_bit(uint32_t slot, uint32_t tag, int j, uint32_t& rdy) {
  if ((rdy >> j) & 1) return;
#pragma unroll 1
  for (uint32_t n = 0; n < 8000000u; n++) {
    uint32_t v;
    asm volatile("ld.acquire.cta.shared.u32 %0, [%1];" : "=r"(v) : "r"(slot) : "memory");
    if ((v >> 16) == tag && ((v >> j) & 1)) { rdy = v; break; }
    if (RELAXED) __nanosleep(200);
  }
  asm volatile("fence.proxy.async.global;" ::: "memory");
}
DEVINL void poll_ge(const uint32_t* p, uint32_t target) {
#pragma unroll 1
  for (uint32_t n = 0; n < 200000u; n++) if (__all_sync(~0u, (int)(ld_acquire(p) - target) >= 0)) break;
}
DEVINL int lane_id() { int v; asm volatile("mov.u32 %0, %%laneid;" : "=r"(v)); return v; }
__host__ DEVINL int remap(int v) {
  const int c = v >> 1, u = c - 36, r = (u * 37) >> 8;
  const int L = max(c - 4 + max(r + 1, 0), (c - 4) >> 31 & (32 + 8 * c));
  return 2 * L + (v & 1);
}
DEVINL int block_id() { int v; asm volatile("mov.u32 %0, %%ctaid.x;" : "=r"(v)); return v; }
#define cta_id() prm.map[block_id()]
#define IDS() const int lane = lane_id(), b = cta_id(), bm = b >> 4, bn = b & 15, rank = b & 1, pm = 2 * bm + (bn >> 3), pn = bn & 7, po = pm & 1; \
  (void)lane; (void)bm; (void)bn; (void)rank; (void)pm; (void)pn; (void)po
DEVINL void st_tagged(unsigned long long* p, uint32_t v, uint32_t tag) {
  asm volatile("{\n.reg .b64 t;\nmov.b64 t, {%1, %2};\nst.relaxed.gpu.global.b64 [%0], t;\n}" ::"l"(p), "r"(v), "r"(tag) : "memory");
}
DEVINL float ex2(float x) { float y; asm("ex2.approx.ftz.f32 %0, %1;" : "=f"(y) : "f"(x)); return y; }
DEVINL float rcp(float x) { float y; asm("rcp.approx.ftz.f32 %0, %1;" : "=f"(y) : "f"(x)); return y; }
DEVINL uint32_t pack2(float lo, float hi) { uint32_t r; asm("cvt.rn.bf16x2.f32 %0, %1, %2;" : "=r"(r) : "f"(hi), "f"(lo)); return r; }
DEVINL float bf_lo(uint32_t w) { return __uint_as_float(w << 16); }
DEVINL float bf_hi(uint32_t w) { return __uint_as_float(w & 0xFFFF0000u); }
DEVINL float bf_round(float x) { return bf_lo(pack2(x, 0.f)); }
DEVINL uint32_t add_bf16x2(uint32_t a, uint32_t b) { uint32_t r; asm("add.rn.bf16x2 %0, %1, %2;" : "=r"(r) : "r"(a), "r"(b)); return r; }
DEVINL uint32_t max_bf2(uint32_t a, uint32_t b) { uint32_t r; asm("max.bf16x2 %0, %1, %2;" : "=r"(r) : "r"(a), "r"(b)); return r; }
DEVINL uint32_t scale_bf2(uint32_t a) {
  uint32_t r;
  asm("{\n.reg .b32 t;\nmul.rn.bf16x2 t, %1, %3;\nfma.rn.bf16x2 %0, %1, %2, t;\n}" : "=r"(r) : "r"(a), "r"(0x3E353E35u), "r"(0x379E379Eu));
  return r;
}
DEVINL void stsm4(uint32_t addr, uint32_t a, uint32_t b, uint32_t c, uint32_t d) {
  asm volatile("stmatrix.sync.aligned.m8n8.x4.shared.b16 [%0], {%1, %2, %3, %4};" ::"r"(addr), "r"(a), "r"(b), "r"(c), "r"(d) : "memory");
}
DEVINL void ldsm4(uint32_t addr, uint32_t (&r)[4]) {
  asm volatile("ldmatrix.sync.aligned.m8n8.x4.shared.b16 {%0, %1, %2, %3}, [%4];" : "=r"(r[0]), "=r"(r[1]), "=r"(r[2]), "=r"(r[3]) : "r"(addr) : "memory");
}
DEVINL void ldsm4t(uint32_t addr, uint32_t (&r)[4]) {
  asm volatile("ldmatrix.sync.aligned.m8n8.x4.trans.shared.b16 {%0, %1, %2, %3}, [%4];" : "=r"(r[0]), "=r"(r[1]), "=r"(r[2]), "=r"(r[3]) : "r"(addr) : "memory");
}
DEVINL void sts128(uint32_t addr, uint32_t a, uint32_t b, uint32_t c, uint32_t d) {
  asm volatile("st.shared.v4.b32 [%0], {%1, %2, %3, %4};" ::"r"(addr), "r"(a), "r"(b), "r"(c), "r"(d) : "memory");
}
DEVINL float4 lds128f(uint32_t addr) { float4 v; asm volatile("ld.shared.v4.f32 {%0, %1, %2, %3}, [%4];" : "=f"(v.x), "=f"(v.y), "=f"(v.z), "=f"(v.w) : "r"(addr) : "memory"); return v; }
DEVINL float lds32f(uint32_t addr) { float v; asm volatile("ld.shared.f32 %0, [%1];" : "=f"(v) : "r"(addr) : "memory"); return v; }
DEVINL void mma16816(float (&d)[4], uint32_t a0, uint32_t a1, uint32_t a2, uint32_t a3, uint32_t b0, uint32_t b1) {
  asm("mma.sync.aligned.m16n8k16.row.col.f32.bf16.bf16.f32 {%0, %1, %2, %3}, {%4, %5, %6, %7}, {%8, %9}, {%0, %1, %2, %3};"
               : "+f"(d[0]), "+f"(d[1]), "+f"(d[2]), "+f"(d[3]) : "r"(a0), "r"(a1), "r"(a2), "r"(a3), "r"(b0), "r"(b1));
}
DEVINL void mma1688(float (&d)[4], uint32_t a0, uint32_t a1, uint32_t b0) {
  asm("mma.sync.aligned.m16n8k8.row.col.f32.bf16.bf16.f32 {%0, %1, %2, %3}, {%4, %5}, {%6}, {%0, %1, %2, %3};"
               : "+f"(d[0]), "+f"(d[1]), "+f"(d[2]), "+f"(d[3]) : "r"(a0), "r"(a1), "r"(b0));
}
DEVINL void mma1688h(float (&d)[4], uint32_t a0, uint32_t a1, uint32_t b0) {
  asm("mma.sync.aligned.m16n8k8.row.col.f32.f16.f16.f32 {%0, %1, %2, %3}, {%4, %5}, {%6}, {%0, %1, %2, %3};"
               : "+f"(d[0]), "+f"(d[1]), "+f"(d[2]), "+f"(d[3]) : "r"(a0), "r"(a1), "r"(b0));
}
DEVINL void mma16816h(float (&d)[4], uint32_t a0, uint32_t a1, uint32_t a2, uint32_t a3, uint32_t b0, uint32_t b1) {
  asm("mma.sync.aligned.m16n8k16.row.col.f32.f16.f16.f32 {%0, %1, %2, %3}, {%4, %5, %6, %7}, {%8, %9}, {%0, %1, %2, %3};"
               : "+f"(d[0]), "+f"(d[1]), "+f"(d[2]), "+f"(d[3]) : "r"(a0), "r"(a1), "r"(a2), "r"(a3), "r"(b0), "r"(b1));
}
template <int N> DEVINL void fence_regs(uint32_t (&d)[N]) {
#pragma unroll
  for (int i = 0; i < N; i++) asm volatile("" : "+r"(d[i])::"memory");
}
template <int N> DEVINL void fence_regs(float (&d)[N]) {
#pragma unroll
  for (int i = 0; i < N; i++) asm volatile("" : "+f"(d[i])::"memory");
}

__device__ __align__(1024) bf16 g_xs[2048 * 1024];
__device__ __align__(1024) bf16 g_os[2048 * 1024];
__device__ __align__(1024) bf16 g_k[32 * 2048 * 32];
__device__ __align__(1024) bf16 g_v[32 * 2048 * 32];
__device__ __align__(128) float2 g_stats[8 * 2048];
__device__ __align__(16) float g_csp[2 * 16 * 8 * 192];
__device__ __align__(128) float g_kn[2 * 128 * 32];
__device__ unsigned long long g_halo[2 * 128 * 32 * 32];
__device__ __align__(128) uint32_t g_cnt[256 * 32];
__device__ uint32_t g_epoch;

DEVINL uint32_t* cnt_x(int l, int bm) { return g_cnt + (l * 8 + bm) * 32; }
DEVINL uint32_t* cnt_o(int l, int pm, int h) { return g_cnt + (32 + (l * 16 + pm) * 2 + h) * 32; }
DEVINL uint32_t* cnt_kv(int lb, int bn) { return g_cnt + (160 + lb * 16 + bn) * 32; }
DEVINL uint32_t* cnt_ad(int bn) { return g_cnt + (192 + bn) * 32; }
DEVINL uint32_t* cnt_cs(int t, int bn) { return g_cnt + (208 + t * 16 + bn) * 32; }

DEVINL int qord(int i, int l, int pn) { return l == 0 ? i : i < 4 ? ((2 * pn) ^ (i & 2)) + (i & 1) : i - 4 < 2 * (pn & 6) ? i - 4 : i; }
DEVINL int pord(int i, int l, int p) { return (l & 1) || i > p ? i : i ? i - 1 : p; }
struct Params {
  CUtensorMap m[17];
  const bf16* x0;
  const bf16* wq[2];
  const bf16* wo;
  uint32_t* epoch;
  uint32_t zero;
  int map[128];
};
enum { M_X0A = 0, M_XSA, M_WQA, M_WQB, M_WOA, M_WOB, M_OS, M_K, M_V, M_X0R, M_XSR, M_XSO, M_OUT, M_XST, M_X0H, M_K4, M_V4, M_COUNT };

constexpr uint32_t QSTG = 57344;
constexpr uint32_t T0 = 65536, TSTG = 32768;
constexpr uint32_t ONES = 229376;
constexpr uint32_t PSTG = 32768;
constexpr uint32_t ASC = 17408;
constexpr uint32_t RSTD = 229376, MEAN = 230400, COLS = 230912, KMAX = 231680, B_QD = 231688, B_OW = 231704, W_C = 231712, BARS = 232192, SMEM_BYTES = 232448;
constexpr uint32_t B_QF = BARS, B_QE = BARS + 32, B_TF = BARS + 64, B_TE = BARS + 96, B_PF = BARS + 128, B_PE = BARS + 176,
                   B_RF = BARS + 224, W_X = BARS + 232, W_O = BARS + 236, B_QL = BARS + 240, B_PA = BARS + 248;
enum { NB_ST = 1, NB_KV = 2  , NB_DONE = 3, NB_SC = 4, NB_SIG = 5  , NB_KN = 9  , NB_X = 11, NB_HALO = 12  , NB_X0 = 15 };

DEVINL uint32_t pslot_b(uint32_t s, int l) { return ((((l & 1) ? 0x32DC45u : 0x468795u) >> (4 * s)) & 15) * 16384u; }
DEVINL uint32_t pslot_a(uint32_t s, int l) { return ((((l & 1) ? 0xBA8796u : 0x32DCBAu) >> (4 * s)) & 15) * 16384u; }

constexpr float QSCALE = 0.17677669529663687f * 1.4426950408889634f;

DEVINL uint32_t hfma2(uint32_t a, uint32_t b, uint32_t c) { uint32_t r; asm("fma.rn.f16x2 %0, %1, %2, %3;" : "=r"(r) : "r"(a), "r"(b), "r"(c)); return r; }
DEVINL uint32_t pack2h(float lo, float hi) { uint32_t r; asm("cvt.rn.f16x2.f32 %0, %1, %2;" : "=r"(r) : "f"(hi), "f"(lo)); return r; }
DEVINL uint32_t h2_to_bf2(uint32_t h) {
  float a, b;
  asm("{\n.reg .b16 l, h;\nmov.b32 {l, h}, %2;\ncvt.f32.f16 %0, l;\ncvt.f32.f16 %1, h;\n}" : "=f"(a), "=f"(b) : "r"(h));
  return pack2(a, b);
}
DEVINL uint32_t exp2_h2(uint32_t s, uint32_t cc) {
  uint32_t r, v;
  asm("{\n.reg .b16 l, h;\n.reg .b32 t;\nmov.b32 {l, h}, %2;\nmov.b32 t, {l, l};\nfma.rn.f16x2 %0, %1, t, %3;\n}" : "=r"(r) : "r"(s), "r"(cc), "r"(0x007E007Eu));
  asm("{\n.reg .b16 l, h;\n.reg .b32 t;\nmov.b32 {l, h}, %2;\nmov.b32 t, {h, h};\nfma.rn.f16x2 %0, %1, t, %3;\n}" : "=r"(v) : "r"(r), "r"(cc), "r"(0x33FD33FDu));
  const uint32_t g = hfma2(v, 0x44004400u, s);
  return __funnelshift_l(r, r, 7) + hfma2(hfma2(g, g, 0x0DE10DE1u), g, 0x00300030u);
}
constexpr uint32_t NOT_F16 = 0x7FC00000u, K_LO = 0x35000000u  ;
DEVINL uint32_t f16_class(uint32_t norm2, uint32_t lo) { return norm2 - lo > 0x4E800000u - lo ? NOT_F16 : norm2; }

DEVINL void attn_slow(const uint32_t (&q)[8], float up, int head, const float* kn, float (&res)[20], int lane) {
  const int g = lane >> 2, qd = lane & 3;
  const bf16* kb = g_k + (size_t)head * 2048 * 32;
  const bf16* vb = g_v + (size_t)head * 2048 * 32;
  float o[4][4], m0 = -INFINITY, m1 = -INFINITY, l0 = 0.f, l1 = 0.f;
#pragma unroll
  for (int j = 0; j < 4; j++) { o[j][0] = o[j][1] = o[j][2] = o[j][3] = 0.f; }
#pragma unroll 1
  for (int k0 = 0; k0 < 2048; k0 += 16) {
    float s[2][4];
    const bool kh = __float_as_uint(__ldcg(kn + (k0 >> 8) * 32 + ((k0 >> 6) & 1) * 8 + ((k0 >> 7) & 1) * 4 + ((k0 >> 4) & 3))) != NOT_F16;
#pragma unroll
    for (int nt = 0; nt < 2; nt++) {
      s[nt][0] = s[nt][1] = s[nt][2] = s[nt][3] = 0.f;
      const uint32_t* kp = (const uint32_t*)(kb + (size_t)(k0 + nt * 8 + g) * 32) + qd;
      uint32_t kf[4];
#pragma unroll
      for (int i = 0; i < 4; i++) { kf[i] = __ldcg(kp + 4 * i); if (kh) kf[i] = h2_to_bf2(kf[i]); }
      mma16816(s[nt], q[0], q[1], q[2], q[3], kf[0], kf[1]);
      mma16816(s[nt], q[4], q[5], q[6], q[7], kf[2], kf[3]);
      s[nt][0] *= up; s[nt][1] *= up; s[nt][2] *= up; s[nt][3] *= up;
    }
    float a0 = fmaxf(fmaxf(s[0][0], s[0][1]), fmaxf(s[1][0], s[1][1]));
    float a1 = fmaxf(fmaxf(s[0][2], s[0][3]), fmaxf(s[1][2], s[1][3]));
    a0 = fmaxf(a0, __shfl_xor_sync(~0u, a0, 1)); a0 = fmaxf(a0, __shfl_xor_sync(~0u, a0, 2));
    a1 = fmaxf(a1, __shfl_xor_sync(~0u, a1, 1)); a1 = fmaxf(a1, __shfl_xor_sync(~0u, a1, 2));
    const float n0 = fmaxf(m0, a0), n1 = fmaxf(m1, a1);
    const float c0 = (m0 == n0) ? 1.f : ex2(m0 - n0), c1 = (m1 == n1) ? 1.f : ex2(m1 - n1);
    m0 = n0; m1 = n1;
    const uint32_t p0 = pack2(ex2(s[0][0] - n0), ex2(s[0][1] - n0)), p1 = pack2(ex2(s[0][2] - n1), ex2(s[0][3] - n1));
    const uint32_t p2 = pack2(ex2(s[1][0] - n0), ex2(s[1][1] - n0)), p3 = pack2(ex2(s[1][2] - n1), ex2(s[1][3] - n1));
    l0 = l0 * c0 + bf_lo(p0) + bf_hi(p0) + bf_lo(p2) + bf_hi(p2);
    l1 = l1 * c1 + bf_lo(p1) + bf_hi(p1) + bf_lo(p3) + bf_hi(p3);
#pragma unroll
    for (int j = 0; j < 4; j++) {
      o[j][0] *= c0; o[j][1] *= c0; o[j][2] *= c1; o[j][3] *= c1;
      const unsigned short* vp = (const unsigned short*)(vb + (size_t)(k0 + 2 * qd) * 32 + j * 8 + g);
      const uint32_t b0 = (uint32_t)__ldcg(vp) | ((uint32_t)__ldcg(vp + 32) << 16);
      const uint32_t b1 = (uint32_t)__ldcg(vp + 256) | ((uint32_t)__ldcg(vp + 288) << 16);
      mma16816(o[j], p0, p1, p2, p3, b0, b1);
    }
  }
  l0 += __shfl_xor_sync(~0u, l0, 1); l0 += __shfl_xor_sync(~0u, l0, 2);
  l1 += __shfl_xor_sync(~0u, l1, 1); l1 += __shfl_xor_sync(~0u, l1, 2);
#pragma unroll
  for (int j = 0; j < 4; j++) { res[4 * j] = o[j][0]; res[4 * j + 1] = o[j][1]; res[4 * j + 2] = o[j][2]; res[4 * j + 3] = o[j][3]; }
  res[16] = l0; res[18] = l1;
}

__global__ void __cluster_dims__(2, 1, 1) __launch_bounds__(384, 1) fused_kernel(const __grid_constant__ Params prm) {
  extern __shared__ __align__(1024) char smem[];
  const uint32_t sb = (uint32_t)__cvta_generic_to_shared(smem);
  const int tid = threadIdx.x;
  const int wid = __shfl_sync(0xffffffffu, tid >> 5, 0), wg = wid >> 2, w = wid & 3;
  const int bm = remap(blockIdx.x) >> 4, bn = remap(blockIdx.x) & 15;
  auto first_tile = [&](int kt) {
    e_expect_tx(sb + B_QF + 8 * kt, QSTG);
    tma_ld(sb + kt * QSTG, &prm.m[M_X0A], kt * 64, bm * 256, sb + B_QF + 8 * kt);
    tma_ld3(sb + kt * QSTG + 32768, &prm.m[M_WQA], bn * 64, kt * 64, 0, sb + B_QF + 8 * kt);
  };
  if (wid == 8) {
    e_init(sb + B_QF, 1);
    asm volatile("fence.mbarrier_init.release.cluster;" ::: "memory");
    first_tile(0);
  }
  if (wid < 8) {
#pragma unroll
    for (int i = 0; i < 4; i++) {
      const uint32_t cnt = (uint32_t)((i == 0 ? 0x14112140 : i == 1 ? 0x04112141 : i == 2 ? 0x14412141 : 0x24412141) >> (4 * wid)) & 7;
      if (cnt) e_init(sb + BARS + 32 * wid + 8 * i, cnt);
    }
    if (wid < 3) e_init(sb + B_QD + wid * 8, wid < 2 ? 1 : 2);
    if (tid == 255) { *(uint2*)(smem + W_X) = make_uint2(0u, 0u); *(uint2*)(smem + W_C) = make_uint2(0xF8000080u, 0xF8000080u); }
    asm volatile("fence.mbarrier_init.release.cluster;" ::: "memory");
  }
  const uint32_t epoch = *(volatile uint32_t*)prm.epoch;
  __syncthreads();
  asm volatile("barrier.cluster.arrive.relaxed.aligned;" ::: "memory");

  if (wg == 2) {
    asm volatile("setmaxnreg.dec.sync.aligned.u32 56;");
    const uint32_t ep1 = epoch + 1;
    if (w == 0) {
      first_tile(1);
      mbar_wait(sb + B_QF, 0);
      first_tile(2); first_tile(3);
#pragma unroll 1
      for (int kt = 4; kt < 9; kt++) l2_prefetch(prm.wq[0] + kt * 196608 + blockIdx.x * 1536, 3072);
      cluster_wait();
#pragma unroll 1
      for (int l = 0; l < 4; l++) {
        IDS();
        const CUtensorMap* mw = &prm.m[M_WQA + (l & 1)];
        const CUtensorMap* mh = &prm.m[l == 0 ? M_X0H : M_XSO];
        const CUtensorMap* mo = &prm.m[M_WOA + (l & 1)];
        auto q_b = [&](int i) {
          const int s = i & 3;
          mbar_wait(sb + B_QE + 8 * s, ((i >> 2) & 1) ^ 1);
          e_expect_tx(sb + B_QF + 8 * s, QSTG);
          tma_ld3(sb + s * QSTG + 32768, mw, bn * 64, qord(i, l, pn) * 64, 0, sb + B_QF + 8 * s);
        };
        uint32_t rdy = l ? 0u : ~0u;
        auto q_a = [&](int i) {
          const int kt = qord(i, l, pn);
          await_bit(sb + W_X, l, kt >> 1, rdy);
          tma_ld_mc(sb + (i & 3) * QSTG + rank * 16384, mh, kt * 64, bm * 256 + rank * 128, sb + B_QF + 8 * (i & 3));
        };
        if (l > 0) {
#pragma unroll 1
          for (int i = 0; i < 4; i++) {
            const int kt = qord(i, l, pn);
            await_bit(sb + W_X, l, kt >> 1, rdy);
            if (i == 1 || i == 2) mbar_wait(sb + B_QF + 8 * (i - 1), 0);
            e_expect_tx(sb + B_QF + 8 * i, 16384);
            tma_ld(sb + i * QSTG + (po ^ 1) * 16384, &prm.m[M_XSO], kt * 64, (pm ^ 1) * 128, sb + B_QF + 8 * i);
          }
        }
#pragma unroll 1
        for (int i = 4; i < 16; i++) {
          q_b(i); q_a(i);
          if (l == 0 && i < 11) l2_prefetch(prm.wq[0] + (i + 5) * 196608 + blockIdx.x * 1536, 3072);
          if (l == 0 && i == 15) l2_prefetch(prm.wo + blockIdx.x * 8192, 16384);
        }
        if (l & 1) {
          if (l == 3) poll_ge(cnt_ad(bn), ep1 * 16);
          const int krow = 2 * bn * 2048 + bm * 256;
          uint32_t* kvc = cnt_kv(l >> 1, bn);
#pragma unroll 1
          for (int m = 1; m >= 0; m--) {
            bar_sync(m ? NB_ST : NB_KV, 288);
#pragma unroll
            for (int i = 0; i < 4; i++) tma_st(&prm.m[M_K4 + (i >> 1)], 0, krow + (i & 1) * 128 + m * 64, sb + T0 + i * 8192 + m * 4096);
            if (m) {
              sts128(sb + ONES + lane * 32, 0x3f803f80u, 0x3f803f80u, 0x3f803f80u, 0x3f803f80u);
              sts128(sb + ONES + lane * 32 + 16, 0x3f803f80u, 0x3f803f80u, 0x3f803f80u, 0x3f803f80u);
              fence_async_smem();
              __syncwarp();
            }
          }
          e_arrive(sb + B_TF);
          bulk_commit(); bulk_wait_n<0>();
          e_red(kvc + bm);
          bar_sync(NB_KV + 12, 288);
          uint32_t seen = 0;
#pragma unroll 1
          for (int it = 1; it < 16; it++) {
            const int s = it & 3, blk = it;
            if (it == 4) { tma_st(&prm.m[M_K], 0, krow + 2048, sb); tma_st(&prm.m[M_V], 0, krow + 2048, sb + 16384); bulk_commit(); }
            if (it == 5) { bulk_wait_n<0>(); e_red(kvc + bm); }
            if (it == 12) { e_expect_tx(sb + B_RF, 32768); tma_ld3(sb, &prm.m[M_XSR], 0, pm * 128, 2 * pn, sb + B_RF); }
            if (it == 2 || it == 3) mbar_wait(sb + B_TF + 8 * (it - 1), 0);
            mbar_wait_long(sb + B_TE + 8 * s, ((it >> 2) & 1) ^ 1);
            if (it < 8) {
#pragma unroll 1
              for (uint32_t n = 0; n < 200000u && !((seen >> it) & 1); n++)
                seen = __ballot_sync(~0u, (int)(ld_acquire(kvc + ((bm + lane) & 7)) - (ep1 * 2 - 1)) >= 0);
              fence_async_gl();
            } else if (it == 8) { poll_ge(kvc + (lane & 7), ep1 * 2); fence_async_gl(); bar_arrive(NB_HALO, 64); }
            else if (it == 15) bar_arrive(NB_HALO + 1, 64);
            const int row = (2 * bn + (it >> 3)) * 2048 + ((bm + blk) & 7) * 256;
            e_expect_tx(sb + B_TF + 8 * s, 32768);
            tma_ld(sb + T0 + s * TSTG, &prm.m[M_K], 0, row, sb + B_TF + 8 * s);
            tma_ld(sb + T0 + s * TSTG + 16384, &prm.m[M_V], 0, row, sb + B_TF + 8 * s);
          }
        }
        auto p_b = [&](int i, uint32_t s, uint32_t par) {
          const int kt = pord(i, l, bn >> 1);
          mbar_wait(sb + B_PE + 8 * s, par ^ 1);
          e_expect_tx(sb + B_PF + 8 * s, PSTG);
          tma_ld5(sb + pslot_b(s, l), mo, kt >> 3, 2 * (kt & 7), 2 * pn, sb + B_PF + 8 * s);
        };
        auto p_a = [&](int i, uint32_t s) {
          const int kt = pord(i, l, bn >> 1);
          await_bit(sb + W_O, l + 1, kt, rdy);
          tma_ld_mc(sb + pslot_a(s, l) + rank * 8192, &prm.m[M_OS], kt * 64, pm * 128 + rank * 64, sb + B_PF + 8 * s);
        };
        auto p_a2 = [&](int i) {
          const int kt = pord(i, l, bn >> 1);
          await_bit(sb + W_O, l + 1, kt, rdy);
          tma_ld(sb + pslot_a(i, l), &prm.m[M_OS], kt * 64, pm * 128, sb + B_PF + 8 * i);
          tma_ld(sb + pslot_a(i, l) + 8192, &prm.m[M_OS], kt * 64, pm * 128 + 64, sb + B_PF + 8 * i);
        };
        rdy = 0;
        if (l & 1) {
#pragma unroll 1
          for (int u = 0; u < 6; u++) { const int i = (0x105432 >> (4 * u)) & 7; if (u == 4) mbar_wait_long(sb + B_TE, 1); p_b(i, i, i < 4 ? 1 : 0); }
#pragma unroll 1
          for (int u = 0; u < 6; u++) {
            const int i = (0x543120 >> (4 * u)) & 7;
            if (!(u & 1)) mbar_wait_long(sb + B_TE + 8 + 4 * u, 1);
            p_a2(i);
          }
        } else {
#pragma unroll 1
          for (int u = 0; u < 5; u++) { const int i = (0x32140 >> (4 * u)) & 7; if (!(u & 5)) mbar_wait(sb + B_QE + 8 + 4 * u, 1); p_b(i, i, 0); }
          mbar_wait(sb + B_QE + 24, 1);
          mbar_wait(sb + B_OW, (l >> 1) & 1);
          fence_async_gl();
          rdy = 1u << (bn >> 1);
#pragma unroll 1
          for (int i = 0; i < 4; i++) { p_a(i, i); }
          bar_sync(NB_DONE, 96);
          e_arrive_both(sb + B_PA);
          p_b(5, 5, 0);
          mbar_wait(sb + B_PA, (l >> 1) & 1);
          p_a(4, 4); p_a(5, 5);
        }
        uint32_t s = 0, lap = 1;
#pragma unroll 1
        for (int i = 6; i < 16; i++) {
          if (i == 15 && !(l & 1)) { e_expect_tx(sb + B_RF, 32768); tma_ld3(sb, &prm.m[l == 0 ? M_X0R : M_XSR], 0, pm * 128, 2 * pn, sb + B_RF); }
          p_b(i, s, ((s < 4 ? l : 0) + lap) & 1);
          p_a(i, s);
          if (++s == 6) { s = 0; lap++; }
        }
        const CUtensorMap* mn = &prm.m[M_WQA + ((l + 1) & 1)];
        if (l < 3) {
          mbar_wait(sb + B_PE + 8 * 4, 1); mbar_wait(sb + B_PE + 8 * 5, 1);
          tma_ld3(sb + 32768, mn, bn * 64, 2 * pn * 64, 0, sb + B_QL);
          mbar_wait(sb + B_PE + 8 * 0, l & 1);
          tma_ld3(sb + QSTG + 32768, mn, bn * 64, (2 * pn + 1) * 64, 0, sb + B_QL);
          mbar_wait(sb + B_PE + 8 * 1, l & 1);
          e_expect_tx(sb + B_QD, 40960);
          tma_ld3(sb + 2 * QSTG + 32768, mn, bn * 64, ((2 * pn) ^ 2) * 64, 0, sb + B_QD);
          bar_sync(NB_X, 288);
          e_expect_tx(sb + B_QL, 49152);
          e_expect_tx(sb + B_QD + 8, 40960);
          tma_ld3(sb + 3 * QSTG + 32768, mn, bn * 64, (((2 * pn) ^ 2) + 1) * 64, 0, sb + B_QD + 8);
        }
      }
      if (blockIdx.x == 0 && lane_id() == 0) *(volatile uint32_t*)prm.epoch = ep1;
    } else {
      const int hw = w - 1;
      if (hw == 1 && lane_id() < M_COUNT) asm volatile("prefetch.tensormap [%0];" ::"l"(&prm.m[lane_id()]) : "memory");
      cluster_wait();
      mbar_wait(sb + B_QF, 0);
#pragma unroll 1
      for (int l = 0; l < 4; l++) {
        IDS();
        if (hw == 2 && l > 0) watch(cnt_x(l, bm) + (lane & 7), ep1 * 2, 0xFFu, l, sb + W_X);
        if (l == 0) {
#pragma unroll 1
          for (int r = 2 * hw; r < 16; r += 6) {
            const uint4* p = (const uint4*)(prm.x0 + (size_t)(b * 16 + r) * 1024) + lane;
            float s1[2] = {0.f, 0.f}, s2[2] = {0.f, 0.f};
#pragma unroll
            for (int i = 0; i < 8; i++) {
              const uint4 v = __ldg(p + 32 * i);
              const uint32_t u[4] = {v.x, v.y, v.z, v.w};
#pragma unroll
              for (int k = 0; k < 4; k++) { const float a = bf_lo(u[k]), c = bf_hi(u[k]); s1[i >> 2] += a + c; s2[i >> 2] = fmaf(a, a, fmaf(c, c, s2[i >> 2])); }
            }
#pragma unroll
            for (int o = 16; o; o >>= 1)
#pragma unroll
              for (int rr = 0; rr < 2; rr++) { s1[rr] += __shfl_xor_sync(~0u, s1[rr], o); s2[rr] += __shfl_xor_sync(~0u, s2[rr], o); }
            if (lane == 0) *(float4*)&g_stats[b * 16 + r] = make_float4(s1[0], s2[0], s1[1], s2[1]);
          }
        }
        if (l == 1) { uint32_t rdy = 0; await_bit<true>(sb + W_X, 1, pn, rdy); mbar_hint(sb + B_QF + 24, 0); }
        if (l < 2) {
          float cs[8];
#pragma unroll
          for (int i = 0; i < 8; i++) cs[i] = 0.f;
          const uint4* wp = (const uint4*)(prm.wq[l] + (size_t)(bm * 128 + (lane >> 3)) * 3072 + hw * 1024 + bn * 64) + (lane & 7);
#pragma unroll 8
          for (int i = 0; i < 32; i++) {
            const uint4 v = __ldg(wp + (size_t)i * 4 * 384);
            cs[0] += bf_lo(v.x); cs[1] += bf_hi(v.x); cs[2] += bf_lo(v.y); cs[3] += bf_hi(v.y);
            cs[4] += bf_lo(v.z); cs[5] += bf_hi(v.z); cs[6] += bf_lo(v.w); cs[7] += bf_hi(v.w);
          }
#pragma unroll
          for (int i = 0; i < 8; i++) { cs[i] += __shfl_xor_sync(~0u, cs[i], 8); cs[i] += __shfl_xor_sync(~0u, cs[i], 16); }
          if (lane < 8) {
            float4* d = (float4*)(g_csp + ((l * 16 + bn) * 8 + bm) * 192 + hw * 64 + lane * 8);
            d[0] = make_float4(cs[0], cs[1], cs[2], cs[3]); d[1] = make_float4(cs[4], cs[5], cs[6], cs[7]);
          }
          __syncwarp();
          asm volatile("fence.acq_rel.gpu;" ::: "memory");
          e_red_relaxed(cnt_cs(l, bn));
          if (l == 0) e_red_relaxed(cnt_x(0, bm) + pn);
          poll_ge(lane < 8 && l == 0 ? cnt_x(0, bm) + lane : cnt_cs(l, bn), ep1 * (lane < 8 && l == 0 ? 6 : 24));
        }
        if (l > 0) {
          uint32_t rdy = 0;
#pragma unroll 1
          for (int j = 0; j < 8; j++) await_bit<true>(sb + W_X, l, j, rdy);
        }
#pragma unroll 1
        for (int it = hw * 32 + lane; it < 176; it += 96) {
          const bool rows = it < 128;
          const float4* p = rows ? (const float4*)(g_stats + bm * 256) + it : (const float4*)(g_csp + ((l & 1) * 16 + bn) * 8 * 192) + (it - 128);
          const int stride = rows ? 1024 : 48, np = rows && l == 0 ? 1 : 8;
          float4 a = make_float4(0.f, 0.f, 0.f, 0.f);
#pragma unroll
          for (int k = 0; k < 8; k++) if (k < np) { const float4 v = __ldcg(p + k * stride); a.x += v.x; a.y += v.y; a.z += v.z; a.w += v.w; }
          if (rows) {
            const float m0 = a.x * (1.f / 1024.f), m1 = a.z * (1.f / 1024.f);
            const float v0 = fmaxf(a.y * (1.f / 1024.f) - m0 * m0, 0.f), v1 = fmaxf(a.w * (1.f / 1024.f) - m1 * m1, 0.f);
            const float r0 = __fdividef(1.f, bf_round(sqrtf(bf_round(bf_round(v0) + 1e-5f)))), r1 = __fdividef(1.f, bf_round(sqrtf(bf_round(bf_round(v1) + 1e-5f))));
            *(float2*)(smem + RSTD + it * 8) = make_float2(r0, r1);
            *(uint32_t*)(smem + MEAN + it * 4) = pack2(-m0, -m1);
          } else {
            float2* d = (float2*)(smem + COLS) + ((it - 128) >> 2) * 8 + (it & 1) * 4 + ((it >> 1) & 1);
            d[0] = make_float2(a.y, a.x); d[2] = make_float2(a.w, a.z);
          }
        }
        __syncwarp();
        if (lane == 0) asm volatile("red.release.cta.shared.add.u32 [%0], 0x100;" ::"r"(sb + W_X) : "memory");
        if (hw == 2) {
          if (!(l & 1)) {
            bar_sync(NB_ST, 288);
            const volatile unsigned long long* hp = g_halo + ((size_t)(l >> 1) * 128 + b - 16) * 1024 + lane;
#pragma unroll 1
            for (int h = 0; h < 2; h++) {
              uint32_t t[16];
#pragma unroll
              for (int i = 0; i < 16; i++) t[i] = 0;
#pragma unroll 1
              for (uint32_t n = bm ? 0 : 100000u; n < 100000u; n++) {
                uint32_t miss = 0;
#pragma unroll
                for (int i = 0; i < 16; i++) {
                  const unsigned long long v = hp[h * 512 + i * 32];
                  t[i] = (uint32_t)v; miss |= (uint32_t)(v >> 32) ^ ep1;
                }
                if (__all_sync(~0u, !miss)) break;
              }
              const uint32_t r = (lane & 7) + ((lane >> 3) & 1) * 8, rv = lane >> 2;
#pragma unroll
              for (int jj = 0; jj < 2; jj++) stsm4(sb + 2 * h * ASC + r * 64 + (((2 * jj + (lane >> 4)) ^ ((r >> 1) & 3)) << 4), t[4 * jj], t[4 * jj + 1], t[4 * jj + 2], t[4 * jj + 3]);
              const uint32_t ad = sb + (2 * h + 1) * ASC + rv * 64 + (((lane & 3) ^ ((rv >> 1) & 3)) << 4);
              sts128(ad, t[8], t[10], t[12], t[14]); sts128(ad + 512, t[9], t[11], t[13], t[15]);
              bar_arrive(NB_HALO + h, 64);
            }
          } else {
            bar_sync(NB_HALO, 64);
            const uint4* kp = (const uint4*)(g_kn + ((l >> 1) * 128 + bn * 8) * 32) + 2 * lane;
            const uint4 v = __ldcg(kp), u = __ldcg(kp + 1);
            const uint32_t mx = max(max(max(v.x, v.y), max(v.z, v.w)), max(max(u.x, u.y), max(u.z, u.w)));
            const uint32_t m0 = __reduce_max_sync(~0u, (lane & 2) ? 0u : mx), m1 = __reduce_max_sync(~0u, (lane & 2) ? mx : 0u);
            if (lane == 0) *(uint2*)(smem + KMAX) = make_uint2(m0, m1);
            __syncwarp();
            bar_arrive(NB_KN, 160); bar_arrive(NB_KN + 1, 160);
            bar_sync(NB_HALO + 1, 64);
            watch(cnt_o(l, pm, 0) + (lane & 7), ep1 * 2, 0xFFu, l + 1, sb + W_O);
          }
        } else {
          bar_sync(NB_SIG + 2 * hw, 160); bar_sync(NB_SIG + 2 * hw + 1, 160);
          if (!(l & 1)) bar_arrive(NB_DONE, 96);
          if (hw == (l & 1)) bar_arrive((l & 1) ? NB_DONE : NB_KN, 64);
          asm volatile("fence.acq_rel.gpu;" ::: "memory");
          e_red_relaxed(cnt_o(l, 2 * bm, hw) + (bn >> 1));
          e_red_relaxed(cnt_o(l, 2 * bm + 1, hw) + (bn >> 1));
          if (hw == 0 && !(l & 1)) e_arrive_both(sb + B_OW);
          if (hw == 1 && l == 1) { e_red_relaxed(cnt_ad(bn)); e_red_relaxed(cnt_ad(bn)); }
        }
        if (hw == 2) { bar_sync((l & 1) ? NB_DONE : NB_KN, 64); watch(cnt_o(l, pm, (lane >> 3) & 1) + (lane & 7), ep1 * 2, 0xFFFFu, l + 1, sb + W_O); }
        if (l < 3) {
          bar_sync(NB_X0, 352);
          if (hw == 0) {
            e_red(cnt_x(l + 1, bm) + pn);
          } else if (hw == 1) {
            mbar_wait(sb + B_PE + 8 * 3, l & 1);
            push_peer(sb + 2 * QSTG + po * 16384, sb + po * 16384, sb + B_QD, rank ^ 1);
            push_peer(sb + 3 * QSTG + po * 16384, sb + QSTG + po * 16384, sb + B_QD + 8, rank ^ 1);
          }
        }
      }
    }
  } else {
    asm volatile("setmaxnreg.inc.sync.aligned.u32 224;");
    const uint32_t zero = prm.zero;
    cluster_wait();
    const uint32_t ep1 = __shfl_sync(~0u, epoch + 1, 0);
#pragma unroll 1
    for (int l = 0; l < 4; l++) {
      {
        float acc[2][96];
#pragma unroll
        for (int i = 0; i < 96; i++) { acc[0][i] = 0.f; acc[1][i] = 0.f; }
        fence_regs(acc[0]); fence_regs(acc[1]);
        const bool early = l > 0 && wg == ((cta_id() >> 3) & 1);
        uint32_t a_lo = (uint32_t)mkdesc(sb + wg * 16384, 16, 0, 0), b_lo = (uint32_t)mkdesc(sb + 32768, 8192, 0, 0);
#pragma unroll 1
        for (int kt = 0; kt < 14; kt++) {
          const int s = kt & 3;
          if (l > 0 && kt < 4 && kt != 1) mbar_wait(sb + (kt ? B_QD - 16 + 8 * kt : B_QL), (l + 1) & 1);
          if (!(early && kt < 4)) mbar_wait(sb + B_QF + 8 * s, (kt >> 2) & 1);
          const uint64_t da = mkdesc(0, 0, 1024, 1) | a_lo, db = mkdesc(0, 0, 1024, 1) | b_lo;
          wg_fence();
#pragma unroll
          for (int k = 0; k < 4; k++)
#pragma unroll
            for (int m = 0; m < 2; m++) wgmma_m64n192k16_ss_tb(acc[m], da + m * 512 + k * 2, db + k * 128, 1);
          wg_commit();
          { const uint32_t d = s == 3 ? 0u - 3 * (QSTG / 16) : QSTG / 16; a_lo += d; b_lo += d; }
          wg_wait<1>();
          if (early && kt < 5) {
#pragma unroll 1
            for (int i = kt == 3 ? 0 : 3; i < kt; i++) { mbar_wait(sb + B_QF + 8 * i, 0); if (w == 0) e_arrive_both(sb + B_QE + 8 * i); }
          } else if (kt > 0 && w == 0) e_arrive_both(sb + B_QE + 8 * ((kt - 1) & 3));
          if (kt == 13 - 2 * wg) {
#pragma unroll 1
            for (uint32_t n = 0; n < 4000000u; n++) {
              uint32_t v;
              asm volatile("ld.acquire.cta.shared.u32 %0, [%1];" : "=r"(v) : "r"(sb + W_X) : "memory");
              if ((v >> 8) == (uint32_t)(l * 256 + 3)) break;
            }
            const int lane = lane_id();
            float nm[4];
#pragma unroll
            for (int i = 0; i < 4; i++) nm[i] = bf_lo(*(volatile unsigned short*)(smem + MEAN + (wg * 128 + w * 16 + (lane >> 2) + (i >> 1) * 64 + (i & 1) * 8) * 2));
            wg_wait<0>();
            fence_regs(acc[0]); fence_regs(acc[1]);
#pragma unroll
            for (int j = 0; j < 12; j++) {
              const float4 c = lds128f(sb + COLS + j * 64 + (lane & 3) * 16);
#pragma unroll
              for (int m = 0; m < 2; m++) {
                float* a = &acc[m][8 * j];
                a[0] = fmaf(nm[2 * m], c.y, a[0]); a[1] = fmaf(nm[2 * m], c.x, a[1]); a[2] = fmaf(nm[2 * m + 1], c.y, a[2]); a[3] = fmaf(nm[2 * m + 1], c.x, a[3]);
                a[4] = fmaf(nm[2 * m], c.w, a[4]); a[5] = fmaf(nm[2 * m], c.z, a[5]); a[6] = fmaf(nm[2 * m + 1], c.w, a[6]); a[7] = fmaf(nm[2 * m + 1], c.z, a[7]);
              }
            }
            fence_regs(acc[0]); fence_regs(acc[1]);
          }
        }
        auto part = [&](int s, int m, int k0, int k1) {
          const uint64_t da = mkdesc(sb + s * QSTG + wg * 16384 + m * 8192, 16, 1024, 1), db = mkdesc(sb + s * QSTG + 32768, 8192, 1024, 1);
          wg_fence();
#pragma unroll
          for (int k = k0; k < k1; k++) wgmma_m64n192k16_ss_tb(acc[m], da + k * 2, db + k * 128, 1);
          wg_commit();
        };
        mbar_wait(sb + B_QF + 16, 1);
        part(2, 1, 0, 4);
        wg_wait<1>();
        if (w == 0) e_arrive_both(sb + B_QE + 8);
        if (!(l & 1)) bar_arrive(NB_ST, 288);
        mbar_wait(sb + B_QF + 24, 1);
        part(3, 1, 0, 4);
        part(2, 0, 0, 2);
        IDS();
        const int g = lane >> 2, qd = lane & 3;
        float rs[2][2];
#pragma unroll
        for (int i = 0; i < 4; i++) rs[i >> 1][i & 1] = lds32f(sb + RSTD + (wg * 128 + w * 16 + g + (i >> 1) * 64 + (i & 1) * 8) * 4);
        auto scale = [&](int gi, int m, float sc) {
          const float r0 = rs[m][0] * sc, r1 = rs[m][1] * sc;
#pragma unroll
          for (int i = 0; i < 16; i++) acc[m][16 * gi + i] *= (i & 2) ? r1 : r0;
        };
        auto pack_b = [&](int gi, int m, uint32_t (&t)[8]) {
#pragma unroll
          for (int i = 0; i < 8; i++) t[i] = pack2(acc[m][16 * gi + 2 * i], acc[m][16 * gi + 2 * i + 1]);
        };
        auto norm_tile = [&](int gi, int m, uint32_t (&t)[8]) { scale(gi, m, 1.f); pack_b(gi, m, t); };
        auto pack_h = [&](int gi, int m, uint32_t (&t)[8]) {
#pragma unroll
          for (int i = 0; i < 8; i++) t[i] = pack2h(acc[m][16 * gi + 2 * i], acc[m][16 * gi + 2 * i + 1]);
        };
        uint32_t q[2][2][8], qn[2][2];
        const uint32_t srow = (lane & 7) + ((lane >> 3) & 1) * 8;
        const uint32_t row0 = wg * 128 + w * 16;
        auto put_kv = [&](int h, int v, int m, const uint32_t (&t)[8]) {
          const uint32_t base = sb + ((l & 1) ? (h ? 0 : T0) + v * 16384 : (2 * h + v) * ASC + 1024) + (row0 + m * 64) * 64;
          if (!v) {
#pragma unroll
            for (int jj = 0; jj < 2; jj++) stsm4(base + srow * 64 + (((2 * jj + (lane >> 4)) ^ ((srow >> 1) & 3)) << 4), t[4 * jj], t[4 * jj + 1], t[4 * jj + 2], t[4 * jj + 3]);
          } else {
            const uint32_t ad = base + g * 64 + ((qd ^ (g >> 1)) << 4);
            sts128(ad, t[0], t[2], t[4], t[6]); sts128(ad + 512, t[1], t[3], t[5], t[7]);
          }
        };
        auto send_halo = [&](int h, int v, const uint32_t (&t)[8]) {
          unsigned long long* hp = g_halo + ((size_t)(l >> 1) * 128 + b) * 1024 + h * 512 + v * 256 + lane;
#pragma unroll
          for (int i = 0; i < 8; i++) st_tagged(hp + i * 32, t[i], ep1);
        };
        auto put_kn = [&](int h, int m, uint32_t kn) {
          if (lane == 0) g_kn[((l >> 1) * 128 + bn * 8 + bm) * 32 + 16 * h + 8 * m + wg * 4 + w] = __uint_as_float(kn);
        };
        auto conv_tile1 = [&](int h) {
          uint32_t t[8], tv[8], kn = NOT_F16;
          norm_tile(4 + h, 1, tv);
          put_kv(h, 1, 1, tv);
          part(2 + h, 0, 2, 4);
          scale(2 + h, 1, 1.f);
          scale(h, 1, (l & 1) ? QSCALE / 128.f : 1.f);
          if (l & 1) {
            float n[2] = {0.f, 0.f};
#pragma unroll
            for (int i = 0; i < 16; i++) n[(i >> 1) & 1] = fmaf(acc[1][32 + 16 * h + i], acc[1][32 + 16 * h + i], n[(i >> 1) & 1]);
            const float a = ((qd & 1) ? n[1] : n[0]) + __shfl_xor_sync(~0u, (qd & 1) ? n[0] : n[1], 1);
            kn = f16_class(__reduce_max_sync(~0u, __float_as_uint(a + __shfl_xor_sync(~0u, a, 2))), K_LO);
            put_kn(h, 1, kn);
          }
          if (kn == NOT_F16) pack_b(2 + h, 1, t); else pack_h(2 + h, 1, t);
          put_kv(h, 0, 1, t);
          if (!(l & 1) && row0 == 176 && bm < 7) { send_halo(h, 0, t); send_halo(h, 1, tv); }
        };
        mbar_wait(sb + B_QE + 8, 1);
        wg_wait<1>();
        fence_regs(acc[1]);
        conv_tile1(0);
        part(3, 0, 0, 2);
        if (l & 1) { fence_async_smem(); bar_arrive(NB_ST, 288); }
        conv_tile1(1);
        wg_wait<2>();
        if (w == 0) e_arrive_both(sb + B_QE + 16);
        wg_wait<0>();
        fence_regs(acc[0]);
        if (w == 0) e_arrive_both(sb + B_QE + 24);
        bf16* const op0 = [&] { IDS(); return g_os + (size_t)(bm * 256 + row0 + (lane >> 2)) * 1024 + bn * 32 + (lane & 3) * 8; }();
        auto put_o = [&](int h, int m, const float (&o)[16], float i0, float i1) {
          bf16* op = op0 + m * 65536 + h * 512;
          const uint4 a = make_uint4(pack2(o[0] * i0, o[1] * i0), pack2(o[4] * i0, o[5] * i0), pack2(o[8] * i0, o[9] * i0), pack2(o[12] * i0, o[13] * i0));
          const uint4 c = make_uint4(pack2(o[2] * i1, o[3] * i1), pack2(o[6] * i1, o[7] * i1), pack2(o[10] * i1, o[11] * i1), pack2(o[14] * i1, o[15] * i1));
          *(uint4*)op = a; *(uint4*)(op + 8 * 1024) = c;
          const uint32_t hi = __vimax3_u16x2(__vimax3_u16x2(a.x, a.y, a.z), __vimax3_u16x2(a.w, c.x, c.y), __vmaxu2(c.z, c.w));
          const uint32_t lo = __vimax3_s16x2(__vimax3_s16x2(a.x, a.y, a.z), __vimax3_s16x2(a.w, c.x, c.y), __vmaxs2(c.z, c.w));
          return __vmaxu2(hi & 0x7FFF7FFFu, lo & 0x7FFF7FFFu);
        };
        if (!(l & 1)) {
          auto conv_kv = [&](int h) {
            uint32_t t[8];
            norm_tile(2 + h, 0, t); put_kv(h, 0, 0, t);
            norm_tile(4 + h, 0, t); put_kv(h, 1, 0, t);
          };
          conv_kv(0);
          norm_tile(0, 0, q[0][0]); pack_b(0, 1, q[0][1]);
          bar_sync(NB_SC, 256);
          const bool e = g & 1, sel = 2 * qd + (g & 1) >= g + 2, first = bm == 0 && row0 == 0;
          const uint32_t pm_a = e ? 0x1044 : 0x4410, pm_b = e ? 0x3244 : 0x4432, pm_lo = sel ? pm_b : 0x4444, pm_hi = sel ? 0x4444 : pm_b;
          const uint32_t ka = sb + (row0 + (lane & 7)) * 64 + (((lane >> 3) ^ ((lane >> 1) & 3)) << 4);
          const uint32_t va0 = sb + ASC + (row0 + srow) * 64 + (((lane >> 4) ^ ((lane >> 1) & 3)) << 4);
#pragma unroll 1
          for (int h = 0; h < 2; h++) {
            if (row0 == 0) bar_sync(NB_HALO + h, 64);
            float s[2][4][4];
            uint32_t vf[2][4][4], pf[2][2][4];
#pragma unroll
            for (int m = 0; m < 2; m++)
#pragma unroll
              for (int nt = 0; nt < 4; nt++) {
                uint32_t kf[4];
                ldsm4(ka + h * (2 * ASC) + (m * 64 + 8 * nt) * 64, kf);
                s[m][nt][0] = s[m][nt][1] = s[m][nt][2] = s[m][nt][3] = 0.f;
                mma16816(s[m][nt], q[0][m][0], q[0][m][1], q[0][m][2], q[0][m][3], kf[0], kf[1]);
                mma16816(s[m][nt], q[0][m][4], q[0][m][5], q[0][m][6], q[0][m][7], kf[2], kf[3]);
              }
#pragma unroll
            for (int m = 0; m < 2; m++)
#pragma unroll
              for (int i = 0; i < 4; i++) {
                ldsm4t(((va0 + h * (2 * ASC)) ^ (32 * (i & 1))) + (m * 64 + 16 * (i >> 1)) * 64, vf[m][i]);
              }
            float va[4], vb[4], mx[4];
            uint32_t ua[2], ub[2], um[2];
#pragma unroll
            for (int m = 0; m < 2; m++) {
              float a[2], c[2];
#pragma unroll
              for (int hh = 0; hh < 2; hh++) {
                a[hh] = e ? s[m][hh + 1][2 * hh + 1] : s[m][hh + 1][2 * hh];
                const float lo = e ? s[m][hh][2 * hh + 1] : s[m][hh][2 * hh], hi = e ? s[m][hh + 2][2 * hh + 1] : s[m][hh + 2][2 * hh];
                c[hh] = sel ? lo : hi;
              }
              ua[m] = scale_bf2(pack2(a[0], a[1])); ub[m] = scale_bf2(pack2(c[0], c[1]));
              if (m == 0) { ua[0] = first ? (ua[0] & 0xFFFF0000u) | 0xFF80u : ua[0]; ub[0] = first && sel ? 0xFF80FF80u : ub[0]; }
              um[m] = max_bf2(ua[m], ub[m]);
            }
#pragma unroll
            for (int m = 0; m < 2; m++) um[m] = max_bf2(um[m], __shfl_xor_sync(~0u, um[m], 1));
#pragma unroll
            for (int m = 0; m < 2; m++) um[m] = max_bf2(um[m], __shfl_xor_sync(~0u, um[m], 2));
#pragma unroll
            for (int i = 0; i < 4; i++) {
              const int m = i >> 1;
              const float top = (i & 1) ? bf_hi(um[m]) : bf_lo(um[m]);
              va[i] = ex2((((i & 1) ? bf_hi(ua[m]) : bf_lo(ua[m])) - top) * 1.4426950408889634f);
              vb[i] = ex2((((i & 1) ? bf_hi(ub[m]) : bf_lo(ub[m])) - top) * 1.4426950408889634f);
              mx[i] = va[i] + vb[i];
            }
#pragma unroll
            for (int i = 0; i < 4; i++) mx[i] += __shfl_xor_sync(~0u, mx[i], 1);
#pragma unroll
            for (int i = 0; i < 4; i++) mx[i] += __shfl_xor_sync(~0u, mx[i], 2);
#pragma unroll
            for (int i = 0; i < 4; i++) {
              const int m = i >> 1, hh = i & 1;
              const float inv = rcp(mx[i]);
              const uint32_t t = pack2(va[i] * inv, vb[i] * inv);
              pf[m][hh][hh + 1] = __byte_perm(t, 0, pm_a); pf[m][hh][hh] = __byte_perm(t, 0, pm_lo); pf[m][hh][hh + 2] = __byte_perm(t, 0, pm_hi); pf[m][hh][3 - 3 * hh] = t & zero;
            }
#pragma unroll
            for (int m = 0; m < 2; m++) {
              float o[4][4];
#pragma unroll
              for (int j = 0; j < 4; j++) o[j][0] = o[j][1] = o[j][2] = o[j][3] = 0.f;
#pragma unroll
              for (int i = 0; i < 4; i++) {
                const int kk = i >> 1, jj = 2 * (i & 1);
                mma16816(o[jj], pf[m][0][2 * kk], pf[m][1][2 * kk], pf[m][0][2 * kk + 1], pf[m][1][2 * kk + 1], vf[m][i][0], vf[m][i][1]);
                mma16816(o[jj + 1], pf[m][0][2 * kk], pf[m][1][2 * kk], pf[m][0][2 * kk + 1], pf[m][1][2 * kk + 1], vf[m][i][2], vf[m][i][3]);
              }
              const float of[16] = {o[0][0], o[0][1], o[0][2], o[0][3], o[1][0], o[1][1], o[1][2], o[1][3], o[2][0], o[2][1], o[2][2], o[2][3], o[3][0], o[3][1], o[3][2], o[3][3]};
              put_o(h, m, of, 1.f, 1.f);
            }
            bar_arrive(NB_SIG + 2 * h + wg, 160);
            if (h == 0) {
              conv_kv(1);
              norm_tile(1, 0, q[0][0]); pack_b(1, 1, q[0][1]);
              bar_sync(NB_SC, 256);
            }
          }
        } else {
          auto conv_h = [&](int gi, int m, uint32_t (&t)[8]) {
            pack_h(gi, m, t);
            float d0[4] = {0.f, 0.f, 0.f, 0.f}, d1[4] = {0.f, 0.f, 0.f, 0.f};
            if (gi == 2) {
              mma16816h(d0, t[0], t[1], t[2], t[3], t[0], t[2]); mma16816h(d1, t[0], t[1], t[2], t[3], t[1], t[3]);
              mma16816h(d0, t[4], t[5], t[6], t[7], t[4], t[6]); mma16816h(d1, t[4], t[5], t[6], t[7], t[5], t[7]);
            } else {
#pragma unroll
              for (int i = 0; i < 8; i += 2) { mma1688h(d0, t[i], t[i + 1], t[i]); mma1688h(d1, t[i], t[i + 1], t[i + 1]); }
            }
            return f16_class(__reduce_max_sync(~0u, max(max(__float_as_int(d0[0]), __float_as_int(d0[1])), max(__float_as_int(d1[2]), __float_as_int(d1[3])))), K_LO);
          };
          uint32_t tk[8], tv[8];
          scale(2, 0, 1.f);
          uint32_t kn = conv_h(2, 0, tk);
          norm_tile(4, 0, tv);
          put_kv(0, 1, 0, tv);
          put_kn(0, 0, kn);
          if (kn == NOT_F16) pack_b(2, 0, tk);
          put_kv(0, 0, 0, tk);
          fence_async_smem();
          bar_arrive(NB_KV, 288);
          mbar_wait(sb + B_QF + 24, 1);
          scale(3, 0, 1.f); scale(0, 0, QSCALE); scale(1, 0, QSCALE);
          kn = conv_h(3, 0, tk);
#pragma unroll
          for (int i = 0; i < 4; i++) qn[i >> 1][i & 1] = conv_h(i >> 1, i & 1, q[i >> 1][i & 1]);
          norm_tile(5, 0, tv);
          if (max(max(max(qn[0][0], qn[0][1]), max(qn[1][0], qn[1][1])), kn) == NOT_F16) {
#pragma unroll
            for (int i = 0; i < 4; i++) if (qn[i >> 1][i & 1] == NOT_F16) pack_b(i >> 1, i & 1, q[i >> 1][i & 1]);
            if (kn == NOT_F16) pack_b(3, 0, tk);
          }
          fence_regs(tv);
          const bool elected = w == 0 && lane == 0;
          uint32_t thr = elected ? 8 : 99;
          asm volatile("" : "+r"(thr));
          thr |= zero;
          uint2 cp;
          asm volatile("ld.shared.v2.u32 {%0, %1}, [%2];" : "=r"(cp.x), "=r"(cp.y) : "r"(sb + W_C));
          const uint64_t kd0 = mkdesc(sb + T0, 16, 512, 2);
          const uint64_t vd0 = mkdesc(sb + T0 + 16384, ONES - (T0 + 16384), 512, 2);
          const uint32_t v0 = (uint32_t)vd0 ^ zero;
          constexpr uint64_t VSTEP = 64 - (64ull << 16);
          float o[2][20], SA[2][16];
          uint32_t SB[2][8], PA[4], PB[4];
          auto qka = [&](int b, int k, uint64_t d, int h = 0) { wgmma_m64n32k16_rs_nb_h(SA[b], q[h][0][4 * k], q[h][0][4 * k + 1], q[h][0][4 * k + 2], q[h][0][4 * k + 3], d + 2 * k, k ? 1 : zero); };
          auto qkb = [&](int b, int k, uint64_t d, int h = 0) { wgmma_m64n32k16_rs_nb_hh(SB[b], q[h][1][4 * k], q[h][1][4 * k + 1], q[h][1][4 * k + 2], q[h][1][4 * k + 3], d + 2 * k, k ? 1 : zero); };
          auto qk = [&](int b, int k, uint64_t d, int h = 0) { qka(b, k, d, h); qkb(b, k, d, h); };
          auto pv = [&](int m, const uint32_t (&Px)[4], uint64_t vd, int keep = 1) { wgmma_m64n40k16_rs_tb(o[m], Px[0], Px[1], Px[2], Px[3], vd, keep); };
          mbar_wait(sb + B_TF, 0);
#pragma unroll
          for (int i = 0; i < 4; i++) PA[i] = PB[i] = zero;
          wg_fence();
          wgmma_m64n40k16_rs_tb_z(o[0], PA[0], PA[1], PA[2], PA[3], vd0, 0); wgmma_m64n40k16_rs_tb_z(o[1], PB[0], PB[1], PB[2], PB[3], vd0 + VSTEP, 0);
#pragma unroll
          for (int b = 1; b >= 0; b--) {
            wgmma_m64n32k16_rs_nb_z_h(SA[b], q[0][0][0], q[0][0][1], q[0][0][2], q[0][0][3], kd0 + 128 * b, 0);
            wgmma_m64n32k16_rs_nb_z_hh(SB[b], q[0][1][0], q[0][1][1], q[0][1][2], q[0][1][3], kd0 + 128 * b, 0);
          }
          qk(0, 1, kd0); wg_commit();
          put_kv(1, 1, 0, tv); put_kv(1, 0, 0, tk); put_kn(1, 0, kn);
          fence_async_smem();
          bar_arrive(NB_KV + 12, 288);
          wg_wait<0>();
          fence_regs(SA[0]); fence_regs(SB[0]); fence_regs(SA[1]); fence_regs(SB[1]); fence_regs(o[0]); fence_regs(o[1]);
#pragma unroll 1
          for (int pass = 0; pass < 2; pass++) {
            uint32_t kc = (uint32_t)kd0, vc = v0, vp = v0, pars = 0x78u | pass << 7;
#pragma unroll 1
            for (uint32_t it = 8; it <= 64; it += 8) {
              const uint32_t s8 = it & 24, par = pars & 1, kn = (uint32_t)kd0 + s8 * 256, tf = (sb + B_TF) ^ s8;
              const uint64_t hi = kd0 & 0xFFFFFFFF00000000ull, kd = hi | kc, vd = hi | vc, kdn = hi | kn, vdp = hi | vp;
              kc = kn; vp = vc + (uint32_t)(15 * VSTEP); vc = v0 + s8 * (uint32_t)(4 * VSTEP); pars >>= 1;
              bool landed = false;
#pragma unroll
              for (int r = 0; r < 16; r++) {
                const int c = r >> 1, ro = r & 1;
                if (r == 14 && !landed) mbar_wait(tf, par);
                wg_fence();
                const uint64_t kx = c < 7 ? kd + (c + 1) * 128 : kdn, vx = r ? vd + (r - 1) * VSTEP : vdp;
                const int keep = r || it != 8;
                if (ro) { qkb(~c & 1, 1, kx); pv(0, PA, vx, keep); pv(1, PB, vx, keep); qka(~c & 1, 1, kx); }
                else { pv(1, PB, vx, keep); qka(~c & 1, 0, kx); qkb(~c & 1, 0, kx); pv(0, PA, vx, keep); }
                wg_commit();
                if (r == 7) landed = mbar_test(tf, par);
#pragma unroll
                for (int i = 0; i < 4; i++) PB[i] = exp2_h2(SB[c & 1][4 * ro + i], (i & 1) ? cp.x : cp.y);
#pragma unroll
                for (int i = 0; i < 4; i++) { const float e0 = ex2(SA[c & 1][8 * ro + 2 * i]); PA[i] = pack2(e0, ex2(SA[c & 1][8 * ro + 2 * i + 1])); }
                if (ro) { wg_wait<0>(); fence_regs(SA[~c & 1]); fence_regs(SB[~c & 1]); } else wg_wait<1>();
                if (r == 5) arrive_if_gt(tf ^ 0x30, it, thr);
              }
            }
            int badm = 0;
            wg_fence();
            pv(0, PA, vd0 + 111 * VSTEP); pv(1, PB, vd0 + 111 * VSTEP); wg_commit();
            qk(0, 0, kd0, 1); qk(0, 1, kd0, 1); wg_commit();
            if (pass == 0) bar_sync(NB_KN + wg, 160);
            const float kmax = *(volatile float*)(smem + KMAX + 4 * pass);
            wg_wait<1>(); fence_regs(o[0]); fence_regs(o[1]);
            arrive_if_gt(sb + B_TE + 8 * 3, 9, thr);
#pragma unroll
            for (int m = 0; m < 2; m++) {
              const float of[16] = {o[m][0], o[m][1], o[m][2], o[m][3], o[m][4], o[m][5], o[m][6], o[m][7], o[m][8], o[m][9], o[m][10], o[m][11], o[m][12], o[m][13], o[m][14], o[m][15]};
              const uint32_t chk = put_o(pass, m, of, rcp(o[m][16]), rcp(o[m][18]));
              const bool bad = !(__uint_as_float(qn[0][m]) * kmax <= (m ? 0.875f * 0.875f : 112.f * 112.f)) || !(fminf(o[m][16], o[m][18]) >= 9.3e-10f) ||
                               !(o[m][16] + o[m][18] <= 3e38f) || ((chk + 0x00800080u) & 0x80008000u);
              badm |= __any_sync(~0u, bad) << m;
            }
            wg_wait<0>(); fence_regs(SA[0]); fence_regs(SB[0]);
            if (badm) {
#pragma unroll 1
              for (int m = 0; m < 2; m++) if ((badm >> m) & 1) {
                uint32_t qq[8]; float res[20];
#pragma unroll
                for (int i = 0; i < 8; i++) { qq[i] = m ? q[0][1][i] : q[0][0][i]; if ((m ? qn[0][1] : qn[0][0]) != NOT_F16) qq[i] = h2_to_bf2(qq[i]); }
                attn_slow(qq, m ? 128.f : 1.f, 2 * (cta_id() & 15) + pass, g_kn + ((l >> 1) * 128 + (cta_id() & 15) * 8) * 32 + 16 * pass, res, lane_id());
                const float of[16] = {res[0], res[1], res[2], res[3], res[4], res[5], res[6], res[7], res[8], res[9], res[10], res[11], res[12], res[13], res[14], res[15]};
                put_o(pass, m, of, rcp(res[16]), rcp(res[18]));
              }
            }
            bar_arrive(NB_SIG + 2 * pass + wg, 160);
            qn[0][0] = qn[1][0]; qn[0][1] = qn[1][1];
#pragma unroll
            for (int m = 0; m < 2; m++)
#pragma unroll
              for (int i = 0; i < 8; i++) q[0][m][i] = q[1][m][i];
#pragma unroll
            for (int i = 0; i < 4; i++) PA[i] = PB[i] = zero;
          }
        }
      }
      {
        float acc[64];
#pragma unroll
        for (int i = 0; i < 64; i++) acc[i] = 0.f;
        fence_regs(acc);
        uint32_t s = 0, lap = 0;
#pragma unroll 1
        for (int kt = 0; kt < 16; kt++) {
          mbar_wait(sb + B_PF + 8 * s, ((s < 4 ? l : 0) + lap) & 1);
          const uint64_t da = mkdesc(sb + pslot_a(s, l) + wg * 8192, 16, 1024, 1), db = mkdesc(sb + pslot_b(s, l), 8192, 1024, 1);
          wg_fence();
#pragma unroll
          for (int k = 0; k < 4; k++) wgmma_m64n128k16_ss_tb(acc, da + k * 2, db + k * 128, 1);
          wg_commit();
          wg_wait<1>();
          if (kt > 0 && w == 0) e_arrive_both(sb + B_PE + 8 * (s ? s - 1 : 5));
          if (++s == 6) { s = 0; lap++; }
        }
        IDS();
        const int g = lane >> 2, qd = lane & 3;
        const int r0 = wg * 64 + w * 16;
        const uint32_t r = r0 + (lane & 7) + ((lane >> 3) & 1) * 8;
        uint32_t x[8][4];
        mbar_wait(sb + B_RF, l & 1);
        mbar_wait(sb + B_PE + 8, l & 1);
#pragma unroll
        for (int jj = 0; jj < 8; jj++) ldsm4(sb + (jj >> 2) * 16384 + r * 128 + ((((2 * jj + (lane >> 4)) & 7) ^ (r & 7)) << 4), x[jj]);
        wg_wait<0>();
        fence_regs(acc);
        if (w == 0) e_arrive_both(sb + B_PE + 8 * 3);
        const CUtensorMap* mo = &prm.m[l == 3 ? M_OUT : M_XST];
#pragma unroll
        for (int jj = 0; jj < 8; jj++) {
#pragma unroll
          for (int i = 0; i < 4; i++) x[jj][i] = add_bf16x2(x[jj][i], pack2(acc[8 * jj + 2 * i], acc[8 * jj + 2 * i + 1]));
          stsm4(sb + (jj >> 2) * QSTG + po * 16384 + r * 128 + ((((2 * jj + (lane >> 4)) & 7) ^ (r & 7)) << 4), x[jj][0], x[jj][1], x[jj][2], x[jj][3]);
          if ((jj & 3) == 3) { fence_async_smem(); __syncwarp(); tma_st(mo, pn * 128 + (jj >> 2) * 64, pm * 128 + r0, sb + (jj >> 2) * QSTG + po * 16384 + r0 * 128); }
        }
        bulk_commit();
        if (l < 3) {
          float s1[4] = {0.f, 0.f, 0.f, 0.f}, s2[4][4];
#pragma unroll
          for (int i = 0; i < 16; i++) s2[i >> 2][i & 3] = 0.f;
#pragma unroll
          for (int jj = 0; jj < 8; jj++) {
            mma16816(s1, x[jj][0], x[jj][1], x[jj][2], x[jj][3], 0x3f803f80u, 0x3f803f80u);
#pragma unroll
            for (int i = 0; i < 4; i++) mma1688(s2[i], x[jj][i & 2], x[jj][i | 1], x[jj][i]);
          }
          if (qd == (g >> 1)) {
            float2* sp = g_stats + pn * 2048 + pm * 128 + r0 + g;
            sp[0] = make_float2(s1[0], (g & 1) ? s2[0][1] + s2[2][1] : s2[0][0] + s2[2][0]);
            sp[8] = make_float2(s1[2], (g & 1) ? s2[1][3] + s2[3][3] : s2[1][2] + s2[3][2]);
          }
          __syncwarp();
          bar_arrive(NB_X, 288);
        }
        bulk_wait_n<0>();
        if (l < 3) bar_arrive(NB_X0, 352);
      }
    }
  }
  asm volatile("barrier.cluster.arrive.relaxed.aligned;\nbarrier.cluster.wait.aligned;" ::: "memory");
}

typedef CUresult (*EncodeFn)(CUtensorMap*, CUtensorMapDataType, cuuint32_t, void*, const cuuint64_t*, const cuuint64_t*, const cuuint32_t*,
                             const cuuint32_t*, CUtensorMapInterleave, CUtensorMapSwizzle, CUtensorMapL2promotion, CUtensorMapFloatOOBfill);

static void make_map(EncodeFn fn, CUtensorMap* m, const void* ptr, int rank, const uint64_t* dims, const uint64_t* strides, const uint32_t* box, CUtensorMapSwizzle sw) {
  cuuint64_t d[5], st[4];
  cuuint32_t bx[5], es[5];
  for (int i = 0; i < rank; i++) { d[i] = dims[i]; bx[i] = box[i]; es[i] = 1; if (i) st[i - 1] = strides[i - 1] * 2; }
  fn(m, CU_TENSOR_MAP_DATA_TYPE_BFLOAT16, rank, (void*)ptr, d, st, bx, es, CU_TENSOR_MAP_INTERLEAVE_NONE, sw,
     CU_TENSOR_MAP_L2_PROMOTION_L2_128B, CU_TENSOR_MAP_FLOAT_OOB_FILL_NONE);
}
static void map2(EncodeFn fn, CUtensorMap* m, const void* ptr, uint64_t inner, uint64_t outer, uint32_t bi, uint32_t bo, CUtensorMapSwizzle sw) {
  const uint64_t d[2] = {inner, outer}, st[1] = {inner};
  const uint32_t bx[2] = {bi, bo};
  make_map(fn, m, ptr, 2, d, st, bx, sw);
}

extern "C" void kernel_launch(void* const* d_in, const int* in_sizes, int n_in, void* d_out, int out_size) {
  (void)in_sizes; (void)n_in; (void)out_size;
  static EncodeFn enc = nullptr;
  static void *xs, *os, *kk, *vv, *ep;
  if (!enc) {
    void* p = nullptr;
    cudaDriverEntryPointQueryResult qr;
    cudaGetDriverEntryPoint("cuTensorMapEncodeTiled", &p, cudaEnableDefault, &qr);
    enc = (EncodeFn)p;
    cudaGetSymbolAddress(&xs, g_xs); cudaGetSymbolAddress(&os, g_os); cudaGetSymbolAddress(&kk, g_k); cudaGetSymbolAddress(&vv, g_v); cudaGetSymbolAddress(&ep, g_epoch);
    cudaFuncSetAttribute(fused_kernel, cudaFuncAttributeMaxDynamicSharedMemorySize, SMEM_BYTES);
  }
  Params prm;
  const CUtensorMapSwizzle S128 = CU_TENSOR_MAP_SWIZZLE_128B, S64 = CU_TENSOR_MAP_SWIZZLE_64B;
  map2(enc, &prm.m[M_X0A], d_in[0], 1024, 2048, 64, 256, S128);
  map2(enc, &prm.m[M_XSA], xs, 1024, 2048, 64, 256, S128);
  for (int t = 0; t < 2; t++) {
    const uint64_t d3[3] = {1024, 1024, 3}, s3[2] = {3072, 1024};
    const uint32_t b3[3] = {64, 64, 3};
    make_map(enc, &prm.m[M_WQA + t], d_in[1 + 3 * t], 3, d3, s3, b3, S128);
    const uint64_t d5[5] = {64, 32, 2, 16, 16}, s5[4] = {1024, 32 * 1024, 64 * 1024, 64};
    const uint32_t b5[5] = {64, 32, 1, 2, 2};
    make_map(enc, &prm.m[M_WOA + t], d_in[2 + 3 * t], 5, d5, s5, b5, S128);
    const uint64_t dr[3] = {64, 2048, 16}, sr[2] = {1024, 64};
    const uint32_t br[3] = {64, 128, 2};
    make_map(enc, &prm.m[M_X0R + t], t ? xs : d_in[0], 3, dr, sr, br, S128);
  }
  map2(enc, &prm.m[M_OS], os, 1024, 2048, 64, 64, S128);
  map2(enc, &prm.m[M_K], kk, 32, 65536, 32, 256, S64);
  map2(enc, &prm.m[M_V], vv, 32, 65536, 32, 256, S64);
  map2(enc, &prm.m[M_K4], kk, 32, 65536, 32, 64, S64);
  map2(enc, &prm.m[M_V4], vv, 32, 65536, 32, 64, S64);
  map2(enc, &prm.m[M_XSO], xs, 1024, 2048, 64, 128, S128);
  map2(enc, &prm.m[M_X0H], d_in[0], 1024, 2048, 64, 128, S128);
  map2(enc, &prm.m[M_XST], xs, 1024, 2048, 64, 16, S128);
  map2(enc, &prm.m[M_OUT], d_out, 1024, 2048, 64, 16, S128);
  prm.x0 = (const bf16*)d_in[0];
  prm.wq[0] = (const bf16*)d_in[1]; prm.wq[1] = (const bf16*)d_in[4];
  prm.wo = (const bf16*)d_in[2];
  prm.epoch = (uint32_t*)ep;
  prm.zero = 0;
  for (int i = 0; i < 128; i++) prm.map[i] = remap(i);
  fused_kernel<<<128, 384, SMEM_BYTES>>>(prm);
}
```

```cpp
#include <cuda_runtime.h>
#include <cuda_bf16.h>
#include <cuda.h>
#include <stdint.h>

typedef __nv_bfloat16 bf16;

__device__ __forceinline__ void wgmma_m64n192k16_ss_tb(float (&d)[96], uint64_t da, uint64_t db, int scale_d) {
  asm volatile("{\n.reg .pred p;\nsetp.ne.b32 p, %98, 0;\n"
    "wgmma.mma_async.sync.aligned.m64n192k16.f32.bf16.bf16 "
    "{%0, %1, %2, %3, %4, %5, %6, %7, %8, %9, %10, %11, %12, %13, %14, %15, "
    "%16, %17, %18, %19, %20, %21, %22, %23, %24, %25, %26, %27, %28, %29, %30, %31, "
    "%32, %33, %34, %35, %36, %37, %38, %39, %40, %41, %42, %43, %44, %45, %46, %47, "
    "%48, %49, %50, %51, %52, %53, %54, %55, %56, %57, %58, %59, %60, %61, %62, %63, "
    "%64, %65, %66, %67, %68, %69, %70, %71, %72, %73, %74, %75, %76, %77, %78, %79, "
    "%80, %81, %82, %83, %84, %85, %86, %87, %88, %89, %90, %91, %92, %93, %94, %95}, "
    "%96, %97, p, 1, 1, 0, 1;\n}\n"
    : "+f"(d[0]), "+f"(d[1]), "+f"(d[2]), "+f"(d[3]), "+f"(d[4]), "+f"(d[5]), "+f"(d[6]), "+f"(d[7]),
      "+f"(d[8]), "+f"(d[9]), "+f"(d[10]), "+f"(d[11]), "+f"(d[12]), "+f"(d[13]), "+f"(d[14]), "+f"(d[15]),
      "+f"(d[16]), "+f"(d[17]), "+f"(d[18]), "+f"(d[19]), "+f"(d[20]), "+f"(d[21]), "+f"(d[22]), "+f"(d[23]),
      "+f"(d[24]), "+f"(d[25]), "+f"(d[26]), "+f"(d[27]), "+f"(d[28]), "+f"(d[29]), "+f"(d[30]), "+f"(d[31]),
      "+f"(d[32]), "+f"(d[33]), "+f"(d[34]), "+f"(d[35]), "+f"(d[36]), "+f"(d[37]), "+f"(d[38]), "+f"(d[39]),
      "+f"(d[40]), "+f"(d[41]), "+f"(d[42]), "+f"(d[43]), "+f"(d[44]), "+f"(d[45]), "+f"(d[46]), "+f"(d[47]),
      "+f"(d[48]), "+f"(d[49]), "+f"(d[50]), "+f"(d[51]), "+f"(d[52]), "+f"(d[53]), "+f"(d[54]), "+f"(d[55]),
      "+f"(d[56]), "+f"(d[57]), "+f"(d[58]), "+f"(d[59]), "+f"(d[60]), "+f"(d[61]), "+f"(d[62]), "+f"(d[63]),
      "+f"(d[64]), "+f"(d[65]), "+f"(d[66]), "+f"(d[67]), "+f"(d[68]), "+f"(d[69]), "+f"(d[70]), "+f"(d[71]),
      "+f"(d[72]), "+f"(d[73]), "+f"(d[74]), "+f"(d[75]), "+f"(d[76]), "+f"(d[77]), "+f"(d[78]), "+f"(d[79]),
      "+f"(d[80]), "+f"(d[81]), "+f"(d[82]), "+f"(d[83]), "+f"(d[84]), "+f"(d[85]), "+f"(d[86]), "+f"(d[87]),
      "+f"(d[88]), "+f"(d[89]), "+f"(d[90]), "+f"(d[91]), "+f"(d[92]), "+f"(d[93]), "+f"(d[94]), "+f"(d[95])
    : "l"(da), "l"(db), "r"(scale_d));
}

__device__ __forceinline__ void wgmma_m64n128k16_ss_tb(float (&d)[64], uint64_t da, uint64_t db, int scale_d) {
  asm volatile("{\n.reg .pred p;\nsetp.ne.b32 p, %66, 0;\n"
    "wgmma.mma_async.sync.aligned.m64n128k16.f32.bf16.bf16 "
    "{%0, %1, %2, %3, %4, %5, %6, %7, %8, %9, %10, %11, %12, %13, %14, %15, "
    "%16, %17, %18, %19, %20, %21, %22, %23, %24, %25, %26, %27, %28, %29, %30, %31, "
    "%32, %33, %34, %35, %36, %37, %38, %39, %40, %41, %42, %43, %44, %45, %46, %47, "
    "%48, %49, %50, %51, %52, %53, %54, %55, %56, %57, %58, %59, %60, %61, %62, %63}, "
    "%64, %65, p, 1, 1, 0, 1;\n}\n"
    : "+f"(d[0]), "+f"(d[1]), "+f"(d[2]), "+f"(d[3]), "+f"(d[4]), "+f"(d[5]), "+f"(d[6]), "+f"(d[7]),
      "+f"(d[8]), "+f"(d[9]), "+f"(d[10]), "+f"(d[11]), "+f"(d[12]), "+f"(d[13]), "+f"(d[14]), "+f"(d[15]),
      "+f"(d[16]), "+f"(d[17]), "+f"(d[18]), "+f"(d[19]), "+f"(d[20]), "+f"(d[21]), "+f"(d[22]), "+f"(d[23]),
      "+f"(d[24]), "+f"(d[25]), "+f"(d[26]), "+f"(d[27]), "+f"(d[28]), "+f"(d[29]), "+f"(d[30]), "+f"(d[31]),
      "+f"(d[32]), "+f"(d[33]), "+f"(d[34]), "+f"(d[35]), "+f"(d[36]), "+f"(d[37]), "+f"(d[38]), "+f"(d[39]),
      "+f"(d[40]), "+f"(d[41]), "+f"(d[42]), "+f"(d[43]), "+f"(d[44]), "+f"(d[45]), "+f"(d[46]), "+f"(d[47]),
      "+f"(d[48]), "+f"(d[49]), "+f"(d[50]), "+f"(d[51]), "+f"(d[52]), "+f"(d[53]), "+f"(d[54]), "+f"(d[55]),
      "+f"(d[56]), "+f"(d[57]), "+f"(d[58]), "+f"(d[59]), "+f"(d[60]), "+f"(d[61]), "+f"(d[62]), "+f"(d[63])
    : "l"(da), "l"(db), "r"(scale_d));
}

__device__ __forceinline__ void wgmma_m64n32k16_rs_nb_h(float (&d)[16], uint32_t a0, uint32_t a1, uint32_t a2, uint32_t a3, uint64_t db, int scale_d) {
  asm volatile("{\n.reg .pred p;\nsetp.ne.b32 p, %21, 0;\n"
    "wgmma.mma_async.sync.aligned.m64n32k16.f32.f16.f16 "
    "{%0, %1, %2, %3, %4, %5, %6, %7, %8, %9, %10, %11, %12, %13, %14, %15}, "
    "{%16, %17, %18, %19}, %20, p, 1, 1, 0;\n}\n"
    : "+f"(d[0]), "+f"(d[1]), "+f"(d[2]), "+f"(d[3]), "+f"(d[4]), "+f"(d[5]), "+f"(d[6]), "+f"(d[7]),
      "+f"(d[8]), "+f"(d[9]), "+f"(d[10]), "+f"(d[11]), "+f"(d[12]), "+f"(d[13]), "+f"(d[14]), "+f"(d[15])
    : "r"(a0), "r"(a1), "r"(a2), "r"(a3), "l"(db), "r"(scale_d));
}

__device__ __forceinline__ void wgmma_m64n32k16_rs_nb_hh(uint32_t (&d)[8], uint32_t a0, uint32_t a1, uint32_t a2, uint32_t a3, uint64_t db, int scale_d) {
  asm volatile("{\n.reg .pred p;\nsetp.ne.b32 p, %13, 0;\n"
    "wgmma.mma_async.sync.aligned.m64n32k16.f16.f16.f16 "
    "{%0, %1, %2, %3, %4, %5, %6, %7}, "
    "{%8, %9, %10, %11}, %12, p, 1, 1, 0;\n}\n"
    : "+r"(d[0]), "+r"(d[1]), "+r"(d[2]), "+r"(d[3]), "+r"(d[4]), "+r"(d[5]), "+r"(d[6]), "+r"(d[7])
    : "r"(a0), "r"(a1), "r"(a2), "r"(a3), "l"(db), "r"(scale_d));
}

__device__ __forceinline__ void wgmma_m64n40k16_rs_tb(float (&d)[20], uint32_t a0, uint32_t a1, uint32_t a2, uint32_t a3, uint64_t db, int scale_d) {
  asm volatile("{\n.reg .pred p;\nsetp.ne.b32 p, %25, 0;\n"
    "wgmma.mma_async.sync.aligned.m64n40k16.f32.bf16.bf16 "
    "{%0, %1, %2, %3, %4, %5, %6, %7, %8, %9, %10, %11, %12, %13, %14, %15, "
    "%16, %17, %18, %19}, "
    "{%20, %21, %22, %23}, %24, p, 1, 1, 1;\n}\n"
    : "+f"(d[0]), "+f"(d[1]), "+f"(d[2]), "+f"(d[3]), "+f"(d[4]), "+f"(d[5]), "+f"(d[6]), "+f"(d[7]),
      "+f"(d[8]), "+f"(d[9]), "+f"(d[10]), "+f"(d[11]), "+f"(d[12]), "+f"(d[13]), "+f"(d[14]), "+f"(d[15]),
      "+f"(d[16]), "+f"(d[17]), "+f"(d[18]), "+f"(d[19])
    : "r"(a0), "r"(a1), "r"(a2), "r"(a3), "l"(db), "r"(scale_d));
}

__device__ __forceinline__ void wgmma_m64n40k16_rs_tb_z(float (&d)[20], uint32_t a0, uint32_t a1, uint32_t a2, uint32_t a3, uint64_t db, int scale_d) {
  asm volatile("{\n.reg .pred p;\nsetp.ne.b32 p, %25, 0;\n"
    "wgmma.mma_async.sync.aligned.m64n40k16.f32.bf16.bf16 "
    "{%0, %1, %2, %3, %4, %5, %6, %7, %8, %9, %10, %11, %12, %13, %14, %15, "
    "%16, %17, %18, %19}, "
    "{%20, %21, %22, %23}, %24, p, 1, 1, 1;\n}\n"
    : "=f"(d[0]), "=f"(d[1]), "=f"(d[2]), "=f"(d[3]), "=f"(d[4]), "=f"(d[5]), "=f"(d[6]), "=f"(d[7]),
      "=f"(d[8]), "=f"(d[9]), "=f"(d[10]), "=f"(d[11]), "=f"(d[12]), "=f"(d[13]), "=f"(d[14]), "=f"(d[15]),
      "=f"(d[16]), "=f"(d[17]), "=f"(d[18]), "=f"(d[19])
    : "r"(a0), "r"(a1), "r"(a2), "r"(a3), "l"(db), "r"(scale_d));
}

__device__ __forceinline__ void wgmma_m64n32k16_rs_nb_z_h(float (&d)[16], uint32_t a0, uint32_t a1, uint32_t a2, uint32_t a3, uint64_t db, int scale_d) {
  asm volatile("{\n.reg .pred p;\nsetp.ne.b32 p, %21, 0;\n"
    "wgmma.mma_async.sync.aligned.m64n32k16.f32.f16.f16 "
    "{%0, %1, %2, %3, %4, %5, %6, %7, %8, %9, %10, %11, %12, %13, %14, %15}, "
    "{%16, %17, %18, %19}, %20, p, 1, 1, 0;\n}\n"
    : "=f"(d[0]), "=f"(d[1]), "=f"(d[2]), "=f"(d[3]), "=f"(d[4]), "=f"(d[5]), "=f"(d[6]), "=f"(d[7]),
      "=f"(d[8]), "=f"(d[9]), "=f"(d[10]), "=f"(d[11]), "=f"(d[12]), "=f"(d[13]), "=f"(d[14]), "=f"(d[15])
    : "r"(a0), "r"(a1), "r"(a2), "r"(a3), "l"(db), "r"(scale_d));
}

__device__ __forceinline__ void wgmma_m64n32k16_rs_nb_z_hh(uint32_t (&d)[8], uint32_t a0, uint32_t a1, uint32_t a2, uint32_t a3, uint64_t db, int scale_d) {
  asm volatile("{\n.reg .pred p;\nsetp.ne.b32 p, %13, 0;\n"
    "wgmma.mma_async.sync.aligned.m64n32k16.f16.f16.f16 "
    "{%0, %1, %2, %3, %4, %5, %6, %7}, "
    "{%8, %9, %10, %11}, %12, p, 1, 1, 0;\n}\n"
    : "=r"(d[0]), "=r"(d[1]), "=r"(d[2]), "=r"(d[3]), "=r"(d[4]), "=r"(d[5]), "=r"(d[6]), "=r"(d[7])
    : "r"(a0), "r"(a1), "r"(a2), "r"(a3), "l"(db), "r"(scale_d));
}

#define DEVINL __device__ __forceinline__
DEVINL void wg_fence() { asm volatile("wgmma.fence.sync.aligned;" ::: "memory"); }
DEVINL void wg_commit() { asm volatile("wgmma.commit_group.sync.aligned;" ::: "memory"); }
template <int N> DEVINL void wg_wait() { asm volatile("wgmma.wait_group.sync.aligned %0;" ::"n"(N) : "memory"); }
DEVINL uint64_t mkdesc(uint32_t addr, uint32_t lbo, uint32_t sbo, int sw) {
  return (uint64_t)((addr & 0x3FFFF) >> 4) | ((uint64_t)(lbo >> 4) << 16) | ((uint64_t)(sbo >> 4) << 32) | ((uint64_t)sw << 62);
}
DEVINL void mbar_arrive(uint32_t bar) { asm volatile("mbarrier.arrive.shared::cta.b64 _, [%0];" ::"r"(bar) : "memory"); }
DEVINL void arrive_if_gt(uint32_t bar, uint32_t a, uint32_t b) {
  asm volatile("{\n.reg .pred p;\nsetp.gt.u32 p, %1, %2;\n@p mbarrier.arrive.shared::cta.b64 _, [%0];\n}" ::"r"(bar), "r"(a), "r"(b) : "memory");
}
DEVINL bool mbar_try(uint32_t bar, uint32_t parity) {
  uint32_t ok;
  asm volatile("{\n.reg .pred p;\nmbarrier.try_wait.parity.shared::cta.b64 p, [%1], %2;\nselp.u32 %0, 1, 0, p;\n}" : "=r"(ok) : "r"(bar), "r"(parity) : "memory");
  return ok;
}
DEVINL bool mbar_test(uint32_t bar, uint32_t parity) {
  uint32_t ok;
  asm volatile("{\n.reg .pred p;\nmbarrier.test_wait.parity.shared::cta.b64 p, [%1], %2;\nselp.u32 %0, 1, 0, p;\n}" : "=r"(ok) : "r"(bar), "r"(parity) : "memory");
  return ok;
}
DEVINL void mbar_hint(uint32_t bar, uint32_t parity) {
#pragma unroll 1
  for (uint32_t n = 0; n < 16u; n++) if (mbar_try(bar, parity)) break;
}
DEVINL void mbar_wait(uint32_t bar, uint32_t parity) {
#pragma unroll 1
  for (uint32_t n = 0; n < 100000u; n++) if (mbar_try(bar, parity)) break;
}
DEVINL void mbar_wait_long(uint32_t bar, uint32_t parity) {
#pragma unroll 1
  for (uint32_t n = 0; n < 100000u; n++) {
    uint32_t ok;
    asm volatile("{\n.reg .pred p;\nmbarrier.try_wait.parity.shared::cta.b64 p, [%1], %2, %3;\nselp.u32 %0, 1, 0, p;\n}" : "=r"(ok) : "r"(bar), "r"(parity), "r"(4000) : "memory");
    if (ok) break;
  }
}
#define EL(txt) "{\n.reg .pred pe;\nelect.sync _|pe, 0xffffffff;\n@pe " txt "\n}"
DEVINL void e_expect_tx(uint32_t bar, uint32_t bytes) { asm volatile(EL("mbarrier.arrive.expect_tx.shared::cta.b64 _, [%0], %1;") ::"r"(bar), "r"(bytes) : "memory"); }
DEVINL void e_init(uint32_t bar, uint32_t cnt) { asm volatile(EL("mbarrier.init.shared::cta.b64 [%0], %1;") ::"r"(bar), "r"(cnt) : "memory"); }
DEVINL void e_arrive(uint32_t bar) { asm volatile(EL("mbarrier.arrive.shared::cta.b64 _, [%0];") ::"r"(bar) : "memory"); }
DEVINL void e_red(uint32_t* p) { asm volatile(EL("red.release.gpu.global.add.u32 [%0], 1;") ::"l"(p) : "memory"); }
DEVINL void e_red_relaxed(uint32_t* p) { asm volatile(EL("red.relaxed.gpu.global.add.u32 [%0], 1;") ::"l"(p) : "memory"); }
DEVINL void tma_ld(uint32_t dst, const CUtensorMap* m, int c0, int c1, uint32_t bar) {
  asm volatile(EL("cp.async.bulk.tensor.2d.shared::cluster.global.mbarrier::complete_tx::bytes [%0], [%1, {%3, %4}], [%2];")
               ::"r"(dst), "l"(m), "r"(bar), "r"(c0), "r"(c1) : "memory");
}
DEVINL void tma_ld3(uint32_t dst, const CUtensorMap* m, int c0, int c1, int c2, uint32_t bar) {
  asm volatile(EL("cp.async.bulk.tensor.3d.shared::cluster.global.mbarrier::complete_tx::bytes [%0], [%1, {%3, %4, %5}], [%2];")
               ::"r"(dst), "l"(m), "r"(bar), "r"(c0), "r"(c1), "r"(c2) : "memory");
}
DEVINL void tma_ld5(uint32_t dst, const CUtensorMap* m, int c2, int c3, int c4, uint32_t bar) {
  asm volatile(EL("cp.async.bulk.tensor.5d.shared::cluster.global.mbarrier::complete_tx::bytes [%0], [%1, {0, 0, %3, %4, %5}], [%2];")
               ::"r"(dst), "l"(m), "r"(bar), "r"(c2), "r"(c3), "r"(c4) : "memory");
}
DEVINL void tma_ld_mc(uint32_t dst, const CUtensorMap* m, int c0, int c1, uint32_t bar) {
  asm volatile(EL("cp.async.bulk.tensor.2d.shared::cluster.global.mbarrier::complete_tx::bytes.multicast::cluster [%0], [%1, {%3, %4}], [%2], %5;")
               ::"r"(dst), "l"(m), "r"(bar), "r"(c0), "r"(c1), "h"((uint16_t)3) : "memory");
}
DEVINL void e_arrive_both(uint32_t bar) {
  asm volatile("{\n.reg .pred pe;\n.reg .b32 r0, r1;\nelect.sync _|pe, 0xffffffff;\nmapa.shared::cluster.u32 r0, %0, 0;\nmapa.shared::cluster.u32 r1, %0, 1;\n"
               "@pe mbarrier.arrive.shared::cluster.b64 _, [r0];\n@pe mbarrier.arrive.shared::cluster.b64 _, [r1];\n}" ::"r"(bar) : "memory");
}
DEVINL void push_peer(uint32_t dst, uint32_t src, uint32_t bar, uint32_t peer) {
  asm volatile("{\n.reg .pred pe;\n.reg .b32 d, b;\nelect.sync _|pe, 0xffffffff;\nmapa.shared::cluster.u32 d, %0, %3;\nmapa.shared::cluster.u32 b, %2, %3;\n"
               "@pe cp.async.bulk.shared::cluster.shared::cta.mbarrier::complete_tx::bytes [d], [%1], 16384, [b];\n}" ::"r"(dst), "r"(src), "r"(bar), "r"(peer) : "memory");
}
DEVINL void tma_st(const CUtensorMap* m, int c0, int c1, uint32_t src) {
  asm volatile(EL("cp.async.bulk.tensor.2d.global.shared::cta.bulk_group [%0, {%2, %3}], [%1];") ::"l"(m), "r"(src), "r"(c0), "r"(c1) : "memory");
}
DEVINL void bulk_commit() { asm volatile("cp.async.bulk.commit_group;" ::: "memory"); }
template <int N> DEVINL void bulk_wait_n() { asm volatile("cp.async.bulk.wait_group %0;\nbar.warp.sync 0xffffffff;" ::"n"(N) : "memory"); }
DEVINL void l2_prefetch(const void* g, uint32_t bytes) { asm volatile(EL("cp.async.bulk.prefetch.L2.global [%0], %1;") ::"l"(g), "r"(bytes) : "memory"); }
DEVINL void fence_async_smem() { asm volatile("fence.proxy.async.shared::cta;" ::: "memory"); }
DEVINL void fence_async_gl() { asm volatile("fence.proxy.async.global;" ::: "memory"); }
DEVINL void cluster_wait() { asm volatile("barrier.cluster.wait.aligned;" ::: "memory"); }
DEVINL void bar_sync(int id, int n) { asm volatile("bar.sync %0, %1;" ::"r"(id), "r"(n) : "memory"); }
DEVINL void bar_arrive(int id, int n) { asm volatile("bar.arrive %0, %1;" ::"r"(id), "r"(n) : "memory"); }
DEVINL uint32_t ld_acquire(const uint32_t* p) { uint32_t v; asm volatile("ld.acquire.gpu.global.u32 %0, [%1];" : "=r"(v) : "l"(p) : "memory"); return v; }
DEVINL void watch(const uint32_t* p, uint32_t target, uint32_t all, uint32_t tag, uint32_t slot) {
  uint32_t seen = 0;
#pragma unroll 1
  for (uint32_t n = 0; n < 200000u && seen != all; n++) {
    const uint32_t m = __ballot_sync(~0u, (int)(ld_acquire(p) - target) >= 0) & all;
    if (m != seen) { seen = m; asm volatile("st.release.cta.shared.u32 [%0], %1;" ::"r"(slot), "r"(tag << 16 | m) : "memory"); }
  }
}
template <bool RELAXED = false> DEVINL void await_bit(uint32_t slot, uint32_t tag, int j, uint32_t& rdy) {
  if ((rdy >> j) & 1) return;
#pragma unroll 1
  for (uint32_t n = 0; n < 8000000u; n++) {
    uint32_t v;
    asm volatile("ld.acquire.cta.shared.u32 %0, [%1];" : "=r"(v) : "r"(slot) : "memory");
    if ((v >> 16) == tag && ((v >> j) & 1)) { rdy = v; break; }
    if (RELAXED) __nanosleep(200);
  }
  asm volatile("fence.proxy.async.global;" ::: "memory");
}
DEVINL void poll_ge(const uint32_t* p, uint32_t target) {
#pragma unroll 1
  for (uint32_t n = 0; n < 200000u; n++) if (__all_sync(~0u, (int)(ld_acquire(p) - target) >= 0)) break;
}
DEVINL int lane_id() { int v; asm volatile("mov.u32 %0, %%laneid;" : "=r"(v)); return v; }
__host__ DEVINL int remap(int v) {
  const int c = v >> 1, u = c - 36, r = (u * 37) >> 8;
  const int L = max(c - 4 + max(r + 1, 0), (c - 4) >> 31 & (32 + 8 * c));
  return 2 * L + (v & 1);
}
DEVINL int block_id() { int v; asm volatile("mov.u32 %0, %%ctaid.x;" : "=r"(v)); return v; }
#define cta_id() prm.map[block_id()]
#define IDS() const int lane = lane_id(), b = cta_id(), bm = b >> 4, bn = b & 15, rank = b & 1, pm = 2 * bm + (bn >> 3), pn = bn & 7, po = pm & 1; \
  (void)lane; (void)bm; (void)bn; (void)rank; (void)pm; (void)pn; (void)po
DEVINL void st_tagged(unsigned long long* p, uint32_t v, uint32_t tag) {
  asm volatile("{\n.reg .b64 t;\nmov.b64 t, {%1, %2};\nst.relaxed.gpu.global.b64 [%0], t;\n}" ::"l"(p), "r"(v), "r"(tag) : "memory");
}
DEVINL float ex2(float x) { float y; asm("ex2.approx.ftz.f32 %0, %1;" : "=f"(y) : "f"(x)); return y; }
DEVINL float rcp(float x) { float y; asm("rcp.approx.ftz.f32 %0, %1;" : "=f"(y) : "f"(x)); return y; }
DEVINL uint32_t pack2(float lo, float hi) { uint32_t r; asm("cvt.rn.bf16x2.f32 %0, %1, %2;" : "=r"(r) : "f"(hi), "f"(lo)); return r; }
DEVINL float bf_lo(uint32_t w) { return __uint_as_float(w << 16); }
DEVINL float bf_hi(uint32_t w) { return __uint_as_float(w & 0xFFFF0000u); }
DEVINL float bf_round(float x) { return bf_lo(pack2(x, 0.f)); }
DEVINL uint32_t add_bf16x2(uint32_t a, uint32_t b) { uint32_t r; asm("add.rn.bf16x2 %0, %1, %2;" : "=r"(r) : "r"(a), "r"(b)); return r; }
DEVINL uint32_t max_bf2(uint32_t a, uint32_t b) { uint32_t r; asm("max.bf16x2 %0, %1, %2;" : "=r"(r) : "r"(a), "r"(b)); return r; }
DEVINL uint32_t scale_bf2(uint32_t a) {
  uint32_t r;
  asm("{\n.reg .b32 t;\nmul.rn.bf16x2 t, %1, %3;\nfma.rn.bf16x2 %0, %1, %2, t;\n}" : "=r"(r) : "r"(a), "r"(0x3E353E35u), "r"(0x379E379Eu));
  return r;
}
DEVINL void stsm4(uint32_t addr, uint32_t a, uint32_t b, uint32_t c, uint32_t d) {
  asm volatile("stmatrix.sync.aligned.m8n8.x4.shared.b16 [%0], {%1, %2, %3, %4};" ::"r"(addr), "r"(a), "r"(b), "r"(c), "r"(d) : "memory");
}
DEVINL void ldsm4(uint32_t addr, uint32_t (&r)[4]) {
  asm volatile("ldmatrix.sync.aligned.m8n8.x4.shared.b16 {%0, %1, %2, %3}, [%4];" : "=r"(r[0]), "=r"(r[1]), "=r"(r[2]), "=r"(r[3]) : "r"(addr) : "memory");
}
DEVINL void ldsm4t(uint32_t addr, uint32_t (&r)[4]) {
  asm volatile("ldmatrix.sync.aligned.m8n8.x4.trans.shared.b16 {%0, %1, %2, %3}, [%4];" : "=r"(r[0]), "=r"(r[1]), "=r"(r[2]), "=r"(r[3]) : "r"(addr) : "memory");
}
DEVINL void sts128(uint32_t addr, uint32_t a, uint32_t b, uint32_t c, uint32_t d) {
  asm volatile("st.shared.v4.b32 [%0], {%1, %2, %3, %4};" ::"r"(addr), "r"(a), "r"(b), "r"(c), "r"(d) : "memory");
}
DEVINL float4 lds128f(uint32_t addr) { float4 v; asm volatile("ld.shared.v4.f32 {%0, %1, %2, %3}, [%4];" : "=f"(v.x), "=f"(v.y), "=f"(v.z), "=f"(v.w) : "r"(addr) : "memory"); return v; }
DEVINL float lds32f(uint32_t addr) { float v; asm volatile("ld.shared.f32 %0, [%1];" : "=f"(v) : "r"(addr) : "memory"); return v; }
DEVINL void mma16816(float (&d)[4], uint32_t a0, uint32_t a1, uint32_t a2, uint32_t a3, uint32_t b0, uint32_t b1) {
  asm("mma.sync.aligned.m16n8k16.row.col.f32.bf16.bf16.f32 {%0, %1, %2, %3}, {%4, %5, %6, %7}, {%8, %9}, {%0, %1, %2, %3};"
               : "+f"(d[0]), "+f"(d[1]), "+f"(d[2]), "+f"(d[3]) : "r"(a0), "r"(a1), "r"(a2), "r"(a3), "r"(b0), "r"(b1));
}
DEVINL void mma1688(float (&d)[4], uint32_t a0, uint32_t a1, uint32_t b0) {
  asm("mma.sync.aligned.m16n8k8.row.col.f32.bf16.bf16.f32 {%0, %1, %2, %3}, {%4, %5}, {%6}, {%0, %1, %2, %3};"
               : "+f"(d[0]), "+f"(d[1]), "+f"(d[2]), "+f"(d[3]) : "r"(a0), "r"(a1), "r"(b0));
}
DEVINL void mma1688h(float (&d)[4], uint32_t a0, uint32_t a1, uint32_t b0) {
  asm("mma.sync.aligned.m16n8k8.row.col.f32.f16.f16.f32 {%0, %1, %2, %3}, {%4, %5}, {%6}, {%0, %1, %2, %3};"
               : "+f"(d[0]), "+f"(d[1]), "+f"(d[2]), "+f"(d[3]) : "r"(a0), "r"(a1), "r"(b0));
}
DEVINL void mma16816h(float (&d)[4], uint32_t a0, uint32_t a1, uint32_t a2, uint32_t a3, uint32_t b0, uint32_t b1) {
  asm("mma.sync.aligned.m16n8k16.row.col.f32.f16.f16.f32 {%0, %1, %2, %3}, {%4, %5, %6, %7}, {%8, %9}, {%0, %1, %2, %3};"
               : "+f"(d[0]), "+f"(d[1]), "+f"(d[2]), "+f"(d[3]) : "r"(a0), "r"(a1), "r"(a2), "r"(a3), "r"(b0), "r"(b1));
}
template <int N> DEVINL void fence_regs(uint32_t (&d)[N]) {
#pragma unroll
  for (int i = 0; i < N; i++) asm volatile("" : "+r"(d[i])::"memory");
}
template <int N> DEVINL void fence_regs(float (&d)[N]) {
#pragma unroll
  for (int i = 0; i < N; i++) asm volatile("" : "+f"(d[i])::"memory");
}

__device__ __align__(1024) bf16 g_xs[2048 * 1024];
__device__ __align__(1024) bf16 g_os[2048 * 1024];
__device__ __align__(1024) bf16 g_k[32 * 2048 * 32];
__device__ __align__(1024) bf16 g_v[32 * 2048 * 32];
__device__ __align__(128) float2 g_stats[8 * 2048];
__device__ __align__(16) float g_csp[2 * 16 * 8 * 192];
__device__ __align__(128) float g_kn[2 * 128 * 32];
__device__ unsigned long long g_halo[2 * 128 * 32 * 32];
__device__ __align__(128) uint32_t g_cnt[256 * 32];
__device__ uint32_t g_epoch;

DEVINL uint32_t* cnt_x(int l, int bm) { return g_cnt + (l * 8 + bm) * 32; }
DEVINL uint32_t* cnt_o(int l, int pm, int h) { return g_cnt + (32 + (l * 16 + pm) * 2 + h) * 32; }
DEVINL uint32_t* cnt_kv(int lb, int bn) { return g_cnt + (160 + lb * 16 + bn) * 32; }
DEVINL uint32_t* cnt_ad(int bn) { return g_cnt + (192 + bn) * 32; }
DEVINL uint32_t* cnt_cs(int t, int bn) { return g_cnt + (208 + t * 16 + bn) * 32; }

DEVINL int qord(int i, int l, int pn) { return l == 0 ? i : i < 4 ? ((2 * pn) ^ (i & 2)) + (i & 1) : i - 4 < 2 * (pn & 6) ? i - 4 : i; }
DEVINL int pord(int i, int l, int p) { return (l & 1) || i > p ? i : i ? i - 1 : p; }
struct Params {
  CUtensorMap m[17];
  const bf16* x0;
  const bf16* wq[2];
  const bf16* wo;
  uint32_t* epoch;
  uint32_t zero;
  int map[128];
};
enum { M_X0A = 0, M_XSA, M_WQA, M_WQB, M_WOA, M_WOB, M_OS, M_K, M_V, M_X0R, M_XSR, M_XSO, M_OUT, M_XST, M_X0H, M_K4, M_V4, M_COUNT };

constexpr uint32_t QSTG = 57344;
constexpr uint32_t T0 = 65536, TSTG = 32768;
constexpr uint32_t ONES = 229376;
constexpr uint32_t PSTG = 32768;
constexpr uint32_t ASC = 17408;
constexpr uint32_t RSTD = 229376, MEAN = 230400, COLS = 230912, KMAX = 231680, B_QD = 231688, B_OW = 231704, W_C = 231712, BARS = 232192, SMEM_BYTES = 232448;
constexpr uint32_t B_QF = BARS, B_QE = BARS + 32, B_TF = BARS + 64, B_TE = BARS + 96, B_PF = BARS + 128, B_PE = BARS + 176,
                   B_RF = BARS + 224, W_X = BARS + 232, W_O = BARS + 236, B_QL = BARS + 240, B_PA = BARS + 248;
enum { NB_ST = 1, NB_KV = 2  , NB_DONE = 3, NB_SC = 4, NB_SIG = 5  , NB_KN = 9  , NB_X = 11, NB_HALO = 12  , NB_X0 = 15 };

DEVINL uint32_t pslot_b(uint32_t s, int l) { return ((((l & 1) ? 0x32DC45u : 0x468795u) >> (4 * s)) & 15) * 16384u; }
DEVINL uint32_t pslot_a(uint32_t s, int l) { return ((((l & 1) ? 0xBA8796u : 0x32DCBAu) >> (4 * s)) & 15) * 16384u; }

constexpr float QSCALE = 0.17677669529663687f * 1.4426950408889634f;

DEVINL uint32_t hfma2(uint32_t a, uint32_t b, uint32_t c) { uint32_t r; asm("fma.rn.f16x2 %0, %1, %2, %3;" : "=r"(r) : "r"(a), "r"(b), "r"(c)); return r; }
DEVINL uint32_t pack2h(float lo, float hi) { uint32_t r; asm("cvt.rn.f16x2.f32 %0, %1, %2;" : "=r"(r) : "f"(hi), "f"(lo)); return r; }
DEVINL uint32_t h2_to_bf2(uint32_t h) {
  float a, b;
  asm("{\n.reg .b16 l, h;\nmov.b32 {l, h}, %2;\ncvt.f32.f16 %0, l;\ncvt.f32.f16 %1, h;\n}" : "=f"(a), "=f"(b) : "r"(h));
  return pack2(a, b);
}
DEVINL uint32_t exp2_h2(uint32_t s, uint32_t cc) {
  uint32_t r, v;
  asm("{\n.reg .b16 l, h;\n.reg .b32 t;\nmov.b32 {l, h}, %2;\nmov.b32 t, {l, l};\nfma.rn.f16x2 %0, %1, t, %3;\n}" : "=r"(r) : "r"(s), "r"(cc), "r"(0x007E007Eu));
  asm("{\n.reg .b16 l, h;\n.reg .b32 t;\nmov.b32 {l, h}, %2;\nmov.b32 t, {h, h};\nfma.rn.f16x2 %0, %1, t, %3;\n}" : "=r"(v) : "r"(r), "r"(cc), "r"(0x33FD33FDu));
  const uint32_t g = hfma2(v, 0x44004400u, s);
  return __funnelshift_l(r, r, 7) + hfma2(hfma2(g, g, 0x0DE10DE1u), g, 0x00300030u);
}
constexpr uint32_t NOT_F16 = 0x7FC00000u, K_LO = 0x35000000u  ;
DEVINL uint32_t f16_class(uint32_t norm2, uint32_t lo) { return norm2 - lo > 0x4E800000u - lo ? NOT_F16 : norm2; }

DEVINL void attn_slow(const uint32_t (&q)[8], float up, int head, const float* kn, float (&res)[20], int lane) {
  const int g = lane >> 2, qd = lane & 3;
  const bf16* kb = g_k + (size_t)head * 2048 * 32;
  const bf16* vb = g_v + (size_t)head * 2048 * 32;
  float o[4][4], m0 = -INFINITY, m1 = -INFINITY, l0 = 0.f, l1 = 0.f;
#pragma unroll
  for (int j = 0; j < 4; j++) { o[j][0] = o[j][1] = o[j][2] = o[j][3] = 0.f; }
#pragma unroll 1
  for (int k0 = 0; k0 < 2048; k0 += 16) {
    float s[2][4];
    const bool kh = __float_as_uint(__ldcg(kn + (k0 >> 8) * 32 + ((k0 >> 6) & 1) * 8 + ((k0 >> 7) & 1) * 4 + ((k0 >> 4) & 3))) != NOT_F16;
#pragma unroll
    for (int nt = 0; nt < 2; nt++) {
      s[nt][0] = s[nt][1] = s[nt][2] = s[nt][3] = 0.f;
      const uint32_t* kp = (const uint32_t*)(kb + (size_t)(k0 + nt * 8 + g) * 32) + qd;
      uint32_t kf[4];
#pragma unroll
      for (int i = 0; i < 4; i++) { kf[i] = __ldcg(kp + 4 * i); if (kh) kf[i] = h2_to_bf2(kf[i]); }
      mma16816(s[nt], q[0], q[1], q[2], q[3], kf[0], kf[1]);
      mma16816(s[nt], q[4], q[5], q[6], q[7], kf[2], kf[3]);
      s[nt][0] *= up; s[nt][1] *= up; s[nt][2] *= up; s[nt][3] *= up;
    }
    float a0 = fmaxf(fmaxf(s[0][0], s[0][1]), fmaxf(s[1][0], s[1][1]));
    float a1 = fmaxf(fmaxf(s[0][2], s[0][3]), fmaxf(s[1][2], s[1][3]));
    a0 = fmaxf(a0, __shfl_xor_sync(~0u, a0, 1)); a0 = fmaxf(a0, __shfl_xor_sync(~0u, a0, 2));
    a1 = fmaxf(a1, __shfl_xor_sync(~0u, a1, 1)); a1 = fmaxf(a1, __shfl_xor_sync(~0u, a1, 2));
    const float n0 = fmaxf(m0, a0), n1 = fmaxf(m1, a1);
    const float c0 = (m0 == n0) ? 1.f : ex2(m0 - n0), c1 = (m1 == n1) ? 1.f : ex2(m1 - n1);
    m0 = n0; m1 = n1;
    const uint32_t p0 = pack2(ex2(s[0][0] - n0), ex2(s[0][1] - n0)), p1 = pack2(ex2(s[0][2] - n1), ex2(s[0][3] - n1));
    const uint32_t p2 = pack2(ex2(s[1][0] - n0), ex2(s[1][1] - n0)), p3 = pack2(ex2(s[1][2] - n1), ex2(s[1][3] - n1));
    l0 = l0 * c0 + bf_lo(p0) + bf_hi(p0) + bf_lo(p2) + bf_hi(p2);
    l1 = l1 * c1 + bf_lo(p1) + bf_hi(p1) + bf_lo(p3) + bf_hi(p3);
#pragma unroll
    for (int j = 0; j < 4; j++) {
      o[j][0] *= c0; o[j][1] *= c0; o[j][2] *= c1; o[j][3] *= c1;
      const unsigned short* vp = (const unsigned short*)(vb + (size_t)(k0 + 2 * qd) * 32 + j * 8 + g);
      const uint32_t b0 = (uint32_t)__ldcg(vp) | ((uint32_t)__ldcg(vp + 32) << 16);
      const uint32_t b1 = (uint32_t)__ldcg(vp + 256) | ((uint32_t)__ldcg(vp + 288) << 16);
      mma16816(o[j], p0, p1, p2, p3, b0, b1);
    }
  }
  l0 += __shfl_xor_sync(~0u, l0, 1); l0 += __shfl_xor_sync(~0u, l0, 2);
  l1 += __shfl_xor_sync(~0u, l1, 1); l1 += __shfl_xor_sync(~0u, l1, 2);
#pragma unroll
  for (int j = 0; j < 4; j++) { res[4 * j] = o[j][0]; res[4 * j + 1] = o[j][1]; res[4 * j + 2] = o[j][2]; res[4 * j + 3] = o[j][3]; }
  res[16] = l0; res[18] = l1;
}

__global__ void __cluster_dims__(2, 1, 1) __launch_bounds__(384, 1) fused_kernel(const __grid_constant__ Params prm) {
  extern __shared__ __align__(1024) char smem[];
  const uint32_t sb = (uint32_t)__cvta_generic_to_shared(smem);
  const int tid = threadIdx.x;
  const int wid = __shfl_sync(0xffffffffu, tid >> 5, 0), wg = wid >> 2, w = wid & 3;
  const int bm = remap(blockIdx.x) >> 4, bn = remap(blockIdx.x) & 15;
  auto first_tile = [&](int kt) {
    e_expect_tx(sb + B_QF + 8 * kt, QSTG);
    tma_ld(sb + kt * QSTG, &prm.m[M_X0A], kt * 64, bm * 256, sb + B_QF + 8 * kt);
    tma_ld3(sb + kt * QSTG + 32768, &prm.m[M_WQA], bn * 64, kt * 64, 0, sb + B_QF + 8 * kt);
  };
  if (wid == 8) {
    e_init(sb + B_QF, 1);
    asm volatile("fence.mbarrier_init.release.cluster;" ::: "memory");
    first_tile(0);
  }
  if (wid < 8) {
#pragma unroll
    for (int i = 0; i < 4; i++) {
      const uint32_t cnt = (uint32_t)((i == 0 ? 0x14112140 : i == 1 ? 0x04112141 : i == 2 ? 0x14412141 : 0x24412141) >> (4 * wid)) & 7;
      if (cnt) e_init(sb + BARS + 32 * wid + 8 * i, cnt);
    }
    if (wid < 3) e_init(sb + B_QD + wid * 8, wid < 2 ? 1 : 2);
    if (tid == 255) { *(uint2*)(smem + W_X) = make_uint2(0u, 0u); *(uint2*)(smem + W_C) = make_uint2(0xF8000080u, 0xF8000080u); }
    asm volatile("fence.mbarrier_init.release.cluster;" ::: "memory");
  }
  const uint32_t epoch = *(volatile uint32_t*)prm.epoch;
  __syncthreads();
  asm volatile("barrier.cluster.arrive.relaxed.aligned;" ::: "memory");

  if (wg == 2) {
    asm volatile("setmaxnreg.dec.sync.aligned.u32 56;");
    const uint32_t ep1 = epoch + 1;
    if (w == 0) {
      first_tile(1);
      mbar_wait(sb + B_QF, 0);
      first_tile(2); first_tile(3);
#pragma unroll 1
      for (int kt = 4; kt < 9; kt++) l2_prefetch(prm.wq[0] + kt * 196608 + blockIdx.x * 1536, 3072);
      cluster_wait();
#pragma unroll 1
      for (int l = 0; l < 4; l++) {
        IDS();
        const CUtensorMap* mw = &prm.m[M_WQA + (l & 1)];
        const CUtensorMap* mh = &prm.m[l == 0 ? M_X0H : M_XSO];
        const CUtensorMap* mo = &prm.m[M_WOA + (l & 1)];
        auto q_b = [&](int i) {
          const int s = i & 3;
          mbar_wait(sb + B_QE + 8 * s, ((i >> 2) & 1) ^ 1);
          e_expect_tx(sb + B_QF + 8 * s, QSTG);
          tma_ld3(sb + s * QSTG + 32768, mw, bn * 64, qord(i, l, pn) * 64, 0, sb + B_QF + 8 * s);
        };
        uint32_t rdy = l ? 0u : ~0u;
        auto q_a = [&](int i) {
          const int kt = qord(i, l, pn);
          await_bit(sb + W_X, l, kt >> 1, rdy);
          tma_ld_mc(sb + (i & 3) * QSTG + rank * 16384, mh, kt * 64, bm * 256 + rank * 128, sb + B_QF + 8 * (i & 3));
        };
        if (l > 0) {
#pragma unroll 1
          for (int i = 0; i < 4; i++) {
            const int kt = qord(i, l, pn);
            await_bit(sb + W_X, l, kt >> 1, rdy);
            if (i == 1 || i == 2) mbar_wait(sb + B_QF + 8 * (i - 1), 0);
            e_expect_tx(sb + B_QF + 8 * i, 16384);
            tma_ld(sb + i * QSTG + (po ^ 1) * 16384, &prm.m[M_XSO], kt * 64, (pm ^ 1) * 128, sb + B_QF + 8 * i);
          }
        }
#pragma unroll 1
        for (int i = 4; i < 16; i++) {
          q_b(i); q_a(i);
          if (l == 0 && i < 11) l2_prefetch(prm.wq[0] + (i + 5) * 196608 + blockIdx.x * 1536, 3072);
          if (l == 0 && i == 15) l2_prefetch(prm.wo + blockIdx.x * 8192, 16384);
        }
        if (l & 1) {
          if (l == 3) poll_ge(cnt_ad(bn), ep1 * 16);
          const int krow = 2 * bn * 2048 + bm * 256;
          uint32_t* kvc = cnt_kv(l >> 1, bn);
#pragma unroll 1
          for (int m = 1; m >= 0; m--) {
            bar_sync(m ? NB_ST : NB_KV, 288);
#pragma unroll
            for (int i = 0; i < 4; i++) tma_st(&prm.m[M_K4 + (i >> 1)], 0, krow + (i & 1) * 128 + m * 64, sb + T0 + i * 8192 + m * 4096);
            if (m) {
              sts128(sb + ONES + lane * 32, 0x3f803f80u, 0x3f803f80u, 0x3f803f80u, 0x3f803f80u);
              sts128(sb + ONES + lane * 32 + 16, 0x3f803f80u, 0x3f803f80u, 0x3f803f80u, 0x3f803f80u);
              fence_async_smem();
              __syncwarp();
            }
          }
          e_arrive(sb + B_TF);
          bulk_commit(); bulk_wait_n<0>();
          e_red(kvc + bm);
          bar_sync(NB_KV + 12, 288);
          uint32_t seen = 0;
#pragma unroll 1
          for (int it = 1; it < 16; it++) {
            const int s = it & 3, blk = it;
            if (it == 4) { tma_st(&prm.m[M_K], 0, krow + 2048, sb); tma_st(&prm.m[M_V], 0, krow + 2048, sb + 16384); bulk_commit(); }
            if (it == 5) { bulk_wait_n<0>(); e_red(kvc + bm); }
            if (it == 12) { e_expect_tx(sb + B_RF, 32768); tma_ld3(sb, &prm.m[M_XSR], 0, pm * 128, 2 * pn, sb + B_RF); }
            if (it == 2 || it == 3) mbar_wait(sb + B_TF + 8 * (it - 1), 0);
            mbar_wait_long(sb + B_TE + 8 * s, ((it >> 2) & 1) ^ 1);
            if (it < 8) {
#pragma unroll 1
              for (uint32_t n = 0; n < 200000u && !((seen >> it) & 1); n++)
                seen = __ballot_sync(~0u, (int)(ld_acquire(kvc + ((bm + lane) & 7)) - (ep1 * 2 - 1)) >= 0);
              fence_async_gl();
            } else if (it == 8) { poll_ge(kvc + (lane & 7), ep1 * 2); fence_async_gl(); bar_arrive(NB_HALO, 64); }
            else if (it == 15) bar_arrive(NB_HALO + 1, 64);
            const int row = (2 * bn + (it >> 3)) * 2048 + ((bm + blk) & 7) * 256;
            e_expect_tx(sb + B_TF + 8 * s, 32768);
            tma_ld(sb + T0 + s * TSTG, &prm.m[M_K], 0, row, sb + B_TF + 8 * s);
            tma_ld(sb + T0 + s * TSTG + 16384, &prm.m[M_V], 0, row, sb + B_TF + 8 * s);
          }
        }
        auto p_b = [&](int i, uint32_t s, uint32_t par) {
          const int kt = pord(i, l, bn >> 1);
          mbar_wait(sb + B_PE + 8 * s, par ^ 1);
          e_expect_tx(sb + B_PF + 8 * s, PSTG);
          tma_ld5(sb + pslot_b(s, l), mo, kt >> 3, 2 * (kt & 7), 2 * pn, sb + B_PF + 8 * s);
        };
        auto p_a = [&](int i, uint32_t s) {
          const int kt = pord(i, l, bn >> 1);
          await_bit(sb + W_O, l + 1, kt, rdy);
          tma_ld_mc(sb + pslot_a(s, l) + rank * 8192, &prm.m[M_OS], kt * 64, pm * 128 + rank * 64, sb + B_PF + 8 * s);
        };
        auto p_a2 = [&](int i) {
          const int kt = pord(i, l, bn >> 1);
          await_bit(sb + W_O, l + 1, kt, rdy);
          tma_ld(sb + pslot_a(i, l), &prm.m[M_OS], kt * 64, pm * 128, sb + B_PF + 8 * i);
          tma_ld(sb + pslot_a(i, l) + 8192, &prm.m[M_OS], kt * 64, pm * 128 + 64, sb + B_PF + 8 * i);
        };
        rdy = 0;
        if (l & 1) {
#pragma unroll 1
          for (int u = 0; u < 6; u++) { const int i = (0x105432 >> (4 * u)) & 7; if (u == 4) mbar_wait_long(sb + B_TE, 1); p_b(i, i, i < 4 ? 1 : 0); }
#pragma unroll 1
          for (int u = 0; u < 6; u++) {
            const int i = (0x543120 >> (4 * u)) & 7;
            if (!(u & 1)) mbar_wait_long(sb + B_TE + 8 + 4 * u, 1);
            p_a2(i);
          }
        } else {
#pragma unroll 1
          for (int u = 0; u < 5; u++) { const int i = (0x32140 >> (4 * u)) & 7; if (!(u & 5)) mbar_wait(sb + B_QE + 8 + 4 * u, 1); p_b(i, i, 0); }
          mbar_wait(sb + B_QE + 24, 1);
          mbar_wait(sb + B_OW, (l >> 1) & 1);
          fence_async_gl();
          rdy = 1u << (bn >> 1);
#pragma unroll 1
          for (int i = 0; i < 4; i++) { p_a(i, i); }
          bar_sync(NB_DONE, 96);
          e_arrive_both(sb + B_PA);
          p_b(5, 5, 0);
          mbar_wait(sb + B_PA, (l >> 1) & 1);
          p_a(4, 4); p_a(5, 5);
        }
        uint32_t s = 0, lap = 1;
#pragma unroll 1
        for (int i = 6; i < 16; i++) {
          if (i == 15 && !(l & 1)) { e_expect_tx(sb + B_RF, 32768); tma_ld3(sb, &prm.m[l == 0 ? M_X0R : M_XSR], 0, pm * 128, 2 * pn, sb + B_RF); }
          p_b(i, s, ((s < 4 ? l : 0) + lap) & 1);
          p_a(i, s);
          if (++s == 6) { s = 0; lap++; }
        }
        const CUtensorMap* mn = &prm.m[M_WQA + ((l + 1) & 1)];
        if (l < 3) {
          mbar_wait(sb + B_PE + 8 * 4, 1); mbar_wait(sb + B_PE + 8 * 5, 1);
          tma_ld3(sb + 32768, mn, bn * 64, 2 * pn * 64, 0, sb + B_QL);
          mbar_wait(sb + B_PE + 8 * 0, l & 1);
          tma_ld3(sb + QSTG + 32768, mn, bn * 64, (2 * pn + 1) * 64, 0, sb + B_QL);
          mbar_wait(sb + B_PE + 8 * 1, l & 1);
          e_expect_tx(sb + B_QD, 40960);
          tma_ld3(sb + 2 * QSTG + 32768, mn, bn * 64, ((2 * pn) ^ 2) * 64, 0, sb + B_QD);
          bar_sync(NB_X, 288);
          e_expect_tx(sb + B_QL, 49152);
          e_expect_tx(sb + B_QD + 8, 40960);
          tma_ld3(sb + 3 * QSTG + 32768, mn, bn * 64, (((2 * pn) ^ 2) + 1) * 64, 0, sb + B_QD + 8);
        }
      }
      if (blockIdx.x == 0 && lane_id() == 0) *(volatile uint32_t*)prm.epoch = ep1;
    } else {
      const int hw = w - 1;
      if (hw == 1 && lane_id() < M_COUNT) asm volatile("prefetch.tensormap [%0];" ::"l"(&prm.m[lane_id()]) : "memory");
      cluster_wait();
      mbar_wait(sb + B_QF, 0);
#pragma unroll 1
      for (int l = 0; l < 4; l++) {
        IDS();
        if (hw == 2 && l > 0) watch(cnt_x(l, bm) + (lane & 7), ep1 * 2, 0xFFu, l, sb + W_X);
        if (l == 0) {
#pragma unroll 1
          for (int r = 2 * hw; r < 16; r += 6) {
            const uint4* p = (const uint4*)(prm.x0 + (size_t)(b * 16 + r) * 1024) + lane;
            float s1[2] = {0.f, 0.f}, s2[2] = {0.f, 0.f};
#pragma unroll
            for (int i = 0; i < 8; i++) {
              const uint4 v = __ldg(p + 32 * i);
              const uint32_t u[4] = {v.x, v.y, v.z, v.w};
#pragma unroll
              for (int k = 0; k < 4; k++) { const float a = bf_lo(u[k]), c = bf_hi(u[k]); s1[i >> 2] += a + c; s2[i >> 2] = fmaf(a, a, fmaf(c, c, s2[i >> 2])); }
            }
#pragma unroll
            for (int o = 16; o; o >>= 1)
#pragma unroll
              for (int rr = 0; rr < 2; rr++) { s1[rr] += __shfl_xor_sync(~0u, s1[rr], o); s2[rr] += __shfl_xor_sync(~0u, s2[rr], o); }
            if (lane == 0) *(float4*)&g_stats[b * 16 + r] = make_float4(s1[0], s2[0], s1[1], s2[1]);
          }
        }
        if (l == 1) { uint32_t rdy = 0; await_bit<true>(sb + W_X, 1, pn, rdy); mbar_hint(sb + B_QF + 24, 0); }
        if (l < 2) {
          float cs[8];
#pragma unroll
          for (int i = 0; i < 8; i++) cs[i] = 0.f;
          const uint4* wp = (const uint4*)(prm.wq[l] + (size_t)(bm * 128 + (lane >> 3)) * 3072 + hw * 1024 + bn * 64) + (lane & 7);
#pragma unroll 8
          for (int i = 0; i < 32; i++) {
            const uint4 v = __ldg(wp + (size_t)i * 4 * 384);
            cs[0] += bf_lo(v.x); cs[1] += bf_hi(v.x); cs[2] += bf_lo(v.y); cs[3] += bf_hi(v.y);
            cs[4] += bf_lo(v.z); cs[5] += bf_hi(v.z); cs[6] += bf_lo(v.w); cs[7] += bf_hi(v.w);
          }
#pragma unroll
          for (int i = 0; i < 8; i++) { cs[i] += __shfl_xor_sync(~0u, cs[i], 8); cs[i] += __shfl_xor_sync(~0u, cs[i], 16); }
          if (lane < 8) {
            float4* d = (float4*)(g_csp + ((l * 16 + bn) * 8 + bm) * 192 + hw * 64 + lane * 8);
            d[0] = make_float4(cs[0], cs[1], cs[2], cs[3]); d[1] = make_float4(cs[4], cs[5], cs[6], cs[7]);
          }
          __syncwarp();
          asm volatile("fence.acq_rel.gpu;" ::: "memory");
          e_red_relaxed(cnt_cs(l, bn));
          if (l == 0) e_red_relaxed(cnt_x(0, bm) + pn);
          poll_ge(lane < 8 && l == 0 ? cnt_x(0, bm) + lane : cnt_cs(l, bn), ep1 * (lane < 8 && l == 0 ? 6 : 24));
        }
        if (l > 0) {
          uint32_t rdy = 0;
#pragma unroll 1
          for (int j = 0; j < 8; j++) await_bit<true>(sb + W_X, l, j, rdy);
        }
#pragma unroll 1
        for (int it = hw * 32 + lane; it < 176; it += 96) {
          const bool rows = it < 128;
          const float4* p = rows ? (const float4*)(g_stats + bm * 256) + it : (const float4*)(g_csp + ((l & 1) * 16 + bn) * 8 * 192) + (it - 128);
          const int stride = rows ? 1024 : 48, np = rows && l == 0 ? 1 : 8;
          float4 a = make_float4(0.f, 0.f, 0.f, 0.f);
#pragma unroll
          for (int k = 0; k < 8; k++) if (k < np) { const float4 v = __ldcg(p + k * stride); a.x += v.x; a.y += v.y; a.z += v.z; a.w += v.w; }
          if (rows) {
            const float m0 = a.x * (1.f / 1024.f), m1 = a.z * (1.f / 1024.f);
            const float v0 = fmaxf(a.y * (1.f / 1024.f) - m0 * m0, 0.f), v1 = fmaxf(a.w * (1.f / 1024.f) - m1 * m1, 0.f);
            const float r0 = __fdividef(1.f, bf_round(sqrtf(bf_round(bf_round(v0) + 1e-5f)))), r1 = __fdividef(1.f, bf_round(sqrtf(bf_round(bf_round(v1) + 1e-5f))));
            *(float2*)(smem + RSTD + it * 8) = make_float2(r0, r1);
            *(uint32_t*)(smem + MEAN + it * 4) = pack2(-m0, -m1);
          } else {
            float2* d = (float2*)(smem + COLS) + ((it - 128) >> 2) * 8 + (it & 1) * 4 + ((it >> 1) & 1);
            d[0] = make_float2(a.y, a.x); d[2] = make_float2(a.w, a.z);
          }
        }
        __syncwarp();
        if (lane == 0) asm volatile("red.release.cta.shared.add.u32 [%0], 0x100;" ::"r"(sb + W_X) : "memory");
        if (hw == 2) {
          if (!(l & 1)) {
            bar_sync(NB_ST, 288);
            const volatile unsigned long long* hp = g_halo + ((size_t)(l >> 1) * 128 + b - 16) * 1024 + lane;
#pragma unroll 1
            for (int h = 0; h < 2; h++) {
              uint32_t t[16];
#pragma unroll
              for (int i = 0; i < 16; i++) t[i] = 0;
#pragma unroll 1
              for (uint32_t n = bm ? 0 : 100000u; n < 100000u; n++) {
                uint32_t miss = 0;
#pragma unroll
                for (int i = 0; i < 16; i++) {
                  const unsigned long long v = hp[h * 512 + i * 32];
                  t[i] = (uint32_t)v; miss |= (uint32_t)(v >> 32) ^ ep1;
                }
                if (__all_sync(~0u, !miss)) break;
              }
              const uint32_t r = (lane & 7) + ((lane >> 3) & 1) * 8, rv = lane >> 2;
#pragma unroll
              for (int jj = 0; jj < 2; jj++) stsm4(sb + 2 * h * ASC + r * 64 + (((2 * jj + (lane >> 4)) ^ ((r >> 1) & 3)) << 4), t[4 * jj], t[4 * jj + 1], t[4 * jj + 2], t[4 * jj + 3]);
              const uint32_t ad = sb + (2 * h + 1) * ASC + rv * 64 + (((lane & 3) ^ ((rv >> 1) & 3)) << 4);
              sts128(ad, t[8], t[10], t[12], t[14]); sts128(ad + 512, t[9], t[11], t[13], t[15]);
              bar_arrive(NB_HALO + h, 64);
            }
          } else {
            bar_sync(NB_HALO, 64);
            const uint4* kp = (const uint4*)(g_kn + ((l >> 1) * 128 + bn * 8) * 32) + 2 * lane;
            const uint4 v = __ldcg(kp), u = __ldcg(kp + 1);
            const uint32_t mx = max(max(max(v.x, v.y), max(v.z, v.w)), max(max(u.x, u.y), max(u.z, u.w)));
            const uint32_t m0 = __reduce_max_sync(~0u, (lane & 2) ? 0u : mx), m1 = __reduce_max_sync(~0u, (lane & 2) ? mx : 0u);
            if (lane == 0) *(uint2*)(smem + KMAX) = make_uint2(m0, m1);
            __syncwarp();
            bar_arrive(NB_KN, 160); bar_arrive(NB_KN + 1, 160);
            bar_sync(NB_HALO + 1, 64);
            watch(cnt_o(l, pm, 0) + (lane & 7), ep1 * 2, 0xFFu, l + 1, sb + W_O);
          }
        } else {
          bar_sync(NB_SIG + 2 * hw, 160); bar_sync(NB_SIG + 2 * hw + 1, 160);
          if (!(l & 1)) bar_arrive(NB_DONE, 96);
          if (hw == (l & 1)) bar_arrive((l & 1) ? NB_DONE : NB_KN, 64);
          asm volatile("fence.acq_rel.gpu;" ::: "memory");
          e_red_relaxed(cnt_o(l, 2 * bm, hw) + (bn >> 1));
          e_red_relaxed(cnt_o(l, 2 * bm + 1, hw) + (bn >> 1));
          if (hw == 0 && !(l & 1)) e_arrive_both(sb + B_OW);
          if (hw == 1 && l == 1) { e_red_relaxed(cnt_ad(bn)); e_red_relaxed(cnt_ad(bn)); }
        }
        if (hw == 2) { bar_sync((l & 1) ? NB_DONE : NB_KN, 64); watch(cnt_o(l, pm, (lane >> 3) & 1) + (lane & 7), ep1 * 2, 0xFFFFu, l + 1, sb + W_O); }
        if (l < 3) {
          bar_sync(NB_X0, 352);
          if (hw == 0) {
            e_red(cnt_x(l + 1, bm) + pn);
          } else if (hw == 1) {
            mbar_wait(sb + B_PE + 8 * 3, l & 1);
            push_peer(sb + 2 * QSTG + po * 16384, sb + po * 16384, sb + B_QD, rank ^ 1);
            push_peer(sb + 3 * QSTG + po * 16384, sb + QSTG + po * 16384, sb + B_QD + 8, rank ^ 1);
          }
        }
      }
    }
  } else {
    asm volatile("setmaxnreg.inc.sync.aligned.u32 224;");
    const uint32_t zero = prm.zero;
    cluster_wait();
    const uint32_t ep1 = __shfl_sync(~0u, epoch + 1, 0);
#pragma unroll 1
    for (int l = 0; l < 4; l++) {
      {
        float acc[2][96];
#pragma unroll
        for (int i = 0; i < 96; i++) { acc[0][i] = 0.f; acc[1][i] = 0.f; }
        fence_regs(acc[0]); fence_regs(acc[1]);
        const bool early = l > 0 && wg == ((cta_id() >> 3) & 1);
        uint32_t a_lo = (uint32_t)mkdesc(sb + wg * 16384, 16, 0, 0), b_lo = (uint32_t)mkdesc(sb + 32768, 8192, 0, 0);
#pragma unroll 1
        for (int kt = 0; kt < 14; kt++) {
          const int s = kt & 3;
          if (l > 0 && kt < 4 && kt != 1) mbar_wait(sb + (kt ? B_QD - 16 + 8 * kt : B_QL), (l + 1) & 1);
          if (!(early && kt < 4)) mbar_wait(sb + B_QF + 8 * s, (kt >> 2) & 1);
          const uint64_t da = mkdesc(0, 0, 1024, 1) | a_lo, db = mkdesc(0, 0, 1024, 1) | b_lo;
          wg_fence();
#pragma unroll
          for (int k = 0; k < 4; k++)
#pragma unroll
            for (int m = 0; m < 2; m++) wgmma_m64n192k16_ss_tb(acc[m], da + m * 512 + k * 2, db + k * 128, 1);
          wg_commit();
          { const uint32_t d = s == 3 ? 0u - 3 * (QSTG / 16) : QSTG / 16; a_lo += d; b_lo += d; }
          wg_wait<1>();
          if (early && kt < 5) {
#pragma unroll 1
            for (int i = kt == 3 ? 0 : 3; i < kt; i++) { mbar_wait(sb + B_QF + 8 * i, 0); if (w == 0) e_arrive_both(sb + B_QE + 8 * i); }
          } else if (kt > 0 && w == 0) e_arrive_both(sb + B_QE + 8 * ((kt - 1) & 3));
          if (kt == 13 - 2 * wg) {
#pragma unroll 1
            for (uint32_t n = 0; n < 4000000u; n++) {
              uint32_t v;
              asm volatile("ld.acquire.cta.shared.u32 %0, [%1];" : "=r"(v) : "r"(sb + W_X) : "memory");
              if ((v >> 8) == (uint32_t)(l * 256 + 3)) break;
            }
            const int lane = lane_id();
            float nm[4];
#pragma unroll
            for (int i = 0; i < 4; i++) nm[i] = bf_lo(*(volatile unsigned short*)(smem + MEAN + (wg * 128 + w * 16 + (lane >> 2) + (i >> 1) * 64 + (i & 1) * 8) * 2));
            wg_wait<0>();
            fence_regs(acc[0]); fence_regs(acc[1]);
#pragma unroll
            for (int j = 0; j < 12; j++) {
              const float4 c = lds128f(sb + COLS + j * 64 + (lane & 3) * 16);
#pragma unroll
              for (int m = 0; m < 2; m++) {
                float* a = &acc[m][8 * j];
                a[0] = fmaf(nm[2 * m], c.y, a[0]); a[1] = fmaf(nm[2 * m], c.x, a[1]); a[2] = fmaf(nm[2 * m + 1], c.y, a[2]); a[3] = fmaf(nm[2 * m + 1], c.x, a[3]);
                a[4] = fmaf(nm[2 * m], c.w, a[4]); a[5] = fmaf(nm[2 * m], c.z, a[5]); a[6] = fmaf(nm[2 * m + 1], c.w, a[6]); a[7] = fmaf(nm[2 * m + 1], c.z, a[7]);
              }
            }
            fence_regs(acc[0]); fence_regs(acc[1]);
          }
        }
        auto part = [&](int s, int m, int k0, int k1) {
          const uint64_t da = mkdesc(sb + s * QSTG + wg * 16384 + m * 8192, 16, 1024, 1), db = mkdesc(sb + s * QSTG + 32768, 8192, 1024, 1);
          wg_fence();
#pragma unroll
          for (int k = k0; k < k1; k++) wgmma_m64n192k16_ss_tb(acc[m], da + k * 2, db + k * 128, 1);
          wg_commit();
        };
        mbar_wait(sb + B_QF + 16, 1);
        part(2, 1, 0, 4);
        wg_wait<1>();
        if (w == 0) e_arrive_both(sb + B_QE + 8);
        if (!(l & 1)) bar_arrive(NB_ST, 288);
        mbar_wait(sb + B_QF + 24, 1);
        part(3, 1, 0, 4);
        part(2, 0, 0, 2);
        IDS();
        const int g = lane >> 2, qd = lane & 3;
        float rs[2][2];
#pragma unroll
        for (int i = 0; i < 4; i++) rs[i >> 1][i & 1] = lds32f(sb + RSTD + (wg * 128 + w * 16 + g + (i >> 1) * 64 + (i & 1) * 8) * 4);
        auto scale = [&](int gi, int m, float sc) {
          const float r0 = rs[m][0] * sc, r1 = rs[m][1] * sc;
#pragma unroll
          for (int i = 0; i < 16; i++) acc[m][16 * gi + i] *= (i & 2) ? r1 : r0;
        };
        auto pack_b = [&](int gi, int m, uint32_t (&t)[8]) {
#pragma unroll
          for (int i = 0; i < 8; i++) t[i] = pack2(acc[m][16 * gi + 2 * i], acc[m][16 * gi + 2 * i + 1]);
        };
        auto norm_tile = [&](int gi, int m, uint32_t (&t)[8]) { scale(gi, m, 1.f); pack_b(gi, m, t); };
        auto pack_h = [&](int gi, int m, uint32_t (&t)[8]) {
#pragma unroll
          for (int i = 0; i < 8; i++) t[i] = pack2h(acc[m][16 * gi + 2 * i], acc[m][16 * gi + 2 * i + 1]);
        };
        uint32_t q[2][2][8], qn[2][2];
        const uint32_t srow = (lane & 7) + ((lane >> 3) & 1) * 8;
        const uint32_t row0 = wg * 128 + w * 16;
        auto put_kv = [&](int h, int v, int m, const uint32_t (&t)[8]) {
          const uint32_t base = sb + ((l & 1) ? (h ? 0 : T0) + v * 16384 : (2 * h + v) * ASC + 1024) + (row0 + m * 64) * 64;
          if (!v) {
#pragma unroll
            for (int jj = 0; jj < 2; jj++) stsm4(base + srow * 64 + (((2 * jj + (lane >> 4)) ^ ((srow >> 1) & 3)) << 4), t[4 * jj], t[4 * jj + 1], t[4 * jj + 2], t[4 * jj + 3]);
          } else {
            const uint32_t ad = base + g * 64 + ((qd ^ (g >> 1)) << 4);
            sts128(ad, t[0], t[2], t[4], t[6]); sts128(ad + 512, t[1], t[3], t[5], t[7]);
          }
        };
        auto send_halo = [&](int h, int v, const uint32_t (&t)[8]) {
          unsigned long long* hp = g_halo + ((size_t)(l >> 1) * 128 + b) * 1024 + h * 512 + v * 256 + lane;
#pragma unroll
          for (int i = 0; i < 8; i++) st_tagged(hp + i * 32, t[i], ep1);
        };
        auto put_kn = [&](int h, int m, uint32_t kn) {
          g_kn[((l >> 1) * 128 + bn * 8 + bm) * 32 + 16 * h + 8 * m + wg * 4 + w] = __uint_as_float(kn);
        };
        auto conv_tile1 = [&](int h) {
          uint32_t t[8], tv[8], kn = NOT_F16;
          norm_tile(4 + h, 1, tv);
          put_kv(h, 1, 1, tv);
          part(2 + h, 0, 2, 4);
          scale(2 + h, 1, 1.f);
          scale(h, 1, (l & 1) ? QSCALE / 128.f : 1.f);
          if (l & 1) {
            float n[2] = {0.f, 0.f};
#pragma unroll
            for (int i = 0; i < 16; i++) n[(i >> 1) & 1] = fmaf(acc[1][32 + 16 * h + i], acc[1][32 + 16 * h + i], n[(i >> 1) & 1]);
            const float a = ((qd & 1) ? n[1] : n[0]) + __shfl_xor_sync(~0u, (qd & 1) ? n[0] : n[1], 1);
            kn = f16_class(__reduce_max_sync(~0u, __float_as_uint(a + __shfl_xor_sync(~0u, a, 2))), K_LO);
            put_kn(h, 1, kn);
          }
          if (kn == NOT_F16) pack_b(2 + h, 1, t); else pack_h(2 + h, 1, t);
          put_kv(h, 0, 1, t);
          if (!(l & 1) && row0 == 176 && bm < 7) { send_halo(h, 0, t); send_halo(h, 1, tv); }
        };
        mbar_wait(sb + B_QE + 8, 1);
        wg_wait<1>();
        fence_regs(acc[1]);
        conv_tile1(0);
        part(3, 0, 0, 2);
        if (l & 1) { fence_async_smem(); bar_arrive(NB_ST, 288); }
        conv_tile1(1);
        wg_wait<2>();
        if (w == 0) e_arrive_both(sb + B_QE + 16);
        wg_wait<0>();
        fence_regs(acc[0]);
        if (w == 0) e_arrive_both(sb + B_QE + 24);
        bf16* const op0 = [&] { IDS(); return g_os + (size_t)(bm * 256 + row0 + (lane >> 2)) * 1024 + bn * 32 + (lane & 3) * 8; }();
        auto put_o = [&](int h, int m, const float (&o)[16], float i0, float i1) {
          bf16* op = op0 + m * 65536 + h * 512;
          const uint4 a = make_uint4(pack2(o[0] * i0, o[1] * i0), pack2(o[4] * i0, o[5] * i0), pack2(o[8] * i0, o[9] * i0), pack2(o[12] * i0, o[13] * i0));
          const uint4 c = make_uint4(pack2(o[2] * i1, o[3] * i1), pack2(o[6] * i1, o[7] * i1), pack2(o[10] * i1, o[11] * i1), pack2(o[14] * i1, o[15] * i1));
          *(uint4*)op = a; *(uint4*)(op + 8 * 1024) = c;
          const uint32_t hi = __vimax3_u16x2(__vimax3_u16x2(a.x, a.y, a.z), __vimax3_u16x2(a.w, c.x, c.y), __vmaxu2(c.z, c.w));
          const uint32_t lo = __vimax3_s16x2(__vimax3_s16x2(a.x, a.y, a.z), __vimax3_s16x2(a.w, c.x, c.y), __vmaxs2(c.z, c.w));
          return __vmaxu2(hi & 0x7FFF7FFFu, lo & 0x7FFF7FFFu);
        };
        if (!(l & 1)) {
          auto conv_kv = [&](int h) {
            uint32_t t[8];
            norm_tile(2 + h, 0, t); put_kv(h, 0, 0, t);
            norm_tile(4 + h, 0, t); put_kv(h, 1, 0, t);
          };
          conv_kv(0);
          norm_tile(0, 0, q[0][0]); pack_b(0, 1, q[0][1]);
          bar_sync(NB_SC, 256);
          const bool e = g & 1, sel = 2 * qd + (g & 1) >= g + 2, first = bm == 0 && row0 == 0;
          const uint32_t pm_a = e ? 0x1044 : 0x4410, pm_b = e ? 0x3244 : 0x4432, pm_lo = sel ? pm_b : 0x4444, pm_hi = sel ? 0x4444 : pm_b;
          const uint32_t ka = sb + (row0 + (lane & 7)) * 64 + (((lane >> 3) ^ ((lane >> 1) & 3)) << 4);
          const uint32_t va0 = sb + ASC + (row0 + srow) * 64 + (((lane >> 4) ^ ((lane >> 1) & 3)) << 4);
#pragma unroll 1
          for (int h = 0; h < 2; h++) {
            if (row0 == 0) bar_sync(NB_HALO + h, 64);
            float s[2][4][4];
            uint32_t vf[2][4][4], pf[2][2][4];
#pragma unroll
            for (int m = 0; m < 2; m++)
#pragma unroll
              for (int nt = 0; nt < 4; nt++) {
                uint32_t kf[4];
                ldsm4(ka + h * (2 * ASC) + (m * 64 + 8 * nt) * 64, kf);
                s[m][nt][0] = s[m][nt][1] = s[m][nt][2] = s[m][nt][3] = 0.f;
                mma16816(s[m][nt], q[0][m][0], q[0][m][1], q[0][m][2], q[0][m][3], kf[0], kf[1]);
                mma16816(s[m][nt], q[0][m][4], q[0][m][5], q[0][m][6], q[0][m][7], kf[2], kf[3]);
              }
#pragma unroll
            for (int m = 0; m < 2; m++)
#pragma unroll
              for (int i = 0; i < 4; i++) {
                ldsm4t(((va0 + h * (2 * ASC)) ^ (32 * (i & 1))) + (m * 64 + 16 * (i >> 1)) * 64, vf[m][i]);
              }
            float va[4], vb[4], mx[4];
            uint32_t ua[2], ub[2], um[2];
#pragma unroll
            for (int m = 0; m < 2; m++) {
              float a[2], c[2];
#pragma unroll
              for (int hh = 0; hh < 2; hh++) {
                a[hh] = e ? s[m][hh + 1][2 * hh + 1] : s[m][hh + 1][2 * hh];
                const float lo = e ? s[m][hh][2 * hh + 1] : s[m][hh][2 * hh], hi = e ? s[m][hh + 2][2 * hh + 1] : s[m][hh + 2][2 * hh];
                c[hh] = sel ? lo : hi;
              }
              ua[m] = scale_bf2(pack2(a[0], a[1])); ub[m] = scale_bf2(pack2(c[0], c[1]));
              if (m == 0) { ua[0] = first ? (ua[0] & 0xFFFF0000u) | 0xFF80u : ua[0]; ub[0] = first && sel ? 0xFF80FF80u : ub[0]; }
              um[m] = max_bf2(ua[m], ub[m]);
            }
#pragma unroll
            for (int m = 0; m < 2; m++) um[m] = max_bf2(um[m], __shfl_xor_sync(~0u, um[m], 1));
#pragma unroll
            for (int m = 0; m < 2; m++) um[m] = max_bf2(um[m], __shfl_xor_sync(~0u, um[m], 2));
#pragma unroll
            for (int i = 0; i < 4; i++) {
              const int m = i >> 1;
              const float top = (i & 1) ? bf_hi(um[m]) : bf_lo(um[m]);
              va[i] = ex2((((i & 1) ? bf_hi(ua[m]) : bf_lo(ua[m])) - top) * 1.4426950408889634f);
              vb[i] = ex2((((i & 1) ? bf_hi(ub[m]) : bf_lo(ub[m])) - top) * 1.4426950408889634f);
              mx[i] = va[i] + vb[i];
            }
#pragma unroll
            for (int i = 0; i < 4; i++) mx[i] += __shfl_xor_sync(~0u, mx[i], 1);
#pragma unroll
            for (int i = 0; i < 4; i++) mx[i] += __shfl_xor_sync(~0u, mx[i], 2);
#pragma unroll
            for (int i = 0; i < 4; i++) {
              const int m = i >> 1, hh = i & 1;
              const float inv = rcp(mx[i]);
              const uint32_t t = pack2(va[i] * inv, vb[i] * inv);
              pf[m][hh][hh + 1] = __byte_perm(t, 0, pm_a); pf[m][hh][hh] = __byte_perm(t, 0, pm_lo); pf[m][hh][hh + 2] = __byte_perm(t, 0, pm_hi); pf[m][hh][3 - 3 * hh] = t & zero;
            }
#pragma unroll
            for (int m = 0; m < 2; m++) {
              float o[4][4];
#pragma unroll
              for (int j = 0; j < 4; j++) o[j][0] = o[j][1] = o[j][2] = o[j][3] = 0.f;
#pragma unroll
              for (int i = 0; i < 4; i++) {
                const int kk = i >> 1, jj = 2 * (i & 1);
                mma16816(o[jj], pf[m][0][2 * kk], pf[m][1][2 * kk], pf[m][0][2 * kk + 1], pf[m][1][2 * kk + 1], vf[m][i][0], vf[m][i][1]);
                mma16816(o[jj + 1], pf[m][0][2 * kk], pf[m][1][2 * kk], pf[m][0][2 * kk + 1], pf[m][1][2 * kk + 1], vf[m][i][2], vf[m][i][3]);
              }
              const float of[16] = {o[0][0], o[0][1], o[0][2], o[0][3], o[1][0], o[1][1], o[1][2], o[1][3], o[2][0], o[2][1], o[2][2], o[2][3], o[3][0], o[3][1], o[3][2], o[3][3]};
              put_o(h, m, of, 1.f, 1.f);
            }
            bar_arrive(NB_SIG + 2 * h + wg, 160);
            if (h == 0) {
              conv_kv(1);
              norm_tile(1, 0, q[0][0]); pack_b(1, 1, q[0][1]);
              bar_sync(NB_SC, 256);
            }
          }
        } else {
          auto conv_h = [&](int gi, int m, uint32_t (&t)[8]) {
            pack_h(gi, m, t);
            float d0[4] = {0.f, 0.f, 0.f, 0.f}, d1[4] = {0.f, 0.f, 0.f, 0.f};
            if (gi == 2) {
              mma16816h(d0, t[0], t[1], t[2], t[3], t[0], t[2]); mma16816h(d1, t[0], t[1], t[2], t[3], t[1], t[3]);
              mma16816h(d0, t[4], t[5], t[6], t[7], t[4], t[6]); mma16816h(d1, t[4], t[5], t[6], t[7], t[5], t[7]);
            } else {
#pragma unroll
              for (int i = 0; i < 8; i += 2) { mma1688h(d0, t[i], t[i + 1], t[i]); mma1688h(d1, t[i], t[i + 1], t[i + 1]); }
            }
            return f16_class(__reduce_max_sync(~0u, max(max(__float_as_int(d0[0]), __float_as_int(d0[1])), max(__float_as_int(d1[2]), __float_as_int(d1[3])))), K_LO);
          };
          uint32_t tk[8], tv[8];
          scale(2, 0, 1.f);
          uint32_t kn = conv_h(2, 0, tk);
          norm_tile(4, 0, tv);
          put_kv(0, 1, 0, tv);
          put_kn(0, 0, kn);
          if (kn == NOT_F16) pack_b(2, 0, tk);
          put_kv(0, 0, 0, tk);
          fence_async_smem();
          bar_arrive(NB_KV, 288);
          mbar_wait(sb + B_QF + 24, 1);
          scale(3, 0, 1.f); scale(0, 0, QSCALE); scale(1, 0, QSCALE);
          kn = conv_h(3, 0, tk);
#pragma unroll
          for (int i = 0; i < 4; i++) qn[i >> 1][i & 1] = conv_h(i >> 1, i & 1, q[i >> 1][i & 1]);
          norm_tile(5, 0, tv);
          if (max(max(max(qn[0][0], qn[0][1]), max(qn[1][0], qn[1][1])), kn) == NOT_F16) {
#pragma unroll
            for (int i = 0; i < 4; i++) if (qn[i >> 1][i & 1] == NOT_F16) pack_b(i >> 1, i & 1, q[i >> 1][i & 1]);
            if (kn == NOT_F16) pack_b(3, 0, tk);
          }
          fence_regs(tv);
          const bool elected = w == 0 && lane == 0;
          uint32_t thr = elected ? 8 : 99;
          asm volatile("" : "+r"(thr));
          thr |= zero;
          uint2 cp;
          asm volatile("ld.shared.v2.u32 {%0, %1}, [%2];" : "=r"(cp.x), "=r"(cp.y) : "r"(sb + W_C));
          const uint64_t kd0 = mkdesc(sb + T0, 16, 512, 2);
          const uint64_t vd0 = mkdesc(sb + T0 + 16384, ONES - (T0 + 16384), 512, 2);
          const uint32_t v0 = (uint32_t)vd0 ^ zero;
          constexpr uint64_t VSTEP = 64 - (64ull << 16);
          float o[2][20], SA[2][16];
          uint32_t SB[2][8], PA[4], PB[4];
          auto qka = [&](int b, int k, uint64_t d, int h = 0) { wgmma_m64n32k16_rs_nb_h(SA[b], q[h][0][4 * k], q[h][0][4 * k + 1], q[h][0][4 * k + 2], q[h][0][4 * k + 3], d + 2 * k, k ? 1 : zero); };
          auto qkb = [&](int b, int k, uint64_t d, int h = 0) { wgmma_m64n32k16_rs_nb_hh(SB[b], q[h][1][4 * k], q[h][1][4 * k + 1], q[h][1][4 * k + 2], q[h][1][4 * k + 3], d + 2 * k, k ? 1 : zero); };
          auto qk = [&](int b, int k, uint64_t d, int h = 0) { qka(b, k, d, h); qkb(b, k, d, h); };
          auto pv = [&](int m, const uint32_t (&Px)[4], uint64_t vd, int keep = 1) { wgmma_m64n40k16_rs_tb(o[m], Px[0], Px[1], Px[2], Px[3], vd, keep); };
          mbar_wait(sb + B_TF, 0);
#pragma unroll
          for (int i = 0; i < 4; i++) PA[i] = PB[i] = zero;
          wg_fence();
          wgmma_m64n40k16_rs_tb_z(o[0], PA[0], PA[1], PA[2], PA[3], vd0, 0); wgmma_m64n40k16_rs_tb_z(o[1], PB[0], PB[1], PB[2], PB[3], vd0 + VSTEP, 0);
#pragma unroll
          for (int b = 1; b >= 0; b--) {
            wgmma_m64n32k16_rs_nb_z_h(SA[b], q[0][0][0], q[0][0][1], q[0][0][2], q[0][0][3], kd0 + 128 * b, 0);
            wgmma_m64n32k16_rs_nb_z_hh(SB[b], q[0][1][0], q[0][1][1], q[0][1][2], q[0][1][3], kd0 + 128 * b, 0);
          }
          qk(0, 1, kd0); wg_commit();
          put_kv(1, 1, 0, tv); put_kv(1, 0, 0, tk); put_kn(1, 0, kn);
          fence_async_smem();
          bar_arrive(NB_KV + 12, 288);
          wg_wait<0>();
          fence_regs(SA[0]); fence_regs(SB[0]); fence_regs(SA[1]); fence_regs(SB[1]); fence_regs(o[0]); fence_regs(o[1]);
#pragma unroll 1
          for (int pass = 0; pass < 2; pass++) {
            uint32_t kc = (uint32_t)kd0, vc = v0, vp = v0, pars = 0x78u | pass << 7;
#pragma unroll 1
            for (uint32_t it = 8; it <= 64; it += 8) {
              const uint32_t s8 = it & 24, par = pars & 1, kn = (uint32_t)kd0 + s8 * 256, tf = (sb + B_TF) ^ s8;
              const uint64_t hi = kd0 & 0xFFFFFFFF00000000ull, kd = hi | kc, vd = hi | vc, kdn = hi | kn, vdp = hi | vp;
              kc = kn; vp = vc + (uint32_t)(15 * VSTEP); vc = v0 + s8 * (uint32_t)(4 * VSTEP); pars >>= 1;
              bool landed = false;
#pragma unroll
              for (int r = 0; r < 16; r++) {
                const int c = r >> 1, ro = r & 1;
                if (r == 14 && !landed) mbar_wait(tf, par);
                wg_fence();
                const uint64_t kx = c < 7 ? kd + (c + 1) * 128 : kdn, vx = r ? vd + (r - 1) * VSTEP : vdp;
                const int keep = r || it != 8;
                if (ro) { qkb(~c & 1, 1, kx); pv(0, PA, vx, keep); pv(1, PB, vx, keep); qka(~c & 1, 1, kx); }
                else { pv(1, PB, vx, keep); qka(~c & 1, 0, kx); qkb(~c & 1, 0, kx); pv(0, PA, vx, keep); }
                wg_commit();
                if (r == 7) landed = mbar_test(tf, par);
#pragma unroll
                for (int i = 0; i < 4; i++) PB[i] = exp2_h2(SB[c & 1][4 * ro + i], (i & 1) ? cp.x : cp.y);
#pragma unroll
                for (int i = 0; i < 4; i++) { const float e0 = ex2(SA[c & 1][8 * ro + 2 * i]); PA[i] = pack2(e0, ex2(SA[c & 1][8 * ro + 2 * i + 1])); }
                if (ro) { wg_wait<0>(); fence_regs(SA[~c & 1]); fence_regs(SB[~c & 1]); } else wg_wait<1>();
                if (r == 5) arrive_if_gt(tf ^ 0x30, it, thr);
              }
            }
            int badm = 0;
            wg_fence();
            pv(0, PA, vd0 + 111 * VSTEP); pv(1, PB, vd0 + 111 * VSTEP); wg_commit();
            qk(0, 0, kd0, 1); qk(0, 1, kd0, 1); wg_commit();
            if (pass == 0) bar_sync(NB_KN + wg, 160);
            const float kmax = *(volatile float*)(smem + KMAX + 4 * pass);
            wg_wait<1>(); fence_regs(o[0]); fence_regs(o[1]);
            arrive_if_gt(sb + B_TE + 8 * 3, 9, thr);
#pragma unroll
            for (int m = 0; m < 2; m++) {
              const float of[16] = {o[m][0], o[m][1], o[m][2], o[m][3], o[m][4], o[m][5], o[m][6], o[m][7], o[m][8], o[m][9], o[m][10], o[m][11], o[m][12], o[m][13], o[m][14], o[m][15]};
              const uint32_t chk = put_o(pass, m, of, rcp(o[m][16]), rcp(o[m][18]));
              const bool bad = !(__uint_as_float(qn[0][m]) * kmax <= (m ? 0.875f * 0.875f : 112.f * 112.f)) || !(fminf(o[m][16], o[m][18]) >= 9.3e-10f) ||
                               !(o[m][16] + o[m][18] <= 3e38f) || ((chk + 0x00800080u) & 0x80008000u);
              badm |= __any_sync(~0u, bad) << m;
            }
            wg_wait<0>(); fence_regs(SA[0]); fence_regs(SB[0]);
            if (badm) {
#pragma unroll 1
              for (int m = 0; m < 2; m++) if ((badm >> m) & 1) {
                uint32_t qq[8]; float res[20];
#pragma unroll
                for (int i = 0; i < 8; i++) { qq[i] = m ? q[0][1][i] : q[0][0][i]; if ((m ? qn[0][1] : qn[0][0]) != NOT_F16) qq[i] = h2_to_bf2(qq[i]); }
                attn_slow(qq, m ? 128.f : 1.f, 2 * (cta_id() & 15) + pass, g_kn + ((l >> 1) * 128 + (cta_id() & 15) * 8) * 32 + 16 * pass, res, lane_id());
                const float of[16] = {res[0], res[1], res[2], res[3], res[4], res[5], res[6], res[7], res[8], res[9], res[10], res[11], res[12], res[13], res[14], res[15]};
                put_o(pass, m, of, rcp(res[16]), rcp(res[18]));
              }
            }
            bar_arrive(NB_SIG + 2 * pass + wg, 160);
            if (pass) break;
            qn[0][0] = qn[1][0]; qn[0][1] = qn[1][1];
#pragma unroll
            for (int m = 0; m < 2; m++)
#pragma unroll
              for (int i = 0; i < 8; i++) q[0][m][i] = q[1][m][i];
#pragma unroll
            for (int i = 0; i < 4; i++) PA[i] = PB[i] = zero;
          }
        }
      }
      {
        float acc[64];
#pragma unroll
        for (int i = 0; i < 64; i++) acc[i] = 0.f;
        fence_regs(acc);
        uint32_t s = 0, lap = 0;
#pragma unroll 1
        for (int kt = 0; kt < 16; kt++) {
          mbar_wait(sb + B_PF + 8 * s, ((s < 4 ? l : 0) + lap) & 1);
          const uint64_t da = mkdesc(sb + pslot_a(s, l) + wg * 8192, 16, 1024, 1), db = mkdesc(sb + pslot_b(s, l), 8192, 1024, 1);
          wg_fence();
#pragma unroll
          for (int k = 0; k < 4; k++) wgmma_m64n128k16_ss_tb(acc, da + k * 2, db + k * 128, 1);
          wg_commit();
          wg_wait<1>();
          if (kt > 0 && w == 0) e_arrive_both(sb + B_PE + 8 * (s ? s - 1 : 5));
          if (++s == 6) { s = 0; lap++; }
        }
        IDS();
        const int g = lane >> 2, qd = lane & 3;
        const int r0 = wg * 64 + w * 16;
        const uint32_t r = r0 + (lane & 7) + ((lane >> 3) & 1) * 8;
        const uint32_t xa = r * 128 + (((lane >> 4) ^ (lane & 7)) << 4);
        uint32_t x[8][4];
        mbar_wait(sb + B_RF, l & 1);
        mbar_wait(sb + B_PE + 8, l & 1);
#pragma unroll
        for (int jj = 0; jj < 8; jj++) ldsm4(sb + (jj >> 2) * 16384 + (xa ^ (32 * (jj & 3))), x[jj]);
        wg_wait<0>();
        fence_regs(acc);
        const CUtensorMap* mo = &prm.m[l == 3 ? M_OUT : M_XST];
#pragma unroll
        for (int jj = 0; jj < 8; jj++) {
#pragma unroll
          for (int i = 0; i < 4; i++) x[jj][i] = add_bf16x2(x[jj][i], pack2(acc[8 * jj + 2 * i], acc[8 * jj + 2 * i + 1]));
          stsm4(sb + (jj >> 2) * QSTG + po * 16384 + (xa ^ (32 * (jj & 3))), x[jj][0], x[jj][1], x[jj][2], x[jj][3]);
          if ((jj & 3) == 3) { fence_async_smem(); __syncwarp(); tma_st(mo, pn * 128 + (jj >> 2) * 64, pm * 128 + r0, sb + (jj >> 2) * QSTG + po * 16384 + r0 * 128); }
        }
        bulk_commit();
        if (w == 0) e_arrive_both(sb + B_PE + 8 * 3);
        if (l < 3) {
          float s1[4] = {0.f, 0.f, 0.f, 0.f}, s2[4][4];
#pragma unroll
          for (int i = 0; i < 16; i++) s2[i >> 2][i & 3] = 0.f;
#pragma unroll
          for (int jj = 0; jj < 8; jj++) {
            mma16816(s1, x[jj][0], x[jj][1], x[jj][2], x[jj][3], 0x3f803f80u, 0x3f803f80u);
#pragma unroll
            for (int i = 0; i < 4; i++) mma1688(s2[i], x[jj][i & 2], x[jj][i | 1], x[jj][i]);
          }
          if (qd == (g >> 1)) {
            float2* sp = g_stats + pn * 2048 + pm * 128 + r0 + g;
            sp[0] = make_float2(s1[0], (g & 1) ? s2[0][1] + s2[2][1] : s2[0][0] + s2[2][0]);
            sp[8] = make_float2(s1[2], (g & 1) ? s2[1][3] + s2[3][3] : s2[1][2] + s2[3][2]);
          }
          __syncwarp();
          bar_arrive(NB_X, 288);
        }
        bulk_wait_n<0>();
        if (l < 3) bar_arrive(NB_X0, 352);
      }
    }
  }
  asm volatile("barrier.cluster.arrive.relaxed.aligned;\nbarrier.cluster.wait.aligned;" ::: "memory");
}

typedef CUresult (*EncodeFn)(CUtensorMap*, CUtensorMapDataType, cuuint32_t, void*, const cuuint64_t*, const cuuint64_t*, const cuuint32_t*,
                             const cuuint32_t*, CUtensorMapInterleave, CUtensorMapSwizzle, CUtensorMapL2promotion, CUtensorMapFloatOOBfill);

static void make_map(EncodeFn fn, CUtensorMap* m, const void* ptr, int rank, const uint64_t* dims, const uint64_t* strides, const uint32_t* box, CUtensorMapSwizzle sw) {
  cuuint64_t d[5], st[4];
  cuuint32_t bx[5], es[5];
  for (int i = 0; i < rank; i++) { d[i] = dims[i]; bx[i] = box[i]; es[i] = 1; if (i) st[i - 1] = strides[i - 1] * 2; }
  fn(m, CU_TENSOR_MAP_DATA_TYPE_BFLOAT16, rank, (void*)ptr, d, st, bx, es, CU_TENSOR_MAP_INTERLEAVE_NONE, sw,
     CU_TENSOR_MAP_L2_PROMOTION_L2_128B, CU_TENSOR_MAP_FLOAT_OOB_FILL_NONE);
}
static void map2(EncodeFn fn, CUtensorMap* m, const void* ptr, uint64_t inner, uint64_t outer, uint32_t bi, uint32_t bo, CUtensorMapSwizzle sw) {
  const uint64_t d[2] = {inner, outer}, st[1] = {inner};
  const uint32_t bx[2] = {bi, bo};
  make_map(fn, m, ptr, 2, d, st, bx, sw);
}

extern "C" void kernel_launch(void* const* d_in, const int* in_sizes, int n_in, void* d_out, int out_size) {
  (void)in_sizes; (void)n_in; (void)out_size;
  static EncodeFn enc = nullptr;
  static void *xs, *os, *kk, *vv, *ep;
  if (!enc) {
    void* p = nullptr;
    cudaDriverEntryPointQueryResult qr;
    cudaGetDriverEntryPoint("cuTensorMapEncodeTiled", &p, cudaEnableDefault, &qr);
    enc = (EncodeFn)p;
    cudaGetSymbolAddress(&xs, g_xs); cudaGetSymbolAddress(&os, g_os); cudaGetSymbolAddress(&kk, g_k); cudaGetSymbolAddress(&vv, g_v); cudaGetSymbolAddress(&ep, g_epoch);
    cudaFuncSetAttribute(fused_kernel, cudaFuncAttributeMaxDynamicSharedMemorySize, SMEM_BYTES);
  }
  Params prm;
  const CUtensorMapSwizzle S128 = CU_TENSOR_MAP_SWIZZLE_128B, S64 = CU_TENSOR_MAP_SWIZZLE_64B;
  map2(enc, &prm.m[M_X0A], d_in[0], 1024, 2048, 64, 256, S128);
  map2(enc, &prm.m[M_XSA], xs, 1024, 2048, 64, 256, S128);
  for (int t = 0; t < 2; t++) {
    const uint64_t d3[3] = {1024, 1024, 3}, s3[2] = {3072, 1024};
    const uint32_t b3[3] = {64, 64, 3};
    make_map(enc, &prm.m[M_WQA + t], d_in[1 + 3 * t], 3, d3, s3, b3, S128);
    const uint64_t d5[5] = {64, 32, 2, 16, 16}, s5[4] = {1024, 32 * 1024, 64 * 1024, 64};
    const uint32_t b5[5] = {64, 32, 1, 2, 2};
    make_map(enc, &prm.m[M_WOA + t], d_in[2 + 3 * t], 5, d5, s5, b5, S128);
    const uint64_t dr[3] = {64, 2048, 16}, sr[2] = {1024, 64};
    const uint32_t br[3] = {64, 128, 2};
    make_map(enc, &prm.m[M_X0R + t], t ? xs : d_in[0], 3, dr, sr, br, S128);
  }
  map2(enc, &prm.m[M_OS], os, 1024, 2048, 64, 64, S128);
  map2(enc, &prm.m[M_K], kk, 32, 65536, 32, 256, S64);
  map2(enc, &prm.m[M_V], vv, 32, 65536, 32, 256, S64);
  map2(enc, &prm.m[M_K4], kk, 32, 65536, 32, 64, S64);
  map2(enc, &prm.m[M_V4], vv, 32, 65536, 32, 64, S64);
  map2(enc, &prm.m[M_XSO], xs, 1024, 2048, 64, 128, S128);
  map2(enc, &prm.m[M_X0H], d_in[0], 1024, 2048, 64, 128, S128);
  map2(enc, &prm.m[M_XST], xs, 1024, 2048, 64, 16, S128);
  map2(enc, &prm.m[M_OUT], d_out, 1024, 2048, 64, 16, S128);
  prm.x0 = (const bf16*)d_in[0];
  prm.wq[0] = (const bf16*)d_in[1]; prm.wq[1] = (const bf16*)d_in[4];
  prm.wo = (const bf16*)d_in[2];
  prm.epoch = (uint32_t*)ep;
  prm.zero = 0;
  for (int i = 0; i < 128; i++) prm.map[i] = remap(i);
  fused_kernel<<<128, 384, SMEM_BYTES>>>(prm);
}
```
